```python
import torch

def _softmax(x, axis=-1):
    return torch.softmax(x, dim=axis)
def _gelu(x):
    return torch.nn.functional.gelu(x, approximate="tanh")
def _silu(x):
    return torch.nn.functional.silu(x)
def _sigmoid(x):
    return torch.sigmoid(x)
def _layernorm(x, axis=-1, eps=1e-5):
    m = x.mean(dim=axis, keepdim=True)
    v = x.var(dim=axis, keepdim=True, unbiased=False)
    return (x - m) / torch.sqrt(v + eps)
def _scatter_add(tgt, idx, src, axis=0):
    return tgt.clone().index_add_(axis, idx, src)
def _segment_sum(src, seg, n):
    out = torch.zeros((n,) + src.shape[1:], dtype=src.dtype)
    return out.index_add_(0, seg, src)
def _pad(x, pw):
    flat = tuple(v for pair in reversed(pw) for v in pair)
    return torch.nn.functional.pad(x, flat)

kernel_name = 'sequential_preLN__linear_attn_block__dense_activation_gelu__prompt'

def setup_inputs():

    _w = (lambda a: (lambda t: t.to(torch.bfloat16) if t.is_floating_point() else t)(torch.as_tensor(a)))
    def _A_setup():
        B, S, D = 1, 2048, 640
        return {
            "x": _w((lambda *s: torch.randn(*s, dtype=torch.bfloat16) * 0.05)(B, S, D)),
            "wqkv": _w((lambda *s: torch.randn(*s, dtype=torch.bfloat16) * 0.05)(D, 3 * D)),
            "wo": _w((lambda *s: torch.randn(*s, dtype=torch.bfloat16) * 0.05)(D, D)),
        }
    _A_in = _A_setup()

    def _B_setup():
        B, S, D, F = 1, 2048, 640, 1536
        return {
            "x": _w((lambda *s: torch.randn(*s, dtype=torch.bfloat16) * 0.05)(B, S, D)),
            "w1": _w((lambda *s: torch.randn(*s, dtype=torch.bfloat16) * 0.8)(D, F) * (D ** -0.5)),
            "b1": _w((lambda *s: torch.randn(*s, dtype=torch.bfloat16) * 12.8)(F) * 0.01),
            "w2": _w((lambda *s: torch.randn(*s, dtype=torch.bfloat16) * 0.2)(F, D) * (F ** -0.5)),
            "b2": _w((lambda *s: torch.randn(*s, dtype=torch.bfloat16) * 3.2)(D) * 0.01),
        }
    _B_in = _B_setup()

    return {
        "A_x": _A_in["x"],
        "A_wqkv": _A_in["wqkv"],
        "A_wo": _A_in["wo"],
        "B_x": _B_in["x"],
        "B_w1": _B_in["w1"],
        "B_b1": _B_in["b1"],
        "B_w2": _B_in["w2"],
        "B_b2": _B_in["b2"],
    }

def reference(A_x, A_wqkv, A_wo, B_x, B_w1, B_b1, B_w2, B_b2):
    def _A_ref(x, wqkv, wo):
        B, S, D = x.shape
        H = 32; Dh = D // H
        qkv = (lambda x, *d: x.permute(*d))((x @ wqkv).reshape(B, S, 3, H, Dh), 2, 0, 3, 1, 4)
        q, k, v = qkv[0], qkv[1], qkv[2]
        phi = lambda t: torch.where(t > 0, t + 1, torch.exp(t)) + 1e-6
        pq, pk = phi(q), phi(k)
        kv = torch.einsum("bhsd,bhse->bhde", pk, v)
        z = torch.einsum("bhsd->bhd", pk)
        num = torch.einsum("bhqd,bhde->bhqe", pq, kv)
        den = torch.einsum("bhqd,bhd->bhq", pq, z)[..., None] + 1e-6
        o = num / den
        return (lambda x, *d: x.permute(*d))(o, 0, 2, 1, 3).reshape(B, S, D) @ wo

    def _B_ref(x, w1, b1, w2, b2):
        h = torch.einsum("bsd,df->bsf", x, w1) + b1
        h = _gelu(h)
        return torch.einsum("bsf,fd->bsd", h, w2) + b2

    x = A_x
    h = x + _A_ref(_layernorm(x, axis=-1), A_wqkv, A_wo)
    h2 = h + _B_ref(_layernorm(h, axis=-1), B_w1, B_b1, B_w2, B_b2)
    return h2
```

```cpp
#include <cuda_runtime.h>
#include <cuda_bf16.h>
#include <cuda.h>
#include <stdint.h>

namespace {

template <int TA, int TB> __device__ __forceinline__ void wgmma_ss_n48(float (&d)[24], uint64_t da, uint64_t db, int sc) {
  asm volatile("{.reg .pred p; setp.ne.b32 p, %26, 0; wgmma.mma_async.sync.aligned.m64n48k16.f32.bf16.bf16 {%0,%1,%2,%3,%4,%5,%6,%7,%8,%9,%10,%11,%12,%13,%14,%15,%16,%17,%18,%19,%20,%21,%22,%23}, %24, %25, p, 1, 1, %27, %28;}"
    : "+f"(d[0]),"+f"(d[1]),"+f"(d[2]),"+f"(d[3]),"+f"(d[4]),"+f"(d[5]),"+f"(d[6]),"+f"(d[7]),"+f"(d[8]),"+f"(d[9]),"+f"(d[10]),"+f"(d[11]),"+f"(d[12]),"+f"(d[13]),"+f"(d[14]),"+f"(d[15]),"+f"(d[16]),"+f"(d[17]),"+f"(d[18]),"+f"(d[19]),"+f"(d[20]),"+f"(d[21]),"+f"(d[22]),"+f"(d[23])
    : "l"(da), "l"(db), "r"(sc), "n"(TA), "n"(TB));
}
template <int TA, int TB> __device__ __forceinline__ void wgmma_ss_n80(float (&d)[40], uint64_t da, uint64_t db, int sc) {
  asm volatile("{.reg .pred p; setp.ne.b32 p, %42, 0; wgmma.mma_async.sync.aligned.m64n80k16.f32.bf16.bf16 {%0,%1,%2,%3,%4,%5,%6,%7,%8,%9,%10,%11,%12,%13,%14,%15,%16,%17,%18,%19,%20,%21,%22,%23,%24,%25,%26,%27,%28,%29,%30,%31,%32,%33,%34,%35,%36,%37,%38,%39}, %40, %41, p, 1, 1, %43, %44;}"
    : "+f"(d[0]),"+f"(d[1]),"+f"(d[2]),"+f"(d[3]),"+f"(d[4]),"+f"(d[5]),"+f"(d[6]),"+f"(d[7]),"+f"(d[8]),"+f"(d[9]),"+f"(d[10]),"+f"(d[11]),"+f"(d[12]),"+f"(d[13]),"+f"(d[14]),"+f"(d[15]),"+f"(d[16]),"+f"(d[17]),"+f"(d[18]),"+f"(d[19]),"+f"(d[20]),"+f"(d[21]),"+f"(d[22]),"+f"(d[23]),"+f"(d[24]),"+f"(d[25]),"+f"(d[26]),"+f"(d[27]),"+f"(d[28]),"+f"(d[29]),"+f"(d[30]),"+f"(d[31]),"+f"(d[32]),"+f"(d[33]),"+f"(d[34]),"+f"(d[35]),"+f"(d[36]),"+f"(d[37]),"+f"(d[38]),"+f"(d[39])
    : "l"(da), "l"(db), "r"(sc), "n"(TA), "n"(TB));
}
template <int TA, int TB> __device__ __forceinline__ void wgmma_ss_n160(float (&d)[80], uint64_t da, uint64_t db, int sc) {
  asm volatile("{.reg .pred p; setp.ne.b32 p, %82, 0; wgmma.mma_async.sync.aligned.m64n160k16.f32.bf16.bf16 {%0,%1,%2,%3,%4,%5,%6,%7,%8,%9,%10,%11,%12,%13,%14,%15,%16,%17,%18,%19,%20,%21,%22,%23,%24,%25,%26,%27,%28,%29,%30,%31,%32,%33,%34,%35,%36,%37,%38,%39,%40,%41,%42,%43,%44,%45,%46,%47,%48,%49,%50,%51,%52,%53,%54,%55,%56,%57,%58,%59,%60,%61,%62,%63,%64,%65,%66,%67,%68,%69,%70,%71,%72,%73,%74,%75,%76,%77,%78,%79}, %80, %81, p, 1, 1, %83, %84;}"
    : "+f"(d[0]),"+f"(d[1]),"+f"(d[2]),"+f"(d[3]),"+f"(d[4]),"+f"(d[5]),"+f"(d[6]),"+f"(d[7]),"+f"(d[8]),"+f"(d[9]),"+f"(d[10]),"+f"(d[11]),"+f"(d[12]),"+f"(d[13]),"+f"(d[14]),"+f"(d[15]),"+f"(d[16]),"+f"(d[17]),"+f"(d[18]),"+f"(d[19]),"+f"(d[20]),"+f"(d[21]),"+f"(d[22]),"+f"(d[23]),"+f"(d[24]),"+f"(d[25]),"+f"(d[26]),"+f"(d[27]),"+f"(d[28]),"+f"(d[29]),"+f"(d[30]),"+f"(d[31]),"+f"(d[32]),"+f"(d[33]),"+f"(d[34]),"+f"(d[35]),"+f"(d[36]),"+f"(d[37]),"+f"(d[38]),"+f"(d[39]),"+f"(d[40]),"+f"(d[41]),"+f"(d[42]),"+f"(d[43]),"+f"(d[44]),"+f"(d[45]),"+f"(d[46]),"+f"(d[47]),"+f"(d[48]),"+f"(d[49]),"+f"(d[50]),"+f"(d[51]),"+f"(d[52]),"+f"(d[53]),"+f"(d[54]),"+f"(d[55]),"+f"(d[56]),"+f"(d[57]),"+f"(d[58]),"+f"(d[59]),"+f"(d[60]),"+f"(d[61]),"+f"(d[62]),"+f"(d[63]),"+f"(d[64]),"+f"(d[65]),"+f"(d[66]),"+f"(d[67]),"+f"(d[68]),"+f"(d[69]),"+f"(d[70]),"+f"(d[71]),"+f"(d[72]),"+f"(d[73]),"+f"(d[74]),"+f"(d[75]),"+f"(d[76]),"+f"(d[77]),"+f"(d[78]),"+f"(d[79])
    : "l"(da), "l"(db), "r"(sc), "n"(TA), "n"(TB));
}
template <int TA, int TB> __device__ __forceinline__ void wgmma_ss_n192(float (&d)[96], uint64_t da, uint64_t db, int sc) {
  asm volatile("{.reg .pred p; setp.ne.b32 p, %98, 0; wgmma.mma_async.sync.aligned.m64n192k16.f32.bf16.bf16 {%0,%1,%2,%3,%4,%5,%6,%7,%8,%9,%10,%11,%12,%13,%14,%15,%16,%17,%18,%19,%20,%21,%22,%23,%24,%25,%26,%27,%28,%29,%30,%31,%32,%33,%34,%35,%36,%37,%38,%39,%40,%41,%42,%43,%44,%45,%46,%47,%48,%49,%50,%51,%52,%53,%54,%55,%56,%57,%58,%59,%60,%61,%62,%63,%64,%65,%66,%67,%68,%69,%70,%71,%72,%73,%74,%75,%76,%77,%78,%79,%80,%81,%82,%83,%84,%85,%86,%87,%88,%89,%90,%91,%92,%93,%94,%95}, %96, %97, p, 1, 1, %99, %100;}"
    : "+f"(d[0]),"+f"(d[1]),"+f"(d[2]),"+f"(d[3]),"+f"(d[4]),"+f"(d[5]),"+f"(d[6]),"+f"(d[7]),"+f"(d[8]),"+f"(d[9]),"+f"(d[10]),"+f"(d[11]),"+f"(d[12]),"+f"(d[13]),"+f"(d[14]),"+f"(d[15]),"+f"(d[16]),"+f"(d[17]),"+f"(d[18]),"+f"(d[19]),"+f"(d[20]),"+f"(d[21]),"+f"(d[22]),"+f"(d[23]),"+f"(d[24]),"+f"(d[25]),"+f"(d[26]),"+f"(d[27]),"+f"(d[28]),"+f"(d[29]),"+f"(d[30]),"+f"(d[31]),"+f"(d[32]),"+f"(d[33]),"+f"(d[34]),"+f"(d[35]),"+f"(d[36]),"+f"(d[37]),"+f"(d[38]),"+f"(d[39]),"+f"(d[40]),"+f"(d[41]),"+f"(d[42]),"+f"(d[43]),"+f"(d[44]),"+f"(d[45]),"+f"(d[46]),"+f"(d[47]),"+f"(d[48]),"+f"(d[49]),"+f"(d[50]),"+f"(d[51]),"+f"(d[52]),"+f"(d[53]),"+f"(d[54]),"+f"(d[55]),"+f"(d[56]),"+f"(d[57]),"+f"(d[58]),"+f"(d[59]),"+f"(d[60]),"+f"(d[61]),"+f"(d[62]),"+f"(d[63]),"+f"(d[64]),"+f"(d[65]),"+f"(d[66]),"+f"(d[67]),"+f"(d[68]),"+f"(d[69]),"+f"(d[70]),"+f"(d[71]),"+f"(d[72]),"+f"(d[73]),"+f"(d[74]),"+f"(d[75]),"+f"(d[76]),"+f"(d[77]),"+f"(d[78]),"+f"(d[79]),"+f"(d[80]),"+f"(d[81]),"+f"(d[82]),"+f"(d[83]),"+f"(d[84]),"+f"(d[85]),"+f"(d[86]),"+f"(d[87]),"+f"(d[88]),"+f"(d[89]),"+f"(d[90]),"+f"(d[91]),"+f"(d[92]),"+f"(d[93]),"+f"(d[94]),"+f"(d[95])
    : "l"(da), "l"(db), "r"(sc), "n"(TA), "n"(TB));
}
template <int TB> __device__ __forceinline__ void wgmma_rs_n96(float (&d)[48], uint32_t a0, uint32_t a1, uint32_t a2, uint32_t a3, uint64_t db, int sc) {
  asm volatile("{.reg .pred p; setp.ne.b32 p, %53, 0; wgmma.mma_async.sync.aligned.m64n96k16.f32.bf16.bf16 {%0,%1,%2,%3,%4,%5,%6,%7,%8,%9,%10,%11,%12,%13,%14,%15,%16,%17,%18,%19,%20,%21,%22,%23,%24,%25,%26,%27,%28,%29,%30,%31,%32,%33,%34,%35,%36,%37,%38,%39,%40,%41,%42,%43,%44,%45,%46,%47}, {%48,%49,%50,%51}, %52, p, 1, 1, %54;}"
    : "+f"(d[0]),"+f"(d[1]),"+f"(d[2]),"+f"(d[3]),"+f"(d[4]),"+f"(d[5]),"+f"(d[6]),"+f"(d[7]),"+f"(d[8]),"+f"(d[9]),"+f"(d[10]),"+f"(d[11]),"+f"(d[12]),"+f"(d[13]),"+f"(d[14]),"+f"(d[15]),"+f"(d[16]),"+f"(d[17]),"+f"(d[18]),"+f"(d[19]),"+f"(d[20]),"+f"(d[21]),"+f"(d[22]),"+f"(d[23]),"+f"(d[24]),"+f"(d[25]),"+f"(d[26]),"+f"(d[27]),"+f"(d[28]),"+f"(d[29]),"+f"(d[30]),"+f"(d[31]),"+f"(d[32]),"+f"(d[33]),"+f"(d[34]),"+f"(d[35]),"+f"(d[36]),"+f"(d[37]),"+f"(d[38]),"+f"(d[39]),"+f"(d[40]),"+f"(d[41]),"+f"(d[42]),"+f"(d[43]),"+f"(d[44]),"+f"(d[45]),"+f"(d[46]),"+f"(d[47])
    : "r"(a0), "r"(a1), "r"(a2), "r"(a3), "l"(db), "r"(sc), "n"(TB));
}
template <int TB> __device__ __forceinline__ void wgmma_rs_n160(float (&d)[80], uint32_t a0, uint32_t a1, uint32_t a2, uint32_t a3, uint64_t db, int sc) {
  asm volatile("{.reg .pred p; setp.ne.b32 p, %85, 0; wgmma.mma_async.sync.aligned.m64n160k16.f32.bf16.bf16 {%0,%1,%2,%3,%4,%5,%6,%7,%8,%9,%10,%11,%12,%13,%14,%15,%16,%17,%18,%19,%20,%21,%22,%23,%24,%25,%26,%27,%28,%29,%30,%31,%32,%33,%34,%35,%36,%37,%38,%39,%40,%41,%42,%43,%44,%45,%46,%47,%48,%49,%50,%51,%52,%53,%54,%55,%56,%57,%58,%59,%60,%61,%62,%63,%64,%65,%66,%67,%68,%69,%70,%71,%72,%73,%74,%75,%76,%77,%78,%79}, {%80,%81,%82,%83}, %84, p, 1, 1, %86;}"
    : "+f"(d[0]),"+f"(d[1]),"+f"(d[2]),"+f"(d[3]),"+f"(d[4]),"+f"(d[5]),"+f"(d[6]),"+f"(d[7]),"+f"(d[8]),"+f"(d[9]),"+f"(d[10]),"+f"(d[11]),"+f"(d[12]),"+f"(d[13]),"+f"(d[14]),"+f"(d[15]),"+f"(d[16]),"+f"(d[17]),"+f"(d[18]),"+f"(d[19]),"+f"(d[20]),"+f"(d[21]),"+f"(d[22]),"+f"(d[23]),"+f"(d[24]),"+f"(d[25]),"+f"(d[26]),"+f"(d[27]),"+f"(d[28]),"+f"(d[29]),"+f"(d[30]),"+f"(d[31]),"+f"(d[32]),"+f"(d[33]),"+f"(d[34]),"+f"(d[35]),"+f"(d[36]),"+f"(d[37]),"+f"(d[38]),"+f"(d[39]),"+f"(d[40]),"+f"(d[41]),"+f"(d[42]),"+f"(d[43]),"+f"(d[44]),"+f"(d[45]),"+f"(d[46]),"+f"(d[47]),"+f"(d[48]),"+f"(d[49]),"+f"(d[50]),"+f"(d[51]),"+f"(d[52]),"+f"(d[53]),"+f"(d[54]),"+f"(d[55]),"+f"(d[56]),"+f"(d[57]),"+f"(d[58]),"+f"(d[59]),"+f"(d[60]),"+f"(d[61]),"+f"(d[62]),"+f"(d[63]),"+f"(d[64]),"+f"(d[65]),"+f"(d[66]),"+f"(d[67]),"+f"(d[68]),"+f"(d[69]),"+f"(d[70]),"+f"(d[71]),"+f"(d[72]),"+f"(d[73]),"+f"(d[74]),"+f"(d[75]),"+f"(d[76]),"+f"(d[77]),"+f"(d[78]),"+f"(d[79])
    : "r"(a0), "r"(a1), "r"(a2), "r"(a3), "l"(db), "r"(sc), "n"(TB));
}
template <int TB> __device__ __forceinline__ void wgmma_rs_n192(float (&d)[96], uint32_t a0, uint32_t a1, uint32_t a2, uint32_t a3, uint64_t db, int sc) {
  asm volatile("{.reg .pred p; setp.ne.b32 p, %101, 0; wgmma.mma_async.sync.aligned.m64n192k16.f32.bf16.bf16 {%0,%1,%2,%3,%4,%5,%6,%7,%8,%9,%10,%11,%12,%13,%14,%15,%16,%17,%18,%19,%20,%21,%22,%23,%24,%25,%26,%27,%28,%29,%30,%31,%32,%33,%34,%35,%36,%37,%38,%39,%40,%41,%42,%43,%44,%45,%46,%47,%48,%49,%50,%51,%52,%53,%54,%55,%56,%57,%58,%59,%60,%61,%62,%63,%64,%65,%66,%67,%68,%69,%70,%71,%72,%73,%74,%75,%76,%77,%78,%79,%80,%81,%82,%83,%84,%85,%86,%87,%88,%89,%90,%91,%92,%93,%94,%95}, {%96,%97,%98,%99}, %100, p, 1, 1, %102;}"
    : "+f"(d[0]),"+f"(d[1]),"+f"(d[2]),"+f"(d[3]),"+f"(d[4]),"+f"(d[5]),"+f"(d[6]),"+f"(d[7]),"+f"(d[8]),"+f"(d[9]),"+f"(d[10]),"+f"(d[11]),"+f"(d[12]),"+f"(d[13]),"+f"(d[14]),"+f"(d[15]),"+f"(d[16]),"+f"(d[17]),"+f"(d[18]),"+f"(d[19]),"+f"(d[20]),"+f"(d[21]),"+f"(d[22]),"+f"(d[23]),"+f"(d[24]),"+f"(d[25]),"+f"(d[26]),"+f"(d[27]),"+f"(d[28]),"+f"(d[29]),"+f"(d[30]),"+f"(d[31]),"+f"(d[32]),"+f"(d[33]),"+f"(d[34]),"+f"(d[35]),"+f"(d[36]),"+f"(d[37]),"+f"(d[38]),"+f"(d[39]),"+f"(d[40]),"+f"(d[41]),"+f"(d[42]),"+f"(d[43]),"+f"(d[44]),"+f"(d[45]),"+f"(d[46]),"+f"(d[47]),"+f"(d[48]),"+f"(d[49]),"+f"(d[50]),"+f"(d[51]),"+f"(d[52]),"+f"(d[53]),"+f"(d[54]),"+f"(d[55]),"+f"(d[56]),"+f"(d[57]),"+f"(d[58]),"+f"(d[59]),"+f"(d[60]),"+f"(d[61]),"+f"(d[62]),"+f"(d[63]),"+f"(d[64]),"+f"(d[65]),"+f"(d[66]),"+f"(d[67]),"+f"(d[68]),"+f"(d[69]),"+f"(d[70]),"+f"(d[71]),"+f"(d[72]),"+f"(d[73]),"+f"(d[74]),"+f"(d[75]),"+f"(d[76]),"+f"(d[77]),"+f"(d[78]),"+f"(d[79]),"+f"(d[80]),"+f"(d[81]),"+f"(d[82]),"+f"(d[83]),"+f"(d[84]),"+f"(d[85]),"+f"(d[86]),"+f"(d[87]),"+f"(d[88]),"+f"(d[89]),"+f"(d[90]),"+f"(d[91]),"+f"(d[92]),"+f"(d[93]),"+f"(d[94]),"+f"(d[95])
    : "r"(a0), "r"(a1), "r"(a2), "r"(a3), "l"(db), "r"(sc), "n"(TB));
}
template <int N, int TA, int TB> __device__ __forceinline__ void wgmma_ss(float (&d)[N / 2], uint64_t da, uint64_t db, int sc) {
  if constexpr (N == 48) wgmma_ss_n48<TA, TB>(d, da, db, sc);
  else if constexpr (N == 80) wgmma_ss_n80<TA, TB>(d, da, db, sc);
  else if constexpr (N == 160) wgmma_ss_n160<TA, TB>(d, da, db, sc);
  else if constexpr (N == 192) wgmma_ss_n192<TA, TB>(d, da, db, sc);
}
template <int N, int TB> __device__ __forceinline__ void wgmma_rs(float (&d)[N / 2], uint32_t a0, uint32_t a1, uint32_t a2, uint32_t a3, uint64_t db, int sc) {
  if constexpr (N == 96) wgmma_rs_n96<TB>(d, a0, a1, a2, a3, db, sc);
  else if constexpr (N == 160) wgmma_rs_n160<TB>(d, a0, a1, a2, a3, db, sc);
  else if constexpr (N == 192) wgmma_rs_n192<TB>(d, a0, a1, a2, a3, db, sc);
}

constexpr uint32_t PAGE = 10240;
constexpr uint32_t OFF_RING = 16 * PAGE;
constexpr uint32_t OFF_KVB = 5 * PAGE;
constexpr uint32_t OFF_R1 = 35840;
constexpr uint32_t OFF_MISC = 22 * PAGE;
constexpr uint32_t OFF_BAR = OFF_MISC;
constexpr uint32_t OFF_LN1 = OFF_MISC + 2048;
constexpr uint32_t OFF_CSKV = OFF_MISC + 3072;
constexpr uint32_t OFF_CSQ = OFF_MISC + 3712;
constexpr uint32_t OFF_CB1 = OFF_MISC + 4032;
constexpr uint32_t OFF_B2 = OFF_MISC + 5568;
constexpr uint32_t OFF_RED = OFF_MISC + 5888;
constexpr uint32_t OFF_EPOCH = OFF_MISC + 6400;
constexpr uint32_t SMEM_BYTES = OFF_MISC + 6416;

enum : int {
  FX = 0, FKV = 10, FQ = 30, FWO = 38, FW1 = 46, FW2 = 54, FO = 66, FH = 82, FF = 98,
  SO = 122, SH = 124, SF = 126, RX = 132, RXK = 134,
  N_CNT1 = 135,
  DKV = 135, DQ = 155, DW = 163, DF = 179, DG = 195,
  RO = 219, RH = 221, RF = 223, SIDE = 229, KVB = 230, PQ0 = 231,
  N_CNT4 = 232,
  PF = 232,
  N_BARS = 234
};

__device__ uint32_t g_epoch;
__device__ uint4 g_ln1[2048];
__device__ uint2 g_cs[3456];
__device__ __align__(128) float g_kv[8 * 80 * 24];
__device__ __align__(128) uint32_t g_flag_z[8 * 32];
__device__ __align__(128) uint32_t g_flag_kv[8 * 32];
__device__ __align__(128) uint32_t g_flag_o[32 * 32];
__device__ __align__(128) uint32_t g_flag_h[32 * 32];
__device__ __align__(128) uint32_t g_flag_f[32 * 32];
__device__ __align__(128) uint8_t g_o[32 * 8 * 10240];
__device__ __align__(128) uint8_t g_h[32 * 8 * 10240];
__device__ __align__(128) uint8_t g_f[32 * 8 * 24576];
__device__ __align__(128) float2 g_hstat[32 * 8 * 64];

#define TL(id)
#define TLW(id)

constexpr int SPIN_LIMIT = 1 << 19;

__device__ __forceinline__ bool elect_one() {
  uint32_t p;
  asm volatile("{.reg .pred P; elect.sync _|P, 0xffffffff; selp.u32 %0,1,0,P;}" : "=r"(p));
  return p;
}
__device__ __forceinline__ void mbar_wait(uint32_t bar) {
  asm volatile("{.reg .pred p; .reg .u32 n; mov.u32 n, 0;\n"
               "W: mbarrier.try_wait.parity.shared::cta.b64 p, [%0], 0;\n"
               "@p bra D; add.u32 n, n, 1; setp.gt.u32 p, n, %1; @p trap; bra W;\n"
               "D: }" ::"r"(bar), "n"(SPIN_LIMIT) : "memory");
}
__device__ __forceinline__ void mbar_wait_cluster(uint32_t bar) {
  asm volatile("{.reg .pred p; .reg .u32 n; mov.u32 n, 0;\n"
               "W: mbarrier.try_wait.parity.acquire.cluster.shared::cta.b64 p, [%0], 0;\n"
               "@p bra D; add.u32 n, n, 1; setp.gt.u32 p, n, %1; @p trap; bra W;\n"
               "D: }" ::"r"(bar), "n"(SPIN_LIMIT) : "memory");
}
__device__ __forceinline__ void mbar_arrive(uint32_t bar) {
  asm volatile("mbarrier.arrive.shared::cta.b64 _, [%0];" ::"r"(bar) : "memory");
}
__device__ __forceinline__ void mbar_arrive_remote(uint32_t bar) {
  asm volatile("mbarrier.arrive.shared::cluster.b64 _, [%0];" ::"r"(bar) : "memory");
}
__device__ __forceinline__ void mbar_expect(uint32_t bar, uint32_t bytes) {
  asm volatile("mbarrier.arrive.expect_tx.shared::cta.b64 _, [%0], %1;" ::"r"(bar), "r"(bytes) : "memory");
}
__device__ __forceinline__ void tma2d(uint32_t dst, const CUtensorMap* tm, uint32_t bar, int c0, int c1) {
  asm volatile("cp.async.bulk.tensor.2d.shared::cluster.global.mbarrier::complete_tx::bytes [%0],[%1,{%3,%4}],[%2];"
               ::"r"(dst), "l"(tm), "r"(bar), "r"(c0), "r"(c1) : "memory");
}
__device__ __forceinline__ void tma3d(uint32_t dst, const CUtensorMap* tm, uint32_t bar, int c0, int c1, int c2) {
  asm volatile("cp.async.bulk.tensor.3d.shared::cluster.global.mbarrier::complete_tx::bytes [%0],[%1,{%3,%4,%5}],[%2];"
               ::"r"(dst), "l"(tm), "r"(bar), "r"(c0), "r"(c1), "r"(c2) : "memory");
}
__device__ __forceinline__ void bulk_load(uint32_t dst, const void* src, uint32_t bytes, uint32_t bar) {
  asm volatile("cp.async.bulk.shared::cluster.global.mbarrier::complete_tx::bytes [%0],[%1],%2,[%3];"
               ::"r"(dst), "l"(src), "r"(bytes), "r"(bar) : "memory");
}
__device__ __forceinline__ void bulk_store(void* dst, uint32_t src, uint32_t bytes) {
  asm volatile("cp.async.bulk.global.shared::cta.bulk_group [%0],[%1],%2;" ::"l"(dst), "r"(src), "r"(bytes) : "memory");
}
__device__ __forceinline__ void bulk_commit_wait() {
  asm volatile("cp.async.bulk.commit_group;" ::: "memory");
  asm volatile("cp.async.bulk.wait_group 0;" ::: "memory");
}
__device__ __forceinline__ void l2_prefetch(const void* src, uint32_t bytes) {
  asm volatile("cp.async.bulk.prefetch.L2.global [%0], %1;" ::"l"(src), "r"(bytes) : "memory");
}
__device__ __forceinline__ void fence_gpu() { asm volatile("fence.acq_rel.gpu;" ::: "memory"); }
__device__ __forceinline__ void fence_async_smem() { asm volatile("fence.proxy.async.shared::cta;" ::: "memory"); }
__device__ __forceinline__ void fence_async_global() { asm volatile("fence.proxy.async.global;" ::: "memory"); }
__device__ __forceinline__ void st_flag(uint32_t* p, uint32_t v) {
  asm volatile("st.relaxed.gpu.global.u32 [%0], %1;" ::"l"(p), "r"(v) : "memory");
}
__device__ __forceinline__ uint32_t ld_acq(const uint32_t* p) {
  uint32_t v;
  asm volatile("ld.acquire.gpu.global.u32 %0, [%1];" : "=r"(v) : "l"(p) : "memory");
  return v;
}
__device__ __forceinline__ void wg_fence() { asm volatile("wgmma.fence.sync.aligned;" ::: "memory"); }
__device__ __forceinline__ void wg_commit() { asm volatile("wgmma.commit_group.sync.aligned;" ::: "memory"); }
template <int N> __device__ __forceinline__ void wg_wait() { asm volatile("wgmma.wait_group.sync.aligned %0;" ::"n"(N) : "memory"); }
template <int N> __device__ __forceinline__ void reg_fence(float (&a)[N]) {
#pragma unroll
  for (int i = 0; i < N; i++) asm volatile("" : "+f"(a[i])::"memory");
}
__device__ __forceinline__ void named_bar(int id) { asm volatile("bar.sync %0, 128;" ::"r"(id) : "memory"); }
__device__ __forceinline__ uint64_t mkdesc(uint32_t addr, uint32_t lbo, uint32_t sbo, uint32_t swz) {
  return (uint64_t)(((addr & 0x3FFFF) >> 4) | ((lbo >> 4) << 16)) | ((uint64_t)((sbo >> 4) | (swz << 30)) << 32);
}
__device__ __forceinline__ uint32_t pack2(float lo, float hi) {
  uint32_t r;
  asm("cvt.rn.bf16x2.f32 %0, %1, %2;" : "=r"(r) : "f"(hi), "f"(lo));
  return r;
}
__device__ __forceinline__ float bf_lo(uint32_t v) { return __uint_as_float(v << 16); }
__device__ __forceinline__ float bf_hi(uint32_t v) { return __uint_as_float(v & 0xffff0000u); }
__device__ __forceinline__ void stsm4(uint32_t addr, uint32_t a, uint32_t b, uint32_t c, uint32_t d) {
  asm volatile("stmatrix.sync.aligned.m8n8.x4.shared.b16 [%0], {%1,%2,%3,%4};" ::"r"(addr), "r"(a), "r"(b), "r"(c), "r"(d) : "memory");
}
__device__ __forceinline__ float2 lds64(uint32_t a) {
  float2 v;
  asm volatile("ld.shared.v2.f32 {%0,%1}, [%2];" : "=f"(v.x), "=f"(v.y) : "r"(a) : "memory");
  return v;
}
__device__ __forceinline__ float4 lds128(uint32_t a) {
  float4 v;
  asm volatile("ld.shared.v4.f32 {%0,%1,%2,%3}, [%4];" : "=f"(v.x), "=f"(v.y), "=f"(v.z), "=f"(v.w) : "r"(a) : "memory");
  return v;
}
__device__ __forceinline__ uint32_t lds32(uint32_t a) {
  uint32_t v;
  asm volatile("ld.shared.u32 %0, [%1];" : "=r"(v) : "r"(a) : "memory");
  return v;
}
__device__ __forceinline__ void sts32(uint32_t a, uint32_t v) { asm volatile("st.shared.u32 [%0], %1;" ::"r"(a), "r"(v) : "memory"); }
__device__ __forceinline__ void sts64(uint32_t a, uint32_t x, uint32_t y) {
  asm volatile("st.shared.v2.u32 [%0], {%1,%2};" ::"r"(a), "r"(x), "r"(y) : "memory");
}
__device__ __forceinline__ void sts128(uint32_t a, uint32_t x, uint32_t y, uint32_t z, uint32_t w) {
  asm volatile("st.shared.v4.u32 [%0], {%1,%2,%3,%4};" ::"r"(a), "r"(x), "r"(y), "r"(z), "r"(w) : "memory");
}
__device__ __forceinline__ float ex2(float x) {
  float r;
  asm("ex2.approx.ftz.f32 %0, %1;" : "=f"(r) : "f"(x));
  return r;
}
__device__ __forceinline__ float rcp(float x) {
  float r;
  asm("rcp.approx.ftz.f32 %0, %1;" : "=f"(r) : "f"(x));
  return r;
}
constexpr float LOG2E = 1.4426950408889634f, LN2 = 0.6931471805599453f;
__device__ __forceinline__ float phi2(float t2) { return fmaf(fmaxf(t2, 0.f), LN2, ex2(fminf(t2, 0.f))) + 1e-6f; }
__device__ __forceinline__ float gelu(float y) {
  float p = fmaf(y * y, 0.044715f * 0.7978845608028654f, 0.7978845608028654f);
  float th;
  asm("tanh.approx.f32 %0, %1;" : "=f"(th) : "f"(y * p));
  float hy = 0.5f * y;
  return fmaf(hy, th, hy);
}
__device__ __forceinline__ float poll_cs(int col, uint32_t epoch) {
  uint32_t v, t;
  int it = 0;
  do {
    asm volatile("ld.relaxed.gpu.global.v2.u32 {%0,%1}, [%2];" : "=r"(v), "=r"(t) : "l"(g_cs + col) : "memory");
  } while (t != epoch && ++it < SPIN_LIMIT);
  return __uint_as_float(v);
}
__device__ __forceinline__ void poll_flags(const uint32_t* f, int n, uint32_t want, uint32_t& mask, uint32_t epoch, int lane) {
  int it = 0;
  while ((mask & want) != want && ++it < SPIN_LIMIT) {
    uint32_t v = lane < n ? ld_acq(f + lane) : 0u;
    mask = __ballot_sync(0xffffffffu, v == epoch);
  }
}

template <bool IS_K>
__device__ __forceinline__ void kv_pair(const float* a0, const float* a1, uint32_t csaddr, const float2 (&st)[4], uint32_t* o) {
#pragma unroll
  for (int tt = 0; tt < 2; tt++) {
    float2 cs = lds64(csaddr + tt * 32);
#pragma unroll
    for (int mb = 0; mb < 2; mb++) {
      const float* a = (mb ? a1 : a0) + 4 * tt;
#pragma unroll
      for (int hh = 0; hh < 2; hh++) {
        float2 s = st[2 * mb + hh];
        float y0 = fmaf(s.x, a[2 * hh], -s.y * cs.x), y1 = fmaf(s.x, a[2 * hh + 1], -s.y * cs.y);
        if (IS_K) { y0 = phi2(y0); y1 = phi2(y1); }
        o[4 * mb + 2 * tt + hh] = pack2(y0, y1);
      }
    }
  }
}

template <int Q>
__device__ __forceinline__ void final_epilogue(float (&acc)[80], const uint32_t (&hp)[20], uint32_t sb, uint32_t sb_peer, int s,
                                               int tid, int lane, int w, __nv_bfloat16* outp) {
  const uint32_t bars = sb + OFF_BAR;
  const uint32_t buf = (11 + 2 * s) * PAGE + tid * 16;
  mbar_wait_cluster(bars + 8 * (PF + s));
#pragma unroll
  for (int m = 0; m < 10; m++) {
    const float* a = acc + 40 * (1 - Q) + 4 * m;
    asm volatile("st.async.shared::cluster.mbarrier::complete_tx::bytes.v4.f32 [%0], {%1,%2,%3,%4}, [%5];"
                 ::"r"(sb_peer + buf + m * 2048), "f"(a[0]), "f"(a[1]), "f"(a[2]), "f"(a[3]),
                 "r"(sb_peer + OFF_BAR + 8 * (RX + s)) : "memory");
  }
  const int c = lane & 3;
#pragma unroll
  for (int m = 0; m < 10; m++) {
    float* a = acc + 40 * Q + 4 * m;
    float2 b = lds64(sb + OFF_B2 + (8 * m + 2 * c) * 4);
    const int ks = Q ? ((m >> 1) + 4) % 5 : (m >> 1);
    uint32_t h0 = hp[4 * ks + 2 * (m & 1)], h1 = hp[4 * ks + 2 * (m & 1) + 1];
    a[0] += b.x + bf_lo(h0); a[1] += b.y + bf_hi(h0);
    a[2] += b.x + bf_lo(h1); a[3] += b.y + bf_hi(h1);
  }
  mbar_wait(bars + 8 * (DG + 12 * s + 11));
  mbar_wait_cluster(bars + 8 * (RX + s));
  const uint32_t stg = sb + s * OFF_R1 + w * 2816;
  const uint32_t sa = stg + (lane & 15) * 176 + (lane >> 4) * 16;
#pragma unroll
  for (int mm = 0; mm < 5; mm++) {
    float4 r0 = lds128(sb + buf + (2 * mm) * 2048), r1 = lds128(sb + buf + (2 * mm + 1) * 2048);
    const float* a = acc + 40 * Q + 8 * mm;
    stsm4(sa + mm * 32, pack2(a[0] + r0.x, a[1] + r0.y), pack2(a[2] + r0.z, a[3] + r0.w),
          pack2(a[4] + r1.x, a[5] + r1.y), pack2(a[6] + r1.z, a[7] + r1.w));
  }
  __syncwarp();
#pragma unroll
  for (int m = 0; m < 5; m++) {
    int n = lane + 32 * m, row = n / 10, ch = n - row * 10;
    float4 v = lds128(stg + row * 176 + ch * 16);
    *reinterpret_cast<float4*>(outp + row * 640 + ch * 8) = v;
  }
}

__global__ void __cluster_dims__(2, 1, 1) __launch_bounds__(384, 1)
fused_block_kernel(const __grid_constant__ CUtensorMap tm_x, const __grid_constant__ CUtensorMap tm_kv,
                   const __grid_constant__ CUtensorMap tm_q, const __grid_constant__ CUtensorMap tm_qr,
                   const __grid_constant__ CUtensorMap tm_wo, const __grid_constant__ CUtensorMap tm_wor,
                   const __grid_constant__ CUtensorMap tm_w1, const __grid_constant__ CUtensorMap tm_w2,
                   const __nv_bfloat16* __restrict__ x, const __nv_bfloat16* __restrict__ wqkv,
                   const __nv_bfloat16* __restrict__ wo, const __nv_bfloat16* __restrict__ w1,
                   const __nv_bfloat16* __restrict__ b1, const __nv_bfloat16* __restrict__ w2,
                   const __nv_bfloat16* __restrict__ b2, __nv_bfloat16* __restrict__ out) {
  extern __shared__ __align__(1024) uint8_t smem_raw[];
  const uint32_t sb = (uint32_t)__cvta_generic_to_shared(smem_raw);
  const uint32_t bars = sb + OFF_BAR;
  const int warp = __shfl_sync(0xffffffffu, threadIdx.x >> 5, 0);
  const int lane = threadIdx.x & 31;

  const int cl = blockIdx.x >> 1, q = blockIdx.x & 1;
  int oct, u4;
  if (cl < 4) { oct = 0; u4 = cl; }
  else if (cl < 36) { oct = 1 + 2 * ((cl - 4) & 7); u4 = (cl - 4) >> 3; }
  else { u4 = (cl - 36) / 7; oct = 2 + 2 * ((cl - 36) - 7 * u4); }
  const int i = 2 * (oct & 7) + (u4 >> 1), p = 2 * (oct >> 3) + (u4 & 1);
  const int j = 2 * p + q;

  if (warp == 8 && elect_one()) {
    asm volatile("prefetch.tensormap [%0];" ::"l"(&tm_x) : "memory");
    asm volatile("prefetch.tensormap [%0];" ::"l"(&tm_kv) : "memory");
  }
  if (threadIdx.x < N_BARS) {
    uint32_t cnt = threadIdx.x < N_CNT1 ? 1 : threadIdx.x < N_CNT4 ? 4 : 8;
    asm volatile("mbarrier.init.shared::cta.b64 [%0], %1;" ::"r"(bars + 8 * threadIdx.x), "r"(cnt) : "memory");
    if (threadIdx.x == RX || threadIdx.x == RX + 1) mbar_expect(bars + 8 * threadIdx.x, 20480);
    if (threadIdx.x == RXK) mbar_expect(bars + 8 * threadIdx.x, 4096);
    asm volatile("fence.mbarrier_init.release.cluster;" ::: "memory");
  }
  __syncthreads();
  asm volatile("barrier.cluster.arrive.relaxed.aligned;" ::: "memory");

  if (warp >= 8) {
    asm volatile("setmaxnreg.dec.sync.aligned.u32 40;");
    if (warp == 8) {
      if (elect_one()) {
        const int ka = 20 + 5 * p + 3 * q, va = 40 + 5 * p + 2 * q - (3 - q);
        auto load_kv = [&](int s, int slot) {
          uint32_t dst = sb + OFF_RING + slot * PAGE, bar = bars + 8 * (FKV + s);
          mbar_expect(bar, 10240);
#pragma unroll
          for (int a = 0; a < 5; a++) tma2d(dst + a * 2048, &tm_kv, bar, 32 * ((a < 3 - q ? ka : va) + a), 32 * s);
        };
        auto load_x = [&](int c) {
          mbar_expect(bars + 8 * (FX + c), 16384);
          tma2d(sb + c * 16384, &tm_x, bars + 8 * (FX + c), 64 * c, 128 * i);
        };
        const int cmain = 80 * j + 16 * q, crem = 80 * j + 64 * (1 - q);
        auto load80 = [&](uint32_t dst, const CUtensorMap* tm, const CUtensorMap* tr, uint32_t bar, int k0) {
          mbar_expect(bar, 12800);
          tma2d(dst, tm, bar, cmain, k0);
          tma2d(dst + 5120, tm, bar, cmain + 32, k0);
          tma2d(dst + 10240, tr, bar, crem, k0);
        };
#pragma unroll 1
        for (int c = 0; c < 3; c++) { load_x(c); load_kv(2 * c, 2 * c); load_kv(2 * c + 1, 2 * c + 1); }
#pragma unroll 1
        for (int c = 3; c < 10; c++) load_x(c);
        TL(40);
        asm volatile("prefetch.tensormap [%0];" ::"l"(&tm_q) : "memory");
        asm volatile("prefetch.tensormap [%0];" ::"l"(&tm_qr) : "memory");
        asm volatile("prefetch.tensormap [%0];" ::"l"(&tm_wo) : "memory");
        asm volatile("prefetch.tensormap [%0];" ::"l"(&tm_wor) : "memory");
        asm volatile("prefetch.tensormap [%0];" ::"l"(&tm_w1) : "memory");
        asm volatile("prefetch.tensormap [%0];" ::"l"(&tm_w2) : "memory");
#pragma unroll 1
        for (int s = 6, slot = 0; s < 20; s++) {
          mbar_wait(bars + 8 * (DKV + s - 6));
          load_kv(s, slot);
          if (++slot == 6) slot = 0;
        }
#pragma unroll 1
        for (int t = 0; t < 8; t++) {
          mbar_wait(bars + 8 * (t < 2 ? DKV + 16 + t : t < 4 ? DKV + 19 : DQ + t - 4));
          load80(sb + OFF_RING + ((t + 2) & 3) * 15360, &tm_q, &tm_qr, bars + 8 * (FQ + t), 80 * t);
        }
#pragma unroll 1
        for (int n = 0; n < 8; n++) {
          const int t = (0x53210476 >> (4 * n)) & 7;
          const int c = t == 0 ? j : (t - 1 < j ? t - 1 : t);
          mbar_wait(bars + 8 * (DQ + ((0x77776654 >> (4 * n)) & 7)));
          load80(sb + 10 * PAGE + t * 15360, &tm_wo, &tm_wor, bars + 8 * (FWO + t), 80 * c);
        }
#pragma unroll 1
        for (int t = 0; t < 8; t++) {
          const int c = t == 0 ? j : (t - 1 < j ? t - 1 : t);
          if (t > 0) {
            const int d = t < 5 ? DW + 2 * t - 1 : DF + t - 5;
            mbar_wait(bars + 8 * d);
            mbar_wait(bars + 8 * (d + 8));
          }
          mbar_expect(bars + 8 * (FW1 + t), 30720);
          tma3d(sb + (7 + 3 * (t < 5 ? t : t - 5)) * PAGE, &tm_w1, bars + 8 * (FW1 + t), 0, 80 * c, 3 * j);
        }
#pragma unroll 1
        for (int t = 0; t < 12; t++) {
          int k0;
          if (t < 3) k0 = 192 * j + 64 * t;
          else { int r = t - 3, uu = r / 3, n = r - 3 * uu; k0 = 192 * (2 * (n < p ? n : n + 1) + q) + 64 * uu; }
          if (t < 7) {
            const int d = DF + ((0x7665443 >> (4 * t)) & 7);
            mbar_wait(bars + 8 * d);
            mbar_wait(bars + 8 * (d + 8));
          } else {
            mbar_wait(bars + 8 * (DG + t - 7));
            mbar_wait(bars + 8 * (DG + 12 + t - 7));
          }
          const int t7 = t < 7 ? t : t - 7;
          mbar_expect(bars + 8 * (FW2 + t), 20480);
          tma3d(sb + (t7 < 3 ? 16 + 2 * t7 : 1 + 2 * t7) * PAGE, &tm_w2, bars + 8 * (FW2 + t), 0, k0, 5 * p);
        }
      }
    } else if (warp == 11) {
      if (elect_one()) {
        mbar_wait(bars + 8 * (DKV + 3));
        l2_prefetch(reinterpret_cast<const uint8_t*>(wo) + blockIdx.x * 6400, 6400);
        l2_prefetch(reinterpret_cast<const uint8_t*>(w2) + blockIdx.x * 15360, 15360);
        mbar_wait(bars + 8 * SIDE);
        const uint32_t epoch = lds32(sb + OFF_EPOCH);
#pragma unroll 1
        for (int s = 0; s < 2; s++) {
          mbar_wait(bars + 8 * (RO + s));
          bulk_store(g_o + ((2 * i + s) * 8 + j) * 10240, sb + s * PAGE, 10240);
          bulk_commit_wait();
          mbar_arrive(bars + 8 * (SO + s));
          fence_gpu();
          st_flag(g_flag_o + (2 * i + s) * 32 + j, epoch);
          TL(44 + s);
        }
#pragma unroll 1
        for (int s = 0; s < 2; s++) {
          mbar_wait(bars + 8 * (RH + s));
          bulk_store(g_h + ((2 * i + s) * 8 + j) * 10240, sb + s * OFF_R1, 10240);
          bulk_commit_wait();
          mbar_arrive(bars + 8 * (SH + s));
          fence_gpu();
          st_flag(g_flag_h + (2 * i + s) * 32 + j, epoch);
          TL(46 + s);
        }
#pragma unroll 1
        for (int s = 0; s < 2; s++) {
          uint8_t* dst = g_f + ((2 * i + s) * 8 + j) * 24576;
          uint32_t* fl = g_flag_f + (2 * i + s) * 32 + j;
          mbar_wait(bars + 8 * (RF + 3 * s));
          bulk_store(dst, sb + s * OFF_R1, 8192);
          bulk_commit_wait();
          mbar_arrive(bars + 8 * (SF + 3 * s));
          fence_gpu();
          st_flag(fl, epoch);
          TL(48 + 2 * s);
          mbar_wait(bars + 8 * (RF + 3 * s + 1));
          bulk_store(dst + 8192, sb + s * OFF_R1 + 8192, 8192);
          mbar_wait(bars + 8 * (RF + 3 * s + 2));
          bulk_store(dst + 16384, sb + s * OFF_R1 + 16384, 8192);
          bulk_commit_wait();
          mbar_arrive(bars + 8 * (SF + 3 * s + 1));
          mbar_arrive(bars + 8 * (SF + 3 * s + 2));
          fence_gpu();
          st_flag(fl + 8, epoch);
          st_flag(fl + 16, epoch);
          TL(49 + 2 * s);
        }
      }
    } else {
      const int s = warp - 9;
      mbar_wait(bars + 8 * SIDE);
      const uint32_t epoch = lds32(sb + OFF_EPOCH);
      const uint32_t rs = sb + s * OFF_R1;
      uint32_t mask = 0;
#pragma unroll 1
      for (int t = 1; t < 8; t++) {
        const int c = t - 1 < j ? t - 1 : t;
        if (s == 0) {
          mbar_wait(bars + 8 * (t < 4 ? RO : t < 6 ? RO + 1 : t == 6 ? DW + 8 : DW));
          if (t >= 6) mbar_wait(bars + 8 * (SO + 7 - t));
        } else {
          mbar_wait(bars + 8 * (t < 7 ? DW + t : DW + 9));
        }
        poll_flags(g_flag_o + (2 * i + s) * 32, 8, 1u << c, mask, epoch, lane);
        if (t == 1) TL(52 + s);
        if (elect_one()) {
          const uint32_t pg = ((s ? 0x21654321u : 0x01654320u) >> (4 * t)) & 7, bar = bars + 8 * (FO + 8 * s + t);
          fence_async_global();
          mbar_expect(bar, 10240);
          bulk_load(sb + pg * PAGE, g_o + ((2 * i + s) * 8 + c) * 10240, 10240, bar);
        }
        __syncwarp();
      }
      mask = 0;
#pragma unroll 1
      for (int t = 1; t < 8; t++) {
        const int c = t - 1 < j ? t - 1 : t;
        mbar_wait(bars + 8 * (t < 3 ? DW + 15 : t == 3 ? SH + s : DF + 8 * s + t - 3));
        poll_flags(g_flag_h + (2 * i + s) * 32, 8, 1u << c, mask, epoch, lane);
        if (t == 1) TL(54 + s);
        if (elect_one()) {
          const uint32_t bar = bars + 8 * (FH + 8 * s + t);
          fence_async_global();
          mbar_expect(bar, 10240);
          bulk_load(rs + (t % 3) * PAGE, g_h + ((2 * i + s) * 8 + c) * 10240, 10240, bar);
        }
        __syncwarp();
      }
      mask = 0;
#pragma unroll 1
      for (int t = 3; t < 12; t++) {
        const int r = t - 3, uu = r / 3, n = r - 3 * uu, c = 2 * (n < p ? n : n + 1) + q;
        mbar_wait(bars + 8 * (t == 3 ? DF + 8 * s + 7 : t < 7 ? SF + 3 * s + t - 4 : DG + 12 * s + t - 4));
        poll_flags(g_flag_f + (2 * i + s) * 32, 24, 1u << (8 * uu + c), mask, epoch, lane);
        if (t == 3) TL(56 + s);
        if (elect_one()) {
          const uint32_t bar = bars + 8 * (FF + 12 * s + t);
          fence_async_global();
          mbar_expect(bar, 8192);
          bulk_load(rs + (t & 3) * 8192, g_f + ((2 * i + s) * 8 + c) * 24576 + uu * 8192, 8192, bar);
        }
        __syncwarp();
      }
    }
    __syncwarp();
    asm volatile("barrier.cluster.wait.aligned;" ::: "memory");
  } else {
    asm volatile("setmaxnreg.inc.sync.aligned.u32 232;");
    const int s = warp >> 2, w = warp & 3, tid = threadIdx.x & 127, c = lane & 3;
    uint32_t sb_peer;
    asm volatile("mapa.shared::cluster.u32 %0, %1, %2;" : "=r"(sb_peer) : "r"(sb), "r"(q ^ 1));

    if (s == 0) {
      float acc0[80], acc1[80];
      {
        auto kv_step = [&](int st, int slot, int first) {
          if ((st & 1) == 0) mbar_wait(bars + 8 * (FX + (st >> 1)));
          mbar_wait(bars + 8 * (FKV + st));
          const uint64_t da = mkdesc(sb + (st >> 1) * 16384 + (st & 1) * 64, 16, 1024, 1);
          const uint64_t db = mkdesc(sb + OFF_RING + slot * PAGE, 2048, 512, 2);
          wg_fence();
          wgmma_ss<160, 0, 1>(acc0, da, db, !first);
          wgmma_ss<160, 0, 1>(acc1, da + 512, db, !first);
          wgmma_ss<160, 0, 1>(acc0, da + 2, db + 64, 1);
          wgmma_ss<160, 0, 1>(acc1, da + 514, db + 64, 1);
          wg_commit();
        };
        kv_step(0, 0, 1);
        TLW(0);
#pragma unroll 1
        for (int st = 1, slot = 1; st < 20; st++) {
          kv_step(st, slot, 0);
          wg_wait<1>();
          if (lane == 0) mbar_arrive(bars + 8 * (DKV + st - 1));
          if (++slot == 6) slot = 0;
        }
      }
      asm volatile("barrier.cluster.wait.aligned;" ::: "memory");
      mbar_wait(bars + 8 * SIDE);
      const uint32_t epoch = lds32(sb + OFF_EPOCH);
      float2 sk[4], sv[4];
#pragma unroll
      for (int r = 0; r < 4; r++) {
        sv[r] = lds64(sb + OFF_LN1 + (64 * (r >> 1) + 16 * w + (lane >> 2) + 8 * (r & 1)) * 8);
        sk[r] = make_float2(sv[r].x * LOG2E, sv[r].y * LOG2E);
      }
      wg_wait<0>();
      reg_fence(acc0);
      reg_fence(acc1);
      if (lane == 0) mbar_arrive(bars + 8 * (DKV + 19));
      TLW(1);
      uint32_t pk[80];
      const uint32_t csa = sb + OFF_CSKV + c * 8;
      if (q == 0) {
        kv_pair<true>(acc0 + 32, acc1 + 32, csa + 4 * 64, sk, pk + 32);
        kv_pair<true>(acc0 + 40, acc1 + 40, csa + 5 * 64, sk, pk + 40);
      } else {
        kv_pair<false>(acc0 + 32, acc1 + 32, csa + 4 * 64, sv, pk + 40);
        kv_pair<false>(acc0 + 40, acc1 + 40, csa + 5 * 64, sv, pk + 32);
      }
      kv_pair<true>(acc0, acc1, csa, sk, pk);
      kv_pair<true>(acc0 + 8, acc1 + 8, csa + 64, sk, pk + 8);
      mbar_wait_cluster(bars + 8 * PQ0);
#pragma unroll
      for (int r = 0; r < 8; r++)
        asm volatile("st.async.shared::cluster.mbarrier::complete_tx::bytes.b32 [%0], %1, [%2];"
                     ::"r"(sb_peer + ((r >> 1) & 1) * 2048 + (64 * (r >> 2) + 16 * w + 8 * (r & 1)) * 16 + lane * 4),
                     "r"(pk[40 + r]), "r"(sb_peer + OFF_BAR + 8 * RXK) : "memory");
      kv_pair<true>(acc0 + 16, acc1 + 16, csa + 2 * 64, sk, pk + 16);
      kv_pair<true>(acc0 + 24, acc1 + 24, csa + 3 * 64, sk, pk + 24);
#pragma unroll
      for (int P = 6; P < 10; P++) kv_pair<false>(acc0 + 8 * P, acc1 + 8 * P, csa + P * 64, sv, pk + 8 * P);
      TLW(2);
      const uint32_t kbase = sb + (q ? 0 : 22528), vbase = sb + (q ? 20480 : 0);
      const int hi = lane >> 4;
      const uint32_t rowoff = (16 * w + (lane & 15)) * 16;
      mbar_wait(bars + 8 * (DQ + 2));
#pragma unroll
      for (int P = 0; P < 10; P++) {
        if (P == 5) continue;
        uint32_t a;
        if (P < 4) a = kbase + (2 * (P + q) + hi) * 2048;
        else if (P == 4) a = q ? vbase + (6 + hi) * 2048 : kbase + (8 + hi) * 2048;
        else { int g = 2 * (P - 6 + q) + hi; a = vbase + (g < 5 ? g + 6 : g < 8 ? g - 3 : g - 8) * 2048; }
        a += rowoff;
        stsm4(a, pk[8 * P], pk[8 * P + 1], pk[8 * P + 2], pk[8 * P + 3]);
        stsm4(a + 1024, pk[8 * P + 4], pk[8 * P + 5], pk[8 * P + 6], pk[8 * P + 7]);
      }
      sts128(vbase + 5 * 2048 + tid * 16, 0x3F803F80u, 0x3F803F80u, 0x3F803F80u, 0x3F803F80u);
      mbar_wait_cluster(bars + 8 * RXK);
      fence_async_smem();
      named_bar(1);
      TLW(3);
      float kv0[24], kv1[24];
      {
        const uint64_t da = mkdesc(kbase, 128, 2048, 0), db = mkdesc(vbase, 128, 2048, 0);
        wg_fence();
#pragma unroll
        for (int kk = 0; kk < 8; kk++) {
          wgmma_ss<48, 1, 1>(kv0, da + 16 * kk, db + 640 + 16 * kk, kk != 0);
          wgmma_ss<48, 1, 1>(kv1, da + 640 + 16 * kk, db + 16 * kk, kk != 0);
        }
        wg_commit();
      }
      mbar_wait(bars + 8 * (DQ + 3));
#pragma unroll
      for (int m = 0; m < 8; m++)
        if (m < 7 || tid < 64) sts128(sb + OFF_KVB + (m * 128 + tid) * 16, 0, 0, 0, 0);
      wg_wait<0>();
      reg_fence(kv0);
      reg_fence(kv1);
      TLW(4);
#pragma unroll
      for (int hh = 0; hh < 2; hh++) {
        const int r = 16 * w + (lane >> 2) + 8 * hh;
        if (r < 40) {
          const int lo = r < 20 ? 0 : 20;
          float* g0 = g_kv + (j * 80 + r) * 24;
#pragma unroll
          for (int b = 0; b < 2; b++) {
            const float* a = b ? kv1 : kv0;
            float* g = g0 + b * 40 * 24;
#pragma unroll
            for (int e8 = 0; e8 < 5; e8++) {
              const int t = b ? (e8 < 3 ? e8 + 2 : e8 - 3) : e8 + 1;
              const int e = 8 * e8 + 2 * c - lo;
              if (e >= 0 && e < 20)
                asm volatile("red.relaxed.gpu.global.add.v2.f32 [%0], {%1,%2};" ::"l"(g + e), "f"(a[4 * t + 2 * hh]), "f"(a[4 * t + 2 * hh + 1]) : "memory");
            }
            if (c == 0)
              asm volatile("red.relaxed.gpu.global.add.f32 [%0], %1;" ::"l"(g + 20), "f"(a[(b ? 20 : 0) + 2 * hh]) : "memory");
          }
        }
      }
      named_bar(1);
      if (tid == 127) {
        fence_gpu();
        st_flag(g_flag_kv + j * 32 + i, epoch);
      }
      __syncwarp();
      TLW(5);
      uint32_t mask = 0;
      poll_flags(g_flag_kv + j * 32, 16, 0xffffu, mask, epoch, lane);
      TLW(6);
      float4 kvv[4];
#pragma unroll
      for (int m = 0; m < 4; m++) {
        const int v = tid + 128 * m;
        if (m < 3 || v < 480)
          asm volatile("ld.relaxed.gpu.global.v4.f32 {%0,%1,%2,%3}, [%4];" : "=f"(kvv[m].x), "=f"(kvv[m].y), "=f"(kvv[m].z), "=f"(kvv[m].w)
                       : "l"(g_kv + j * 1920 + v * 4) : "memory");
      }
#pragma unroll
      for (int m = 0; m < 4; m++) {
        const int v = tid + 128 * m;
        if (m < 3 || v < 480) {
          const int d = v / 6, part = v - 6 * d, head = d / 20;
          if (part < 5) {
            const int n = 20 * head + 4 * part;
            sts64(sb + OFF_KVB + (n >> 3) * 1280 + d * 16 + (n & 7) * 2, pack2(kvv[m].x, kvv[m].y), pack2(kvv[m].z, kvv[m].w));
          } else {
            const uint32_t z = (head & 1) ? pack2(0.f, kvv[m].x) : pack2(kvv[m].x, 0.f);
            sts128(sb + OFF_KVB + (10 + (head >> 1)) * 1280 + d * 16, z, z, z, z);
          }
        }
      }
      fence_async_smem();
      __syncwarp();
      if (lane == 0) mbar_arrive(bars + 8 * KVB);
      TLW(7);
    } else {
      uint32_t epoch;
      asm volatile("ld.relaxed.gpu.global.u32 %0, [%1];" : "=r"(epoch) : "l"(&g_epoch) : "memory");
      epoch += 1;
      if (tid < 30) *reinterpret_cast<float4*>(g_kv + j * 1920 + i * 120 + tid * 4) = make_float4(0.f, 0.f, 0.f, 0.f);
      const int unit = i * 8 + j;
      mbar_wait(bars + 8 * FX);
      uint4 xv[10];
      const int myrow = 128 * i + 16 * j + 4 * w + (lane >> 3);
#pragma unroll
      for (int m = 0; m < 10; m++) xv[m] = __ldg(reinterpret_cast<const uint4*>(x + myrow * 640) + (lane & 7) + 8 * m);
      float cs[8];
#pragma unroll
      for (int e = 0; e < 8; e++) cs[e] = 0.f;
      if (unit < 108) {
        const bool is1 = unit >= 60;
        const int ld = is1 ? 1536 : 1920;
        const __nv_bfloat16* wp = (is1 ? w1 + 32 * (unit - 60) : wqkv + 32 * unit) + (tid >> 2) * ld + c * 8;
        uint4 wv[20];
#pragma unroll
        for (int m = 0; m < 20; m++) wv[m] = __ldg(reinterpret_cast<const uint4*>(wp + m * 32 * ld));
#pragma unroll
        for (int m = 0; m < 20; m++) {
          cs[0] += bf_lo(wv[m].x); cs[1] += bf_hi(wv[m].x); cs[2] += bf_lo(wv[m].y); cs[3] += bf_hi(wv[m].y);
          cs[4] += bf_lo(wv[m].z); cs[5] += bf_hi(wv[m].z); cs[6] += bf_lo(wv[m].w); cs[7] += bf_hi(wv[m].w);
        }
      }
      {
        float sum = 0.f;
#pragma unroll
        for (int m = 0; m < 10; m++)
          sum += ((bf_lo(xv[m].x) + bf_hi(xv[m].x)) + (bf_lo(xv[m].y) + bf_hi(xv[m].y))) +
                 ((bf_lo(xv[m].z) + bf_hi(xv[m].z)) + (bf_lo(xv[m].w) + bf_hi(xv[m].w)));
#pragma unroll
        for (int o = 1; o < 8; o <<= 1) sum += __shfl_xor_sync(0xffffffffu, sum, o);
        const float mean = sum * (1.f / 640.f);
        float sq = 0.f;
#pragma unroll
        for (int m = 0; m < 10; m++) {
          const uint32_t vv[4] = {xv[m].x, xv[m].y, xv[m].z, xv[m].w};
#pragma unroll
          for (int e = 0; e < 4; e++) {
            float a = bf_lo(vv[e]) - mean, b = bf_hi(vv[e]) - mean;
            sq = fmaf(a, a, sq);
            sq = fmaf(b, b, sq);
          }
        }
#pragma unroll
        for (int o = 1; o < 8; o <<= 1) sq += __shfl_xor_sync(0xffffffffu, sq, o);
        const float rstd = rsqrtf(sq * (1.f / 640.f) + 1e-5f);
        if ((lane & 7) == 0)
          asm volatile("st.relaxed.gpu.global.v4.u32 [%0], {%1,%2,%3,%2};" ::"l"(g_ln1 + myrow), "r"(__float_as_uint(rstd)),
                       "r"(epoch), "r"(__float_as_uint(rstd * mean)) : "memory");
      }
#pragma unroll
      for (int e = 0; e < 8; e++) {
#pragma unroll
        for (int o = 4; o < 32; o <<= 1) cs[e] += __shfl_xor_sync(0xffffffffu, cs[e], o);
      }
      if (lane < 4) {
        sts128(sb + OFF_RED + w * 128 + lane * 32, __float_as_uint(cs[0]), __float_as_uint(cs[1]), __float_as_uint(cs[2]), __float_as_uint(cs[3]));
        sts128(sb + OFF_RED + w * 128 + lane * 32 + 16, __float_as_uint(cs[4]), __float_as_uint(cs[5]), __float_as_uint(cs[6]), __float_as_uint(cs[7]));
      }
      named_bar(2);
      if (w == 0 && unit < 108) {
        const uint32_t a = sb + OFF_RED + lane * 4;
        const float v = (__uint_as_float(lds32(a)) + __uint_as_float(lds32(a + 128))) + (__uint_as_float(lds32(a + 256)) + __uint_as_float(lds32(a + 384)));
        asm volatile("st.relaxed.gpu.global.v2.u32 [%0], {%1,%2};" ::"l"(g_cs + 32 * unit + lane), "r"(__float_as_uint(v)), "r"(epoch) : "memory");
      }
      if (tid == 127) {
        fence_gpu();
        st_flag(g_flag_z + j * 32 + i, epoch);
        sts32(sb + OFF_EPOCH, epoch);
      }
      __syncwarp();
      TLW(10);
      if (tid < 80) sts32(sb + OFF_B2 + tid * 4, (uint32_t)__bfloat16_as_ushort(b2[80 * j + tid]) << 16);
      uint32_t bb = 0;
      if (tid < 96) bb = *reinterpret_cast<const uint32_t*>(b1 + 192 * j + 2 * tid);
      {
        uint32_t a, t0, b, t1;
        int it = 0;
        do {
          asm volatile("ld.relaxed.gpu.global.v4.u32 {%0,%1,%2,%3}, [%4];" : "=r"(a), "=r"(t0), "=r"(b), "=r"(t1) : "l"(g_ln1 + 128 * i + tid) : "memory");
        } while ((t0 != epoch || t1 != epoch) && ++it < SPIN_LIMIT);
        sts64(sb + OFF_LN1 + tid * 8, a, b);
      }
#pragma unroll
      for (int m = 0; m < 2; m++) {
        const int n = tid + 128 * m;
        if (n < 240) {
          int col;
          if (n < 160) col = n < 96 - 32 * q ? 640 + 160 * p + 96 * q + n : 1280 + 160 * p - 96 + 96 * q + n;
          else { int nn = n - 160; col = 80 * j + (q ? (nn < 64 ? nn + 16 : nn - 64) : nn); }
          sts32(sb + OFF_CSKV + n * 4, __float_as_uint(poll_cs(col, epoch)));
        }
      }
      if (tid < 96) {
        const float c0 = poll_cs(1920 + 192 * j + 2 * tid, epoch), c1 = poll_cs(1920 + 192 * j + 2 * tid + 1, epoch);
        sts128(sb + OFF_CB1 + tid * 16, __float_as_uint(c0), __float_as_uint(c1), bb << 16, bb & 0xffff0000u);
      }
      __syncwarp();
      if (w == 0) {
        uint32_t mask = 0;
        poll_flags(g_flag_z + j * 32, 16, 0xffffu, mask, epoch, lane);
      }
      __syncwarp();
      if (lane == 0) mbar_arrive(bars + 8 * SIDE);
      TLW(11);
      asm volatile("barrier.cluster.wait.aligned;" ::: "memory");

      float acc0[40], acc1[40];
      for (int c2 = 1; c2 < 10; c2++) mbar_wait(bars + 8 * (FX + c2));
      mbar_wait(bars + 8 * (DKV + 18));
      auto q_step = [&](int t, int first) {
        mbar_wait(bars + 8 * (FQ + t));
        const uint64_t db = mkdesc(sb + OFF_RING + ((t + 2) & 3) * 15360, 5120, 512, 2);
        wg_fence();
#pragma unroll
        for (int ks = 0; ks < 5; ks++) {
          const int kk = 5 * t + ks;
          const uint64_t da = mkdesc(sb + (kk >> 2) * 16384 + (kk & 3) * 32, 16, 1024, 1);
          wgmma_ss<80, 0, 1>(acc0, da, db + 64 * ks, !(first && ks == 0));
          wgmma_ss<80, 0, 1>(acc1, da + 512, db + 64 * ks, !(first && ks == 0));
        }
        wg_commit();
      };
      q_step(0, 1);
      TLW(12);
#pragma unroll 1
      for (int t = 1; t < 8; t++) {
        q_step(t, 0);
        wg_wait<1>();
        if (lane == 0) {
          mbar_arrive(bars + 8 * (DQ + t - 1));
          if (t == 1) mbar_arrive_remote(sb_peer + OFF_BAR + 8 * PQ0);
        }
      }
      mbar_wait(bars + 8 * SIDE);
      float2 sk[4];
#pragma unroll
      for (int r = 0; r < 4; r++) {
        sk[r] = lds64(sb + OFF_LN1 + (64 * (r >> 1) + 16 * w + (lane >> 2) + 8 * (r & 1)) * 8);
        sk[r].x *= LOG2E;
        sk[r].y *= LOG2E;
      }
      wg_wait<0>();
      reg_fence(acc0);
      reg_fence(acc1);
      if (lane == 0) mbar_arrive(bars + 8 * (DQ + 7));
      TLW(13);
      uint32_t pq[40];
#pragma unroll
      for (int P = 0; P < 5; P++) kv_pair<true>(acc0 + 8 * P, acc1 + 8 * P, sb + OFF_CSQ + c * 8 + P * 64, sk, pq + 8 * P);
      TLW(14);
      float o0[48], o1[48];
      mbar_wait(bars + 8 * KVB);
      TLW(15);
      const uint64_t dkv = mkdesc(sb + OFF_KVB, 128, 1280, 0);
      wg_fence();
#pragma unroll
      for (int ks = 0; ks < 5; ks++)
        wgmma_rs<96, 1>(o0, pq[8 * ks], pq[8 * ks + 1], pq[8 * ks + 2], pq[8 * ks + 3], dkv + 16 * (ks < 4 ? ks + q : 4 - 4 * q), ks != 0);
      wg_commit();
#pragma unroll
      for (int ks = 0; ks < 5; ks++)
        wgmma_rs<96, 1>(o1, pq[8 * ks + 4], pq[8 * ks + 5], pq[8 * ks + 6], pq[8 * ks + 7], dkv + 16 * (ks < 4 ? ks + q : 4 - 4 * q), ks != 0);
      wg_commit();
      const uint32_t sa = sb + (lane >> 4) * 1024 + (16 * w + (lane & 15)) * 16;
      auto o_epi = [&](float(&o)[48], int mb) {
        float inv[2][4];
#pragma unroll
        for (int hh = 0; hh < 2; hh++)
#pragma unroll
          for (int h = 0; h < 4; h++) inv[hh][h] = rcp(o[40 + 4 * (h >> 1) + 2 * hh + (h & 1)] + 1e-6f);
        uint32_t r[4];
#pragma unroll
        for (int t = 0; t < 10; t++) {
#pragma unroll
          for (int hh = 0; hh < 2; hh++) {
            const float f = t == 2 ? (c < 2 ? inv[hh][0] : inv[hh][1]) : t == 7 ? (c < 2 ? inv[hh][2] : inv[hh][3]) : inv[hh][(8 * t) / 20];
            r[2 * (t & 1) + hh] = pack2(o[4 * t + 2 * hh] * f, o[4 * t + 2 * hh + 1] * f);
          }
          if (t & 1) stsm4(sa + mb * PAGE + (t >> 1) * 2048, r[0], r[1], r[2], r[3]);
        }
        fence_async_smem();
        __syncwarp();
        if (lane == 0) mbar_arrive(bars + 8 * (RO + mb));
      };
      wg_wait<1>();
      reg_fence(o0);
      o_epi(o0, 0);
      TLW(16);
      wg_wait<0>();
      reg_fence(o1);
      o_epi(o1, 1);
      TLW(17);
    }

    const int row0 = 128 * i + 64 * s + 16 * w;
    const uint32_t rs = sb + s * OFF_R1;
    uint32_t hp[20];
    {
      const __nv_bfloat16* xr = x + (row0 + (lane >> 2)) * 640 + 80 * j + 2 * c;
#pragma unroll
      for (int r = 0; r < 20; r++) {
        const int ks = r >> 2;
        hp[r] = __ldg(reinterpret_cast<const uint32_t*>(xr + (r & 1) * 8 * 640 + ((r >> 1) & 1) * 8 + 16 * (ks < 4 ? ks + q : 4 - 4 * q)));
      }
      float acc[40];
      auto w_step = [&](int t, int first) {
        mbar_wait(bars + 8 * (first ? RO + s : FO + 8 * s + t));
        mbar_wait(bars + 8 * (FWO + t));
        if (t == 1) TLW(20 + s);
        const uint32_t pg = ((s ? 0x21654321u : 0x01654320u) >> (4 * t)) & 7;
        const uint64_t da = mkdesc(sb + pg * PAGE, 1024, 128, 0), db = mkdesc(sb + 10 * PAGE + t * 15360, 5120, 512, 2);
        wg_fence();
#pragma unroll
        for (int ks = 0; ks < 5; ks++) wgmma_ss<80, 0, 1>(acc, da + 128 * ks, db + 64 * ks, !(first && ks == 0));
        wg_commit();
      };
      w_step(0, 1);
      wg_wait<0>();
      if (lane == 0) mbar_arrive(bars + 8 * (DW + 8 * s));
#pragma unroll 1
      for (int t = 1; t < 8; t++) {
        w_step(t, 0);
        wg_wait<1>();
        if (t > 1 && lane == 0) mbar_arrive(bars + 8 * (DW + 8 * s + t - 1));
      }
      wg_wait<0>();
      reg_fence(acc);
      if (lane == 0) mbar_arrive(bars + 8 * (DW + 8 * s + 7));
      TLW(22 + s);
      float sm[2] = {0.f, 0.f}, sq[2] = {0.f, 0.f};
#pragma unroll
      for (int r = 0; r < 20; r++) {
        const uint32_t v = pack2(acc[2 * r] + bf_lo(hp[r]), acc[2 * r + 1] + bf_hi(hp[r]));
        hp[r] = v;
        const float a = bf_lo(v), b = bf_hi(v);
        sm[r & 1] += a + b;
        sq[r & 1] = fmaf(a, a, fmaf(b, b, sq[r & 1]));
      }
      mbar_wait(bars + 8 * (DW + 8 * s + 7));
      const uint32_t sa = rs + (lane >> 4) * 1024 + (16 * w + (lane & 15)) * 16;
#pragma unroll
      for (int ks = 0; ks < 5; ks++)
        stsm4(sa + (ks < 4 ? ks + q : 4 - 4 * q) * 2048, hp[4 * ks], hp[4 * ks + 1], hp[4 * ks + 2], hp[4 * ks + 3]);
#pragma unroll
      for (int hh = 0; hh < 2; hh++) {
#pragma unroll
        for (int o = 1; o < 4; o <<= 1) {
          sm[hh] += __shfl_xor_sync(0xffffffffu, sm[hh], o);
          sq[hh] += __shfl_xor_sync(0xffffffffu, sq[hh], o);
        }
      }
      if (c < 2) g_hstat[((2 * i + s) * 8 + j) * 64 + 16 * w + (lane >> 2) + 8 * c] = c ? make_float2(sm[1], sq[1]) : make_float2(sm[0], sq[0]);
      fence_async_smem();
      __syncwarp();
      if (lane == 0) mbar_arrive(bars + 8 * (RH + s));
      TLW(24 + s);
    }
    float accf[96];
    mbar_wait(bars + 8 * FW1);
    {
      const uint64_t db = mkdesc(sb + 7 * PAGE, 10240, 1024, 1);
      wg_fence();
#pragma unroll
      for (int ks = 0; ks < 5; ks++)
        wgmma_rs<192, 1>(accf, hp[4 * ks], hp[4 * ks + 1], hp[4 * ks + 2], hp[4 * ks + 3], db + 128 * (ks < 4 ? ks + q : 4 - 4 * q), ks != 0);
      wg_commit();
      wg_wait<0>();
      if (lane == 0) mbar_arrive(bars + 8 * (DF + 8 * s));
    }
#pragma unroll 1
    for (int t = 1; t < 8; t++) {
      mbar_wait(bars + 8 * (FH + 8 * s + t));
      mbar_wait(bars + 8 * (FW1 + t));
      if (t == 1) TLW(26 + s);
      const uint64_t da = mkdesc(rs + (t % 3) * PAGE, 1024, 128, 0);
      const uint64_t db = mkdesc(sb + (7 + 3 * (t < 5 ? t : t - 5)) * PAGE, 10240, 1024, 1);
      wg_fence();
#pragma unroll
      for (int ks = 0; ks < 5; ks++) wgmma_ss<192, 0, 1>(accf, da + 128 * ks, db + 128 * ks, 1);
      wg_commit();
      wg_wait<1>();
      if (t > 1 && lane == 0) mbar_arrive(bars + 8 * (DF + 8 * s + t - 1));
    }
    float ra[2], rb[2];
    {
      float2 v[4];
#pragma unroll
      for (int m = 0; m < 4; m++)
        asm volatile("ld.relaxed.gpu.global.v2.f32 {%0,%1}, [%2];" : "=f"(v[m].x), "=f"(v[m].y)
                     : "l"(g_hstat + ((2 * i + s) * 8 + 2 * c + (m >> 1)) * 64 + 16 * w + (lane >> 2) + 8 * (m & 1)) : "memory");
#pragma unroll
      for (int hh = 0; hh < 2; hh++) {
        float sm = v[hh].x + v[2 + hh].x, sq = v[hh].y + v[2 + hh].y;
#pragma unroll
        for (int o = 1; o < 4; o <<= 1) {
          sm += __shfl_xor_sync(0xffffffffu, sm, o);
          sq += __shfl_xor_sync(0xffffffffu, sq, o);
        }
        const float mean = sm * (1.f / 640.f);
        const float var = fmaxf(fmaf(-mean, mean, sq * (1.f / 640.f)), 0.f);
        ra[hh] = rsqrtf(var + 1e-5f);
        rb[hh] = -ra[hh] * mean;
      }
    }
    wg_wait<0>();
    reg_fence(accf);
    if (lane == 0) mbar_arrive(bars + 8 * (DF + 8 * s + 7));
    TLW(28 + s);
    float accg[80];
    uint32_t fp[48];
    {
      const uint32_t sa = rs + (lane >> 4) * 1024 + (16 * w + (lane & 15)) * 16;
#pragma unroll
      for (int u = 0; u < 3; u++) {
#pragma unroll
        for (int t = 0; t < 8; t++) {
          const float4 cb = lds128(sb + OFF_CB1 + (32 * u + 4 * t + c) * 16);
#pragma unroll
          for (int hh = 0; hh < 2; hh++) {
            const float* a = accf + 32 * u + 4 * t + 2 * hh;
            const float y0 = fmaf(ra[hh], a[0], fmaf(rb[hh], cb.x, cb.z)), y1 = fmaf(ra[hh], a[1], fmaf(rb[hh], cb.y, cb.w));
            fp[16 * u + 2 * t + hh] = pack2(gelu(y0), gelu(y1));
          }
        }
        if (u == 0) mbar_wait(bars + 8 * (DF + 8 * s + 7));
#pragma unroll
        for (int ks = 0; ks < 4; ks++)
          stsm4(sa + u * 8192 + ks * 2048, fp[16 * u + 4 * ks], fp[16 * u + 4 * ks + 1], fp[16 * u + 4 * ks + 2], fp[16 * u + 4 * ks + 3]);
        fence_async_smem();
        __syncwarp();
        if (lane == 0) mbar_arrive(bars + 8 * (RF + 3 * s + u));
        mbar_wait(bars + 8 * (FW2 + u));
        const uint64_t db = mkdesc(sb + (16 + 2 * u) * PAGE, 4096, 512, 2);
        wg_fence();
#pragma unroll
        for (int ks = 0; ks < 4; ks++)
          wgmma_rs<160, 1>(accg, fp[16 * u + 4 * ks], fp[16 * u + 4 * ks + 1], fp[16 * u + 4 * ks + 2], fp[16 * u + 4 * ks + 3], db + 64 * ks, (u | ks) != 0);
        wg_commit();
        if (u > 0) {
          wg_wait<1>();
          if (lane == 0) mbar_arrive(bars + 8 * (DG + 12 * s + u - 1));
        }
      }
      TLW(30 + s);
      wg_wait<0>();
      if (lane == 0) mbar_arrive(bars + 8 * (DG + 12 * s + 2));
    }
#pragma unroll 1
    for (int t = 3; t < 12; t++) {
      mbar_wait(bars + 8 * (FF + 12 * s + t));
      mbar_wait(bars + 8 * (FW2 + t));
      if (t == 3) TLW(32 + s);
      const int t7 = t < 7 ? t : t - 7;
      const uint64_t da = mkdesc(rs + (t & 3) * 8192, 1024, 128, 0);
      const uint64_t db = mkdesc(sb + (t7 < 3 ? 16 + 2 * t7 : 1 + 2 * t7) * PAGE, 4096, 512, 2);
      wg_fence();
#pragma unroll
      for (int ks = 0; ks < 4; ks++) wgmma_ss<160, 0, 1>(accg, da + 128 * ks, db + 64 * ks, 1);
      wg_commit();
      wg_wait<1>();
      if (t > 3 && lane == 0) {
        mbar_arrive(bars + 8 * (DG + 12 * s + t - 1));
        if (t == 6 || t == 7) mbar_arrive_remote(sb_peer + OFF_BAR + 8 * (PF + t - 6));
      }
    }
    wg_wait<0>();
    reg_fence(accg);
    if (lane == 0) mbar_arrive(bars + 8 * (DG + 12 * s + 11));
    TLW(34 + s);
    __nv_bfloat16* outp = out + row0 * 640 + 80 * j;
    if (q == 0) final_epilogue<0>(accg, hp, sb, sb_peer, s, tid, lane, w, outp);
    else final_epilogue<1>(accg, hp, sb, sb_peer, s, tid, lane, w, outp);
    if (blockIdx.x == 0 && threadIdx.x == 0) g_epoch = lds32(sb + OFF_EPOCH);
    TLW(36 + s);
  }
}

typedef CUresult (*EncodeFn)(CUtensorMap*, CUtensorMapDataType, cuuint32_t, void*, const cuuint64_t*, const cuuint64_t*,
                             const cuuint32_t*, const cuuint32_t*, CUtensorMapInterleave, CUtensorMapSwizzle,
                             CUtensorMapL2promotion, CUtensorMapFloatOOBfill);

void make_map(EncodeFn enc, CUtensorMap* tm, const void* base, int rank, const cuuint64_t* dims, const cuuint64_t* strides,
              const cuuint32_t* box, CUtensorMapSwizzle sw) {
  const cuuint32_t es[3] = {1, 1, 1};
  enc(tm, CU_TENSOR_MAP_DATA_TYPE_BFLOAT16, rank, const_cast<void*>(base), dims, strides, box, es, CU_TENSOR_MAP_INTERLEAVE_NONE,
      sw, CU_TENSOR_MAP_L2_PROMOTION_L2_128B, CU_TENSOR_MAP_FLOAT_OOB_FILL_NONE);
}
void make_map2(EncodeFn enc, CUtensorMap* tm, const void* base, int rows, int cols, int box_rows, int box_cols, CUtensorMapSwizzle sw) {
  const cuuint64_t dims[2] = {(cuuint64_t)cols, (cuuint64_t)rows}, strides[1] = {(cuuint64_t)cols * 2};
  const cuuint32_t box[2] = {(cuuint32_t)box_cols, (cuuint32_t)box_rows};
  make_map(enc, tm, base, 2, dims, strides, box, sw);
}
void make_map3(EncodeFn enc, CUtensorMap* tm, const void* base, int rows, int cols, int box_rows, int atom, int natom, CUtensorMapSwizzle sw) {
  const cuuint64_t dims[3] = {(cuuint64_t)atom, (cuuint64_t)rows, (cuuint64_t)(cols / atom)};
  const cuuint64_t strides[2] = {(cuuint64_t)cols * 2, (cuuint64_t)atom * 2};
  const cuuint32_t box[3] = {(cuuint32_t)atom, (cuuint32_t)box_rows, (cuuint32_t)natom};
  make_map(enc, tm, base, 3, dims, strides, box, sw);
}

}

extern "C" void kernel_launch(void* const* d_in, const int* in_sizes, int n_in, void* d_out, int out_size) {
  const __nv_bfloat16* x = (const __nv_bfloat16*)d_in[0];
  const __nv_bfloat16* wqkv = (const __nv_bfloat16*)d_in[1];
  const __nv_bfloat16* wo = (const __nv_bfloat16*)d_in[2];
  const __nv_bfloat16* w1 = (const __nv_bfloat16*)d_in[4];
  const __nv_bfloat16* b1 = (const __nv_bfloat16*)d_in[5];
  const __nv_bfloat16* w2 = (const __nv_bfloat16*)d_in[6];
  const __nv_bfloat16* b2 = (const __nv_bfloat16*)d_in[7];

  void* fn = nullptr;
  cudaDriverEntryPointQueryResult qr;
  cudaGetDriverEntryPoint("cuTensorMapEncodeTiled", &fn, cudaEnableDefault, &qr);
  EncodeFn enc = (EncodeFn)fn;
  CUtensorMap tm_x, tm_kv, tm_q, tm_qr, tm_wo, tm_wor, tm_w1, tm_w2;
  make_map2(enc, &tm_x, x, 2048, 640, 128, 64, CU_TENSOR_MAP_SWIZZLE_128B);
  make_map2(enc, &tm_kv, wqkv, 640, 1920, 32, 32, CU_TENSOR_MAP_SWIZZLE_64B);
  make_map2(enc, &tm_q, wqkv, 640, 1920, 80, 32, CU_TENSOR_MAP_SWIZZLE_64B);
  make_map2(enc, &tm_qr, wqkv, 640, 1920, 80, 16, CU_TENSOR_MAP_SWIZZLE_64B);
  make_map2(enc, &tm_wo, wo, 640, 640, 80, 32, CU_TENSOR_MAP_SWIZZLE_64B);
  make_map2(enc, &tm_wor, wo, 640, 640, 80, 16, CU_TENSOR_MAP_SWIZZLE_64B);
  make_map3(enc, &tm_w1, w1, 640, 1536, 80, 64, 3, CU_TENSOR_MAP_SWIZZLE_128B);
  make_map3(enc, &tm_w2, w2, 1536, 640, 64, 32, 5, CU_TENSOR_MAP_SWIZZLE_64B);
  cudaFuncSetAttribute(fused_block_kernel, cudaFuncAttributeMaxDynamicSharedMemorySize, SMEM_BYTES);
  fused_block_kernel<<<128, 384, SMEM_BYTES>>>(tm_x, tm_kv, tm_q, tm_qr, tm_wo, tm_wor, tm_w1, tm_w2, x, wqkv, wo, w1, b1, w2, b2,
                                               (__nv_bfloat16*)d_out);
}
```

```cpp
#include <cuda_runtime.h>
#include <cuda_bf16.h>
#include <cuda.h>
#include <stdint.h>

namespace {

template <int TA, int TB> __device__ __forceinline__ void wgmma_ss_n48(float (&d)[24], uint64_t da, uint64_t db, int sc) {
  asm volatile("{.reg .pred p; setp.ne.b32 p, %26, 0; wgmma.mma_async.sync.aligned.m64n48k16.f32.bf16.bf16 {%0,%1,%2,%3,%4,%5,%6,%7,%8,%9,%10,%11,%12,%13,%14,%15,%16,%17,%18,%19,%20,%21,%22,%23}, %24, %25, p, 1, 1, %27, %28;}"
    : "+f"(d[0]),"+f"(d[1]),"+f"(d[2]),"+f"(d[3]),"+f"(d[4]),"+f"(d[5]),"+f"(d[6]),"+f"(d[7]),"+f"(d[8]),"+f"(d[9]),"+f"(d[10]),"+f"(d[11]),"+f"(d[12]),"+f"(d[13]),"+f"(d[14]),"+f"(d[15]),"+f"(d[16]),"+f"(d[17]),"+f"(d[18]),"+f"(d[19]),"+f"(d[20]),"+f"(d[21]),"+f"(d[22]),"+f"(d[23])
    : "l"(da), "l"(db), "r"(sc), "n"(TA), "n"(TB));
}
template <int TA, int TB> __device__ __forceinline__ void wgmma_ss_n80(float (&d)[40], uint64_t da, uint64_t db, int sc) {
  asm volatile("{.reg .pred p; setp.ne.b32 p, %42, 0; wgmma.mma_async.sync.aligned.m64n80k16.f32.bf16.bf16 {%0,%1,%2,%3,%4,%5,%6,%7,%8,%9,%10,%11,%12,%13,%14,%15,%16,%17,%18,%19,%20,%21,%22,%23,%24,%25,%26,%27,%28,%29,%30,%31,%32,%33,%34,%35,%36,%37,%38,%39}, %40, %41, p, 1, 1, %43, %44;}"
    : "+f"(d[0]),"+f"(d[1]),"+f"(d[2]),"+f"(d[3]),"+f"(d[4]),"+f"(d[5]),"+f"(d[6]),"+f"(d[7]),"+f"(d[8]),"+f"(d[9]),"+f"(d[10]),"+f"(d[11]),"+f"(d[12]),"+f"(d[13]),"+f"(d[14]),"+f"(d[15]),"+f"(d[16]),"+f"(d[17]),"+f"(d[18]),"+f"(d[19]),"+f"(d[20]),"+f"(d[21]),"+f"(d[22]),"+f"(d[23]),"+f"(d[24]),"+f"(d[25]),"+f"(d[26]),"+f"(d[27]),"+f"(d[28]),"+f"(d[29]),"+f"(d[30]),"+f"(d[31]),"+f"(d[32]),"+f"(d[33]),"+f"(d[34]),"+f"(d[35]),"+f"(d[36]),"+f"(d[37]),"+f"(d[38]),"+f"(d[39])
    : "l"(da), "l"(db), "r"(sc), "n"(TA), "n"(TB));
}
template <int TA, int TB> __device__ __forceinline__ void wgmma_ss_n160(float (&d)[80], uint64_t da, uint64_t db, int sc) {
  asm volatile("{.reg .pred p; setp.ne.b32 p, %82, 0; wgmma.mma_async.sync.aligned.m64n160k16.f32.bf16.bf16 {%0,%1,%2,%3,%4,%5,%6,%7,%8,%9,%10,%11,%12,%13,%14,%15,%16,%17,%18,%19,%20,%21,%22,%23,%24,%25,%26,%27,%28,%29,%30,%31,%32,%33,%34,%35,%36,%37,%38,%39,%40,%41,%42,%43,%44,%45,%46,%47,%48,%49,%50,%51,%52,%53,%54,%55,%56,%57,%58,%59,%60,%61,%62,%63,%64,%65,%66,%67,%68,%69,%70,%71,%72,%73,%74,%75,%76,%77,%78,%79}, %80, %81, p, 1, 1, %83, %84;}"
    : "+f"(d[0]),"+f"(d[1]),"+f"(d[2]),"+f"(d[3]),"+f"(d[4]),"+f"(d[5]),"+f"(d[6]),"+f"(d[7]),"+f"(d[8]),"+f"(d[9]),"+f"(d[10]),"+f"(d[11]),"+f"(d[12]),"+f"(d[13]),"+f"(d[14]),"+f"(d[15]),"+f"(d[16]),"+f"(d[17]),"+f"(d[18]),"+f"(d[19]),"+f"(d[20]),"+f"(d[21]),"+f"(d[22]),"+f"(d[23]),"+f"(d[24]),"+f"(d[25]),"+f"(d[26]),"+f"(d[27]),"+f"(d[28]),"+f"(d[29]),"+f"(d[30]),"+f"(d[31]),"+f"(d[32]),"+f"(d[33]),"+f"(d[34]),"+f"(d[35]),"+f"(d[36]),"+f"(d[37]),"+f"(d[38]),"+f"(d[39]),"+f"(d[40]),"+f"(d[41]),"+f"(d[42]),"+f"(d[43]),"+f"(d[44]),"+f"(d[45]),"+f"(d[46]),"+f"(d[47]),"+f"(d[48]),"+f"(d[49]),"+f"(d[50]),"+f"(d[51]),"+f"(d[52]),"+f"(d[53]),"+f"(d[54]),"+f"(d[55]),"+f"(d[56]),"+f"(d[57]),"+f"(d[58]),"+f"(d[59]),"+f"(d[60]),"+f"(d[61]),"+f"(d[62]),"+f"(d[63]),"+f"(d[64]),"+f"(d[65]),"+f"(d[66]),"+f"(d[67]),"+f"(d[68]),"+f"(d[69]),"+f"(d[70]),"+f"(d[71]),"+f"(d[72]),"+f"(d[73]),"+f"(d[74]),"+f"(d[75]),"+f"(d[76]),"+f"(d[77]),"+f"(d[78]),"+f"(d[79])
    : "l"(da), "l"(db), "r"(sc), "n"(TA), "n"(TB));
}
template <int TA, int TB> __device__ __forceinline__ void wgmma_ss_n192(float (&d)[96], uint64_t da, uint64_t db, int sc) {
  asm volatile("{.reg .pred p; setp.ne.b32 p, %98, 0; wgmma.mma_async.sync.aligned.m64n192k16.f32.bf16.bf16 {%0,%1,%2,%3,%4,%5,%6,%7,%8,%9,%10,%11,%12,%13,%14,%15,%16,%17,%18,%19,%20,%21,%22,%23,%24,%25,%26,%27,%28,%29,%30,%31,%32,%33,%34,%35,%36,%37,%38,%39,%40,%41,%42,%43,%44,%45,%46,%47,%48,%49,%50,%51,%52,%53,%54,%55,%56,%57,%58,%59,%60,%61,%62,%63,%64,%65,%66,%67,%68,%69,%70,%71,%72,%73,%74,%75,%76,%77,%78,%79,%80,%81,%82,%83,%84,%85,%86,%87,%88,%89,%90,%91,%92,%93,%94,%95}, %96, %97, p, 1, 1, %99, %100;}"
    : "+f"(d[0]),"+f"(d[1]),"+f"(d[2]),"+f"(d[3]),"+f"(d[4]),"+f"(d[5]),"+f"(d[6]),"+f"(d[7]),"+f"(d[8]),"+f"(d[9]),"+f"(d[10]),"+f"(d[11]),"+f"(d[12]),"+f"(d[13]),"+f"(d[14]),"+f"(d[15]),"+f"(d[16]),"+f"(d[17]),"+f"(d[18]),"+f"(d[19]),"+f"(d[20]),"+f"(d[21]),"+f"(d[22]),"+f"(d[23]),"+f"(d[24]),"+f"(d[25]),"+f"(d[26]),"+f"(d[27]),"+f"(d[28]),"+f"(d[29]),"+f"(d[30]),"+f"(d[31]),"+f"(d[32]),"+f"(d[33]),"+f"(d[34]),"+f"(d[35]),"+f"(d[36]),"+f"(d[37]),"+f"(d[38]),"+f"(d[39]),"+f"(d[40]),"+f"(d[41]),"+f"(d[42]),"+f"(d[43]),"+f"(d[44]),"+f"(d[45]),"+f"(d[46]),"+f"(d[47]),"+f"(d[48]),"+f"(d[49]),"+f"(d[50]),"+f"(d[51]),"+f"(d[52]),"+f"(d[53]),"+f"(d[54]),"+f"(d[55]),"+f"(d[56]),"+f"(d[57]),"+f"(d[58]),"+f"(d[59]),"+f"(d[60]),"+f"(d[61]),"+f"(d[62]),"+f"(d[63]),"+f"(d[64]),"+f"(d[65]),"+f"(d[66]),"+f"(d[67]),"+f"(d[68]),"+f"(d[69]),"+f"(d[70]),"+f"(d[71]),"+f"(d[72]),"+f"(d[73]),"+f"(d[74]),"+f"(d[75]),"+f"(d[76]),"+f"(d[77]),"+f"(d[78]),"+f"(d[79]),"+f"(d[80]),"+f"(d[81]),"+f"(d[82]),"+f"(d[83]),"+f"(d[84]),"+f"(d[85]),"+f"(d[86]),"+f"(d[87]),"+f"(d[88]),"+f"(d[89]),"+f"(d[90]),"+f"(d[91]),"+f"(d[92]),"+f"(d[93]),"+f"(d[94]),"+f"(d[95])
    : "l"(da), "l"(db), "r"(sc), "n"(TA), "n"(TB));
}
template <int TB> __device__ __forceinline__ void wgmma_rs_n96(float (&d)[48], uint32_t a0, uint32_t a1, uint32_t a2, uint32_t a3, uint64_t db, int sc) {
  asm volatile("{.reg .pred p; setp.ne.b32 p, %53, 0; wgmma.mma_async.sync.aligned.m64n96k16.f32.bf16.bf16 {%0,%1,%2,%3,%4,%5,%6,%7,%8,%9,%10,%11,%12,%13,%14,%15,%16,%17,%18,%19,%20,%21,%22,%23,%24,%25,%26,%27,%28,%29,%30,%31,%32,%33,%34,%35,%36,%37,%38,%39,%40,%41,%42,%43,%44,%45,%46,%47}, {%48,%49,%50,%51}, %52, p, 1, 1, %54;}"
    : "+f"(d[0]),"+f"(d[1]),"+f"(d[2]),"+f"(d[3]),"+f"(d[4]),"+f"(d[5]),"+f"(d[6]),"+f"(d[7]),"+f"(d[8]),"+f"(d[9]),"+f"(d[10]),"+f"(d[11]),"+f"(d[12]),"+f"(d[13]),"+f"(d[14]),"+f"(d[15]),"+f"(d[16]),"+f"(d[17]),"+f"(d[18]),"+f"(d[19]),"+f"(d[20]),"+f"(d[21]),"+f"(d[22]),"+f"(d[23]),"+f"(d[24]),"+f"(d[25]),"+f"(d[26]),"+f"(d[27]),"+f"(d[28]),"+f"(d[29]),"+f"(d[30]),"+f"(d[31]),"+f"(d[32]),"+f"(d[33]),"+f"(d[34]),"+f"(d[35]),"+f"(d[36]),"+f"(d[37]),"+f"(d[38]),"+f"(d[39]),"+f"(d[40]),"+f"(d[41]),"+f"(d[42]),"+f"(d[43]),"+f"(d[44]),"+f"(d[45]),"+f"(d[46]),"+f"(d[47])
    : "r"(a0), "r"(a1), "r"(a2), "r"(a3), "l"(db), "r"(sc), "n"(TB));
}
template <int N, int TA, int TB> __device__ __forceinline__ void wgmma_ss(float (&d)[N / 2], uint64_t da, uint64_t db, int sc) {
  if constexpr (N == 48) wgmma_ss_n48<TA, TB>(d, da, db, sc);
  else if constexpr (N == 80) wgmma_ss_n80<TA, TB>(d, da, db, sc);
  else if constexpr (N == 160) wgmma_ss_n160<TA, TB>(d, da, db, sc);
  else if constexpr (N == 192) wgmma_ss_n192<TA, TB>(d, da, db, sc);
}
template <int N, int TB> __device__ __forceinline__ void wgmma_rs(float (&d)[N / 2], uint32_t a0, uint32_t a1, uint32_t a2, uint32_t a3, uint64_t db, int sc) {
  if constexpr (N == 96) wgmma_rs_n96<TB>(d, a0, a1, a2, a3, db, sc);
}

constexpr uint32_t PAGE = 10240;
constexpr uint32_t OFF_RING = 16 * PAGE;
constexpr uint32_t OFF_KVB = 49152;
constexpr uint32_t OFF_R1 = 35840;
constexpr uint32_t OFF_MISC = 22 * PAGE;
constexpr uint32_t OFF_BAR = OFF_MISC;
constexpr uint32_t OFF_LN1 = OFF_MISC + 2048;
constexpr uint32_t OFF_CSKV = OFF_MISC + 3072;
constexpr uint32_t OFF_CSQ = OFF_MISC + 3712;
constexpr uint32_t OFF_CB1 = OFF_MISC + 4032;
constexpr uint32_t OFF_B2 = OFF_MISC + 5568;
constexpr uint32_t OFF_EPOCH = OFF_MISC + 5888;
constexpr uint32_t SMEM_BYTES = OFF_MISC + 5904;

enum : int {
  FX = 0, FKV = 13, FQ = 33, FWO = 43, FW1 = 51, FW2 = 59,
  AO = 71, AH = 87, AF = 103,
  DKV = 127, DQ = 147, DW = 157, DF = 173, DG = 189,
  SO = 213, SH = 215, SF = 217, SFB = 219,
  RX = 221, RXK = 223, SIDE = 224, SIDE2 = 225, KVB = 226, RKV = 227, PX = 228, PF = 229, END = 231
};

__device__ uint32_t g_epoch;
__device__ uint4 g_ln1[2048];
__device__ uint4 g_cs[4 * 1728];
__device__ uint4 g_hstat[32 * 8 * 64];
__device__ __align__(128) float g_kv[8 * 80 * 24];
__device__ __align__(128) uint32_t g_flag_z[8 * 32];
__device__ __align__(128) uint32_t g_flag_kv[8 * 32];
__device__ __align__(128) uint32_t g_flag[3 * 32 * 32];
__device__ __align__(128) uint8_t g_act[3 * 32 * 8 * 24576];

struct Maps { CUtensorMap m[8]; };
enum : int { M_X, M_KV, M_Q, M_QR, M_WO, M_WOR, M_W1, M_W2 };

#define TL(id)
#define TLW(id)

constexpr int SPIN_LIMIT = 1 << 19;

__device__ __forceinline__ bool elect_one() {
  uint32_t p;
  asm volatile("{.reg .pred P; elect.sync _|P, 0xffffffff; selp.u32 %0,1,0,P;}" : "=r"(p));
  return p;
}
__device__ __forceinline__ void mbar_wait(uint32_t bar) {
  asm volatile("{.reg .pred p;\nW: mbarrier.try_wait.parity.shared::cta.b64 p, [%0], 0;\n@!p bra W;}" ::"r"(bar) : "memory");
}
__device__ __forceinline__ void mbar_wait_cluster(uint32_t bar) {
  asm volatile("{.reg .pred p;\nW: mbarrier.try_wait.parity.acquire.cluster.shared::cta.b64 p, [%0], 0;\n@!p bra W;}" ::"r"(bar) : "memory");
}
__device__ __forceinline__ void mbar_wait_wd(uint32_t bar) {
  asm volatile("{.reg .pred p; .reg .u32 n; mov.u32 n, 0;\n"
               "W: mbarrier.try_wait.parity.shared::cta.b64 p, [%0], 0;\n"
               "@p bra D; add.u32 n, n, 1; setp.gt.u32 p, n, %1; @p trap; bra W;\n"
               "D: }" ::"r"(bar), "n"(SPIN_LIMIT) : "memory");
}
__device__ __forceinline__ void mbar_arrive(uint32_t bar, uint32_t n) {
  asm volatile("mbarrier.arrive.shared::cta.b64 _, [%0], %1;" ::"r"(bar), "r"(n) : "memory");
}
__device__ __forceinline__ void mbar_arrive_remote(uint32_t bar) {
  asm volatile("mbarrier.arrive.shared::cluster.b64 _, [%0];" ::"r"(bar) : "memory");
}
__device__ __forceinline__ void mbar_expect(uint32_t bar, uint32_t bytes) {
  asm volatile("mbarrier.arrive.expect_tx.shared::cta.b64 _, [%0], %1;" ::"r"(bar), "r"(bytes) : "memory");
  asm volatile("mbarrier.arrive.shared::cta.b64 _, [%0], 7;" ::"r"(bar) : "memory");
}
__device__ __forceinline__ void tma2d(uint32_t dst, const CUtensorMap* tm, uint32_t bar, int c0, int c1) {
  asm volatile("cp.async.bulk.tensor.2d.shared::cluster.global.mbarrier::complete_tx::bytes [%0],[%1,{%3,%4}],[%2];"
               ::"r"(dst), "l"(tm), "r"(bar), "r"(c0), "r"(c1) : "memory");
}
__device__ __forceinline__ void bulk_load(uint32_t dst, const void* src, uint32_t bytes, uint32_t bar) {
  asm volatile("cp.async.bulk.shared::cluster.global.mbarrier::complete_tx::bytes [%0],[%1],%2,[%3];"
               ::"r"(dst), "l"(src), "r"(bytes), "r"(bar) : "memory");
}
__device__ __forceinline__ void bulk_store(void* dst, uint32_t src, uint32_t bytes) {
  asm volatile("cp.async.bulk.global.shared::cta.bulk_group [%0],[%1],%2;" ::"l"(dst), "r"(src), "r"(bytes) : "memory");
}
__device__ __forceinline__ void bulk_commit_wait() {
  asm volatile("cp.async.bulk.commit_group;" ::: "memory");
  asm volatile("cp.async.bulk.wait_group 0;" ::: "memory");
}
__device__ __forceinline__ void l2_prefetch(const void* src, uint32_t bytes) {
  asm volatile("cp.async.bulk.prefetch.L2.global [%0], %1;" ::"l"(src), "r"(bytes) : "memory");
}
__device__ __forceinline__ void fence_gpu() { asm volatile("fence.acq_rel.gpu;" ::: "memory"); }
__device__ __forceinline__ void fence_async_smem() { asm volatile("fence.proxy.async.shared::cta;" ::: "memory"); }
__device__ __forceinline__ void fence_async_global() { asm volatile("fence.proxy.async.global;" ::: "memory"); }
__device__ __forceinline__ void st_flag(uint32_t* p, uint32_t v) {
  asm volatile("st.relaxed.gpu.global.u32 [%0], %1;" ::"l"(p), "r"(v) : "memory");
}
__device__ __forceinline__ uint32_t ld_acq(const uint32_t* p) {
  uint32_t v;
  asm volatile("ld.acquire.gpu.global.u32 %0, [%1];" : "=r"(v) : "l"(p) : "memory");
  return v;
}
__device__ __forceinline__ void wg_fence() { asm volatile("wgmma.fence.sync.aligned;" ::: "memory"); }
__device__ __forceinline__ void wg_commit() { asm volatile("wgmma.commit_group.sync.aligned;" ::: "memory"); }
template <int N> __device__ __forceinline__ void wg_wait() { asm volatile("wgmma.wait_group.sync.aligned %0;" ::"n"(N) : "memory"); }
template <int N> __device__ __forceinline__ void reg_fence(float (&a)[N]) {
#pragma unroll
  for (int i = 0; i < N; i++) asm volatile("" : "+f"(a[i])::"memory");
}
template <int ID, int N> __device__ __forceinline__ void named_bar() { asm volatile("bar.sync %0, %1;" ::"n"(ID), "n"(N) : "memory"); }
__device__ __forceinline__ uint64_t mkdesc(uint32_t addr, uint32_t lbo, uint32_t sbo, uint32_t swz) {
  return (uint64_t)(((addr & 0x3FFFF) >> 4) | ((lbo >> 4) << 16)) | ((uint64_t)((sbo >> 4) | (swz << 30)) << 32);
}
__device__ __forceinline__ uint32_t pack2(float lo, float hi) {
  uint32_t r;
  asm("cvt.rn.bf16x2.f32 %0, %1, %2;" : "=r"(r) : "f"(hi), "f"(lo));
  return r;
}
__device__ __forceinline__ float bf_lo(uint32_t v) { return __uint_as_float(v << 16); }
__device__ __forceinline__ float bf_hi(uint32_t v) { return __uint_as_float(v & 0xffff0000u); }
__device__ __forceinline__ void stsm4(uint32_t addr, uint32_t a, uint32_t b, uint32_t c, uint32_t d) {
  asm volatile("stmatrix.sync.aligned.m8n8.x4.shared.b16 [%0], {%1,%2,%3,%4};" ::"r"(addr), "r"(a), "r"(b), "r"(c), "r"(d) : "memory");
}
__device__ __forceinline__ float2 lds64(uint32_t a) {
  float2 v;
  asm volatile("ld.shared.v2.f32 {%0,%1}, [%2];" : "=f"(v.x), "=f"(v.y) : "r"(a) : "memory");
  return v;
}
__device__ __forceinline__ float4 lds128(uint32_t a) {
  float4 v;
  asm volatile("ld.shared.v4.f32 {%0,%1,%2,%3}, [%4];" : "=f"(v.x), "=f"(v.y), "=f"(v.z), "=f"(v.w) : "r"(a) : "memory");
  return v;
}
__device__ __forceinline__ uint32_t lds32(uint32_t a) {
  uint32_t v;
  asm volatile("ld.shared.u32 %0, [%1];" : "=r"(v) : "r"(a) : "memory");
  return v;
}
__device__ __forceinline__ void sts32(uint32_t a, uint32_t v) { asm volatile("st.shared.u32 [%0], %1;" ::"r"(a), "r"(v) : "memory"); }
__device__ __forceinline__ void sts64(uint32_t a, uint32_t x, uint32_t y) {
  asm volatile("st.shared.v2.u32 [%0], {%1,%2};" ::"r"(a), "r"(x), "r"(y) : "memory");
}
__device__ __forceinline__ void sts128(uint32_t a, uint32_t x, uint32_t y, uint32_t z, uint32_t w) {
  asm volatile("st.shared.v4.u32 [%0], {%1,%2,%3,%4};" ::"r"(a), "r"(x), "r"(y), "r"(z), "r"(w) : "memory");
}
__device__ __forceinline__ float ex2(float x) {
  float r;
  asm("ex2.approx.ftz.f32 %0, %1;" : "=f"(r) : "f"(x));
  return r;
}
__device__ __forceinline__ float rcp(float x) {
  float r;
  asm("rcp.approx.ftz.f32 %0, %1;" : "=f"(r) : "f"(x));
  return r;
}
constexpr float LOG2E = 1.4426950408889634f, LN2 = 0.6931471805599453f;
__device__ __forceinline__ float phi2(float t2) { return fmaf(fmaxf(t2, 0.f), LN2, ex2(fminf(t2, 0.f))) + 1e-6f; }
__device__ __forceinline__ float gelu(float y) {
  float p = fmaf(y * y, 0.044715f * 0.7978845608028654f, 0.7978845608028654f);
  float th;
  asm("tanh.approx.f32 %0, %1;" : "=f"(th) : "f"(y * p));
  float hy = 0.5f * y;
  return fmaf(hy, th, hy);
}
__device__ __forceinline__ void mma16816(float (&d)[4], uint32_t a0, uint32_t a1, uint32_t a2, uint32_t a3, uint32_t b0, uint32_t b1) {
  asm("mma.sync.aligned.m16n8k16.row.col.f32.bf16.bf16.f32 {%0,%1,%2,%3}, {%4,%5,%6,%7}, {%8,%9}, {%0,%1,%2,%3};"
      : "+f"(d[0]), "+f"(d[1]), "+f"(d[2]), "+f"(d[3]) : "r"(a0), "r"(a1), "r"(a2), "r"(a3), "r"(b0), "r"(b1));
}
constexpr uint32_t ONES = 0x3F803F80u;
__device__ __forceinline__ void ll_store(uint4* p, float a, float b, uint32_t tag) {
  asm volatile("st.relaxed.gpu.global.v4.u32 [%0], {%1,%2,%3,%2};" ::"l"(p), "r"(__float_as_uint(a)), "r"(tag), "r"(__float_as_uint(b)) : "memory");
}
template <int N>
__device__ __forceinline__ float2 ll_sum(const uint4* p, int stride, uint32_t tag) {
  float2 r;
  uint32_t bad;
  int it = 0;
  do {
    r = make_float2(0.f, 0.f);
    bad = 0;
#pragma unroll
    for (int m = 0; m < N; m++) {
      uint32_t a, t0, b, t1;
      asm volatile("ld.relaxed.gpu.global.v4.u32 {%0,%1,%2,%3}, [%4];" : "=r"(a), "=r"(t0), "=r"(b), "=r"(t1) : "l"(p + m * stride) : "memory");
      r.x += __uint_as_float(a);
      r.y += __uint_as_float(b);
      bad |= (t0 ^ tag) | (t1 ^ tag);
    }
  } while (bad && ++it < SPIN_LIMIT);
  return r;
}
__device__ __forceinline__ void poll_flags(const uint32_t* f, uint32_t want, uint32_t& mask, uint32_t epoch, int lane) {
  int it = 0;
  while ((mask & want) != want && ++it < SPIN_LIMIT) {
    mask = __ballot_sync(0xffffffffu, ld_acq(f + lane) == epoch);
    fence_async_global();
  }
}
template <bool PHI>
__device__ __forceinline__ void ln_pair(const float* a, uint32_t csaddr, const float2 (&st)[2], uint32_t* o) {
#pragma unroll
  for (int tt = 0; tt < 2; tt++) {
    const float2 cs = lds64(csaddr + tt * 32);
#pragma unroll
    for (int hh = 0; hh < 2; hh++) {
      float y0 = fmaf(st[hh].x, a[4 * tt + 2 * hh], st[hh].y * cs.x), y1 = fmaf(st[hh].x, a[4 * tt + 2 * hh + 1], st[hh].y * cs.y);
      if (PHI) { y0 = phi2(y0); y1 = phi2(y1); }
      o[2 * tt + hh] = pack2(y0, y1);
    }
  }
}

__global__ void __cluster_dims__(2, 1, 1) __launch_bounds__(384, 1)
fused_block_kernel(const __grid_constant__ Maps maps, const __nv_bfloat16* __restrict__ x, const __nv_bfloat16* __restrict__ wqkv,
                   const __nv_bfloat16* __restrict__ wo, const __nv_bfloat16* __restrict__ w1,
                   const __nv_bfloat16* __restrict__ b1, const __nv_bfloat16* __restrict__ w2,
                   const __nv_bfloat16* __restrict__ b2, __nv_bfloat16* __restrict__ out) {
  extern __shared__ __align__(1024) uint8_t smem_raw[];
  const uint32_t sb = (uint32_t)__cvta_generic_to_shared(smem_raw);
  const uint32_t bars = sb + OFF_BAR;
  const int warp = __shfl_sync(0xffffffffu, threadIdx.x >> 5, 0);
  const int lane = threadIdx.x & 31;

  if (elect_one()) {
    if (warp < 8) asm volatile("prefetch.tensormap [%0];" ::"l"(&maps.m[warp]) : "memory");
#pragma unroll
    for (int n = 0; n < 20; n++) asm volatile("mbarrier.init.shared::cta.b64 [%0], 8;" ::"r"(bars + 160 * warp + 8 * n) : "memory");
    asm volatile("fence.mbarrier_init.release.cluster;" ::: "memory");
  }
  const int cl = blockIdx.x >> 1, q = blockIdx.x & 1;
  int oct, u4;
  if (cl < 4) { oct = 0; u4 = cl; }
  else if (cl < 36) { oct = 1 + 2 * ((cl - 4) & 7); u4 = (cl - 4) >> 3; }
  else { u4 = (cl - 36) / 7; oct = 2 + 2 * ((cl - 36) - 7 * u4); }
  const int i = 2 * (oct & 7) + (u4 >> 1), p = 2 * (oct >> 3) + (u4 & 1);
  const int j = 2 * p + q;
  __syncthreads();
  asm volatile("barrier.cluster.arrive.relaxed.aligned;" ::: "memory");

  if (warp >= 8) {
    asm volatile("setmaxnreg.dec.sync.aligned.u32 56;");
    if (warp == 8) {
      if (elect_one()) {
        TL(41);
#pragma unroll 1
        for (int op = 0; op < 58; op++) {
          int wa, wb, m0, m1, cA = 80 * j + 16 * q, cB = 80 * j + 64 - 64 * q, cC = -1, w = 32, k0, xc = -1, xs;
          uint32_t dst, as, bytes;
          int bar = FKV + op;
          if (op < 20) {
            wa = wb = op < 6 ? -1 : DKV + op - 6;
            m0 = m1 = M_KV;
            cA = 640 + 160 * p + 96 * q; cB = 704 + 160 * p + 640 * q; cC = cA + 640;
            k0 = 32 * op; dst = OFF_RING + (op % 6) * PAGE; as = 2048; bytes = 10240;
            if (op == 0) xc = 0;
            else if ((op & 1) && op < 18) xc = (op + 1) >> 1;
            xs = xc;
          } else if (op < 30) {
            const int t = op - 20;
            wa = wb = t < 5 ? DKV + (t < 3 ? 15 + t : 19) : DQ + t - 5;
            m0 = M_Q; m1 = M_QR;
            k0 = 64 * (t < 7 ? t + 3 : t - 7); dst = OFF_RING + ((t + 2) % 5) * 12288; as = 4096; bytes = 10240;
            if (t >= 6 && t < 9) { xc = t - 6; xs = t + 4; }
          } else if (op < 46) {
            int t = (op - 30) & 7;
            if (op < 38) {
              wa = wb = DQ + ((0x99976665u >> (4 * t)) & 15);
              t = (0x54076321u >> (4 * t)) & 7;
              bar = FWO + t;
              m0 = M_WO; m1 = M_WOR;
              dst = 10 * PAGE + t * 15360; as = 5120; bytes = 12800;
            } else {
              wa = t == 0 ? DQ + 1 : t < 5 ? DW + 2 * t - 1 : DF + t - 5;
              wb = wa + 8;
              m0 = m1 = M_W1;
              cA = 192 * j; cB = cA + 128; w = 64;
              dst = (7 + 3 * (t < 5 ? t : t - 5)) * PAGE; as = 10240; bytes = 30720;
            }
            k0 = 80 * (t == 0 ? j : (t - 1 < j ? t - 1 : t));
          } else {
            const int t = op - 46, t7 = t < 7 ? t : t - 7;
            const int uu = t < 3 ? t : (t - 3) / 3, n = t - 3 - 3 * uu;
            k0 = 192 * (t < 3 ? j : 2 * (n < p ? n : n + 1) + q) + 64 * uu;
            wa = t < 7 ? DF + ((0x7665443 >> (4 * t)) & 7) : DG + t7;
            wb = wa + (t < 7 ? 8 : 12);
            m0 = m1 = M_W2;
            cA = 160 * p + 96 * q; cB = 160 * p + 64; cC = 160 * p + 96 - 96 * q;
            dst = (t7 < 3 ? 16 + 2 * t7 : 1 + 2 * t7) * PAGE; as = 4096; bytes = 20480;
          }
          if (wa >= 0) {
            mbar_wait(bars + 8 * wa);
            mbar_wait(bars + 8 * wb);
          }
          if (xc >= 0) {
            mbar_expect(bars + 8 * (FX + xs), 16384);
            tma2d(sb + (xs < 10 ? xs : xs - 6) * 16384, &maps.m[M_X], bars + 8 * (FX + xs), 64 * xc, 128 * i);
          }
          const uint32_t fb = bars + 8 * bar;
          dst += sb;
          mbar_expect(fb, bytes);
          tma2d(dst, &maps.m[m0], fb, cA, k0);
          tma2d(dst + as, &maps.m[m0], fb, cA + w, k0);
          tma2d(dst + 2 * as, &maps.m[m1], fb, cB, k0);
          if (cC >= 0) {
            tma2d(dst + 3 * as, &maps.m[m0], fb, cC, k0);
            tma2d(dst + 4 * as, &maps.m[m0], fb, cC + w, k0);
          }
          if (op == 5) TL(40);
        }
      }
    } else {
      uint32_t epoch;
      asm volatile("ld.relaxed.gpu.global.u32 %0, [%1];" : "=r"(epoch) : "l"(&g_epoch) : "memory");
      epoch += 1;
      const int g = lane >> 2, c = lane & 3, unit = i * 8 + j;
      auto colsum = [&](const __nv_bfloat16* wp, int ld, int rounds, uint4* dst) {
        const uint32_t id = (g >> 1) == c ? (g & 1 ? 0x3F800000u : 0x3F80u) : 0u;
        float d0[4] = {0.f, 0.f, 0.f, 0.f}, d1[4] = {0.f, 0.f, 0.f, 0.f};
        wp += g * ld + c * 8;
#pragma unroll 1
        for (int r = 0; r < rounds; r++) {
          uint4 v[5];
#pragma unroll
          for (int m = 0; m < 5; m++) v[m] = __ldg(reinterpret_cast<const uint4*>(wp + m * 8 * ld));
          wp += 40 * ld;
#pragma unroll
          for (int m = 0; m < 5; m++) {
            mma16816(d0, v[m].x, v[m].y, v[m].z, v[m].w, id, 0u);
            mma16816(d1, v[m].x, v[m].y, v[m].z, v[m].w, 0u, id);
          }
        }
#pragma unroll 1
        for (int o = 4; o < 32; o <<= 1) {
#pragma unroll
          for (int e = 0; e < 4; e++) {
            d0[e] += __shfl_xor_sync(0xffffffffu, d0[e], o);
            d1[e] += __shfl_xor_sync(0xffffffffu, d1[e], o);
          }
        }
        if (g & 2) { d0[0] = d1[0]; d0[1] = d1[1]; d0[2] = d1[2]; d0[3] = d1[3]; }
        if (g < 4) ll_store(dst + 4 * c + g, g & 1 ? d0[2] : d0[0], g & 1 ? d0[3] : d0[1], epoch);
      };
      uint32_t mask = 0;
      if (warp == 9) {
        if (lane < 30) *reinterpret_cast<float4*>(g_kv + j * 1920 + i * 120 + lane * 4) = make_float4(0.f, 0.f, 0.f, 0.f);
        if (lane == 0) {
          mbar_expect(bars + 8 * RX, 20480);
          mbar_expect(bars + 8 * (RX + 1), 20480);
          mbar_expect(bars + 8 * RXK, 4096);
          sts32(sb + OFF_EPOCH, epoch);
        }
#pragma unroll 1
        for (int h = 0; h < 2; h++) {
          const int row = 128 * i + 16 * j + 8 * h + g;
          float ds[4] = {0.f, 0.f, 0.f, 0.f}, d0[4] = {0.f, 0.f, 0.f, 0.f}, d1[4] = {0.f, 0.f, 0.f, 0.f};
#pragma unroll 1
          for (int r = 0; r < 4; r++) {
            uint4 v[5];
#pragma unroll
            for (int m = 0; m < 5; m++) v[m] = __ldg(reinterpret_cast<const uint4*>(x + row * 640) + c + 4 * m + 20 * r);
#pragma unroll
            for (int m = 0; m < 5; m++) {
              mma16816(ds, v[m].x, v[m].y, v[m].z, v[m].w, ONES, ONES);
              mma16816(d0, v[m].x, v[m].y, v[m].z, v[m].w, v[m].x, v[m].z);
              mma16816(d1, v[m].x, v[m].y, v[m].z, v[m].w, v[m].y, v[m].w);
            }
          }
          const float mean = (ds[0] + ds[2]) * (1.f / 640.f);
          const float sq = g & 1 ? d0[1] + d1[3] : d0[0] + d1[2];
          const float rstd = rsqrtf(fmaxf(fmaf(-mean, mean, sq * (1.f / 640.f)), 0.f) + 1e-5f);
          if ((g >> 1) == c) ll_store(g_ln1 + row, rstd, -rstd * mean, epoch);
        }
        TL(10);
        __syncwarp();
        if (lane == 0) {
          fence_gpu();
          st_flag(g_flag_z + j * 32 + i, epoch);
        }
#pragma unroll 1
        for (int m = 0; m < 4; m++) {
          const float2 v = ll_sum<1>(g_ln1 + 128 * i + 32 * m + lane, 0, epoch);
          sts64(sb + OFF_LN1 + (32 * m + lane) * 8, __float_as_uint(v.x), __float_as_uint(v.y));
        }
        poll_flags(g_flag_z + j * 32, 0xffffu, mask, epoch, lane);
      } else {
        if (unit < 120) {
          const int half = unit >= 60, cg = unit - 60 * half, part = 2 * half + warp - 10;
          colsum(wqkv + part * 160 * 1920 + 32 * cg, 1920, 4, g_cs + part * 1728 + 16 * cg);
        }
        if (warp == 10) TL(8);
        if (lane == 0) {
          if (warp == 10) l2_prefetch(reinterpret_cast<const uint8_t*>(wo) + blockIdx.x * 6400, 6400);
          l2_prefetch(reinterpret_cast<const uint8_t*>(warp == 10 ? w1 : w2) + blockIdx.x * 15360, 15360);
        }
#pragma unroll 1
        for (int n = 64 * (warp - 10) + 2 * lane; n < 240; n += 128) {
          int col;
          if (n < 160) col = 160 * p + 96 * q + n + (n < 96 - 32 * q ? 640 : 1184);
          else {
            col = 80 * j + n - 160 + (q ? (n < 224 ? 16 : -64) : 0);
            const uint32_t bb = *reinterpret_cast<const uint32_t*>(b2 + col);
            sts64(sb + OFF_B2 + (n - 160) * 4, bb << 16, bb & 0xffff0000u);
          }
          const float2 v = ll_sum<4>(g_cs + (col >> 1), 1728, epoch);
          sts64(sb + OFF_CSKV + n * 4, __float_as_uint(v.x), __float_as_uint(v.y));
        }
      }
      __syncwarp();
      if (lane == 0) mbar_arrive(bars + 8 * SIDE, warp == 11 ? 2 : 3);
      if (warp == 9) TL(11);
      if (warp == 10) TL(9);
      const int ht = (warp - 9) * 32 + lane;
      mbar_wait_wd(bars + 8 * DQ);
#pragma unroll 1
      for (int m = 0; m < 10; m++) sts128(sb + OFF_KVB + (m * 96 + ht) * 16, 0, 0, 0, 0);
      named_bar<2, 96>();
      if (warp == 11) {
        mbar_wait_wd(bars + 8 * RKV);
        if (lane == 0) {
          fence_gpu();
          st_flag(g_flag_kv + j * 32 + i, epoch);
        }
        TL(5);
        __syncwarp();
      }
      mask = 0;
      poll_flags(g_flag_kv + j * 32, 0xffffu, mask, epoch, lane);
      if (warp == 9) TL(6);
      {
        float4 v[5];
#pragma unroll
        for (int m = 0; m < 5; m++)
          asm volatile("ld.relaxed.gpu.global.v4.f32 {%0,%1,%2,%3}, [%4];" : "=f"(v[m].x), "=f"(v[m].y), "=f"(v[m].z), "=f"(v[m].w)
                       : "l"(g_kv + j * 1920 + (ht + 96 * m) * 4) : "memory");
        const int d0 = ht / 6, part = ht - 6 * d0;
#pragma unroll
        for (int m = 0; m < 5; m++) {
          const int d = d0 + 16 * m, head = (d * 205) >> 12, n = 20 * head + 4 * part;
          const uint32_t a = sb + OFF_KVB + d * 16;
          const uint32_t lo = pack2(v[m].x, v[m].y), z = head & 1 ? lo << 16 : lo & 0xffffu;
          if (part < 5) sts64(a + (n >> 3) * 1280 + (n & 7) * 2, lo, pack2(v[m].z, v[m].w));
          else sts128(a + (10 + (head >> 1)) * 1280, z, z, z, z);
        }
      }
      fence_async_smem();
      __syncwarp();
      if (lane == 0) mbar_arrive(bars + 8 * KVB, warp == 11 ? 2 : 3);
      if (warp == 9) TL(7);

      if (warp == 11) {
        if (unit < 96) {
          const int half = unit >= 48, cg = unit - 48 * half;
          colsum(w1 + half * 320 * 1536 + 32 * cg, 1536, 8, g_cs + half * 1728 + 960 + 16 * cg);
        }
#pragma unroll 1
        for (int n = lane; n < 96; n += 32) {
          const uint32_t bb = *reinterpret_cast<const uint32_t*>(b1 + 192 * j + 2 * n);
          const float2 v = ll_sum<2>(g_cs + 960 + 96 * j + n, 1728, epoch);
          sts128(sb + OFF_CB1 + n * 16, __float_as_uint(v.x), __float_as_uint(v.y), bb << 16, bb & 0xffff0000u);
        }
        __syncwarp();
        if (elect_one()) {
          mbar_arrive(bars + 8 * SIDE2, 8);
          TL(18);
#pragma unroll 1
          for (int s = 0; s < 2; s++) {
            uint8_t* dst = g_act + ((64 + 2 * i + s) * 8 + j) * 24576;
            mbar_wait_wd(bars + 8 * (AF + 12 * s + 1));
            bulk_store(dst + 8192, sb + s * OFF_R1 + 8192, 8192);
            mbar_wait_wd(bars + 8 * (AF + 12 * s + 2));
            bulk_store(dst + 16384, sb + s * OFF_R1 + 16384, 8192);
            bulk_commit_wait();
            mbar_arrive(bars + 8 * (SFB + s), 8);
            fence_gpu();
            st_flag(g_flag + (64 + 2 * i + s) * 32 + 8 + j, epoch);
            TL(50 + s);
          }
          mbar_wait_wd(bars + 8 * END);
          if (blockIdx.x == 0) g_epoch = epoch;
        }
      } else {
        const int s = warp - 9;
#pragma unroll 1
        for (int ph = 0; ph < 3; ph++) {
          const int ab = ph < 2 ? AO + 16 * ph + 8 * s : AF + 12 * s;
          const uint32_t bytes = ph < 2 ? 10240 : 8192;
          uint8_t* gb = g_act + (ph * 32 + 2 * i + s) * 8 * 24576;
          uint32_t* fl = g_flag + (ph * 32 + 2 * i + s) * 32;
          mbar_wait(bars + 8 * ab);
          if (elect_one()) {
            bulk_store(gb + j * 24576, sb + s * (ph ? OFF_R1 : PAGE), bytes);
            bulk_commit_wait();
            mbar_arrive(bars + 8 * (SO + 2 * ph + s), 8);
            fence_gpu();
            st_flag(fl + j, epoch);
          }
          __syncwarp();
          TL(44 + 2 * ph + s);
          mask = 0;
#pragma unroll 1
          for (int t = ph < 2 ? 1 : 3; t < (ph < 2 ? 8 : 12); t++) {
            int cc = t - 1 < j ? t - 1 : t, bit = cc, wa, wb;
            uint32_t dst = s * OFF_R1, off = 0;
            if (ph == 0) {
              dst = (((s ? 0x21654321u : 0x01654320u) >> (4 * t)) & 7) * PAGE;
              wa = s ? (t < 7 ? DW + t : DW + 9) : (t < 6 ? AO + 8 : t == 6 ? DW + 8 : DW);
              wb = !s && t == 6 ? SO + 1 : wa;
            } else if (ph == 1) {
              dst += (t % 3) * PAGE;
              wa = wb = t < 3 ? DW + 15 : DF + 8 * s + t - 3;
            } else {
              const int uu = (t - 3) / 3, n = t - 3 - 3 * uu;
              cc = 2 * (n < p ? n : n + 1) + q;
              bit = cc + (uu ? 8 : 0);
              off = uu * 8192;
              dst += (t & 3) * 8192;
              wa = t == 3 ? ab : DG + 12 * s + t - 4;
              wb = t == 5 ? SFB + s : wa;
            }
            mbar_wait(bars + 8 * wa);
            mbar_wait(bars + 8 * wb);
            poll_flags(fl, 1u << bit, mask, epoch, lane);
            if (t == (ph < 2 ? 1 : 3)) TL(52 + 2 * ph + s);
            if (elect_one()) {
              mbar_expect(bars + 8 * (ab + t), bytes);
              bulk_load(sb + dst, gb + cc * 24576 + off, bytes, bars + 8 * (ab + t));
            }
            __syncwarp();
          }
        }
      }
    }
    __syncwarp();
    asm volatile("barrier.cluster.wait.aligned;" ::: "memory");
  } else {
    asm volatile("setmaxnreg.inc.sync.aligned.u32 224;");
    const int s = warp >> 2, w = warp & 3, tid = threadIdx.x & 127, c = lane & 3, g = lane >> 2;
    const bool l0 = lane == 0;
    uint32_t sb_peer;
    asm volatile("mapa.shared::cluster.u32 %0, %1, %2;" : "=r"(sb_peer) : "r"(sb), "r"(q ^ 1));
    asm volatile("barrier.cluster.wait.aligned;" ::: "memory");
    const int lp4 = 4 - 4 * q;
    const int row0 = 128 * i + 64 * s + 16 * w;
    uint32_t pq[20];
    uint32_t epoch;
    {
      float acc[80];
      auto kv_step = [&](int st, int slot, int first) {
        if ((st & 1) == 0) mbar_wait(bars + 8 * (FX + (st >> 1)));
        mbar_wait(bars + 8 * (FKV + st));
        const uint64_t da = mkdesc(sb + s * 8192 + (st >> 1) * 16384 + (st & 1) * 64, 16, 1024, 1);
        const uint64_t db = mkdesc(sb + OFF_RING + slot * PAGE, 2048, 512, 2);
        wg_fence();
        wgmma_ss<160, 0, 1>(acc, da, db, !first);
        wgmma_ss<160, 0, 1>(acc, da + 2, db + 64, 1);
        wg_commit();
      };
      kv_step(0, 0, 1);
      if (s == 0) TLW(0);
#pragma unroll 1
      for (int st = 1, slot = 1; st < 20; st++) {
        kv_step(st, slot, 0);
        wg_wait<1>();
        if (l0) {
          mbar_arrive(bars + 8 * (DKV + st - 1), 1);
          if (st == 2) mbar_arrive_remote(sb_peer + OFF_BAR + 8 * PX);
        }
        if (++slot == 6) slot = 0;
      }
      if (s == 0) TLW(12);
      float accq[40];
      auto q_step = [&](int t, int xs, int slot, int first) {
        mbar_wait(bars + 8 * (FQ + t));
        const uint64_t da = mkdesc(sb + s * 8192 + xs * 16384, 16, 1024, 1);
        const uint64_t db = mkdesc(sb + OFF_RING + slot * 12288, 4096, 512, 2);
        wg_fence();
#pragma unroll
        for (int ks = 0; ks < 4; ks++) wgmma_ss<80, 0, 1>(accq, da + 2 * ks, db + 64 * ks, !(first && ks == 0));
        wg_commit();
      };
      mbar_wait(bars + 8 * SIDE);
      epoch = lds32(sb + OFF_EPOCH);
      float2 sk[2], sv[2];
#pragma unroll
      for (int r = 0; r < 2; r++) {
        sv[r] = lds64(sb + OFF_LN1 + (64 * s + 16 * w + g + 8 * r) * 8);
        sk[r] = make_float2(sv[r].x * LOG2E, sv[r].y * LOG2E);
      }
      mbar_wait_cluster(bars + 8 * PX);
      q_step(0, 3, 2, 1);
      wg_wait<1>();
      reg_fence(acc);
      if (l0) mbar_arrive(bars + 8 * (DKV + 19), 1);
      if (s == 0) TLW(1);
      const uint32_t kbase = sb + (q ? 0 : 22528), vbase = sb + (q ? 20480 : 0);
      const int hi = lane >> 4;
      const uint32_t rowoff = (64 * s + 16 * w + (lane & 15)) * 16;
      const uint32_t csa = sb + OFF_CSKV + c * 8;
      {
        uint32_t keep[4], send[4];
        if (q == 0) {
          ln_pair<true>(acc + 32, csa + 4 * 64, sk, keep);
          ln_pair<true>(acc + 40, csa + 5 * 64, sk, send);
        } else {
          ln_pair<false>(acc + 32, csa + 4 * 64, sv, send);
          ln_pair<false>(acc + 40, csa + 5 * 64, sv, keep);
        }
#pragma unroll
        for (int r = 0; r < 4; r++)
          asm volatile("st.async.shared::cluster.mbarrier::complete_tx::bytes.b32 [%0], %1, [%2];"
                       ::"r"(sb_peer + (r >> 1) * 2048 + (64 * s + 16 * w + 8 * (r & 1)) * 16 + lane * 4),
                       "r"(send[r]), "r"(sb_peer + OFF_BAR + 8 * RXK) : "memory");
        stsm4((q ? vbase + 6 * 2048 : kbase + 8 * 2048) + hi * 2048 + rowoff, keep[0], keep[1], keep[2], keep[3]);
      }
      q_step(1, 4, 3, 0);
#pragma unroll
      for (int P = 0; P < 4; P++) {
        uint32_t r[4];
        ln_pair<true>(acc + 8 * P, csa + P * 64, sk, r);
        stsm4(kbase + (2 * (P + q) + hi) * 2048 + rowoff, r[0], r[1], r[2], r[3]);
        if (P == 1) q_step(2, 5, 4, 0);
      }
#pragma unroll
      for (int P = 6; P < 10; P++) {
        uint32_t r[4];
        ln_pair<false>(acc + 8 * P, csa + P * 64, sv, r);
        const uint32_t pos = (uint32_t)(0x10432A9876ull >> (8 * (P - 6))) >> (8 * q + 4 * hi) & 15;
        stsm4(vbase + pos * 2048 + rowoff, r[0], r[1], r[2], r[3]);
      }
      if (lane < 16) sts128(vbase + 5 * 2048 + rowoff, ONES, ONES, ONES, ONES);
      if (s == 0) TLW(2);
      mbar_wait_cluster(bars + 8 * RXK);
      fence_async_smem();
      named_bar<1, 256>();
      if (s == 0) TLW(3);
      float kv[24];
      {
        const uint64_t da = mkdesc(kbase + s * 10240, 128, 2048, 0), db = mkdesc(vbase + 10240 - s * 10240, 128, 2048, 0);
        wg_fence();
#pragma unroll
        for (int kk = 0; kk < 8; kk++) wgmma_ss<48, 1, 1>(kv, da + 16 * kk, db + 16 * kk, kk != 0);
        wg_commit();
      }
      wg_wait<1>();
      if (lane < 3) mbar_arrive(bars + 8 * (DQ + lane), 1);
#pragma unroll 1
      for (int t = 3, slot = 0; t < 10; t++) {
        if (t >= 7) mbar_wait(bars + 8 * (FX + 3 + t));
        q_step(t, t < 7 ? t + 3 : t - 3, slot, 0);
        if (++slot == 5) slot = 0;
        wg_wait<1>();
        if (t == 3) {
          reg_fence(kv);
          if (s == 0) TLW(4);
#pragma unroll
          for (int hh = 0; hh < 2; hh++) {
            const int r = 16 * w + g + 8 * hh;
            const int e0 = 2 * c - (r < 20 ? 0 : r < 40 ? 20 : 99);
            float* gp = g_kv + (j * 80 + 40 * s + r) * 24;
#pragma unroll
            for (int tt = 0; tt < 6; tt++) {
              const bool isz = s ? tt == 5 : tt == 0;
              const int e = e0 + 8 * (s ? (tt + 3) % 5 : tt - 1);
              const bool ok = isz ? (c == 0 && r < 40) : (unsigned)e < 20u;
              asm volatile("{.reg .pred p; setp.ne.u32 p, %3, 0; @p red.relaxed.gpu.global.add.v2.f32 [%0], {%1,%2};}"
                           ::"l"(gp + (isz ? 20 : e)), "f"(kv[4 * tt + 2 * hh]), "f"(kv[4 * tt + 2 * hh + 1]), "r"((uint32_t)ok) : "memory");
            }
          }
          __syncwarp();
        }
        if (l0) mbar_arrive(bars + 8 * (t == 3 ? RKV : DQ + t - 1), 1);
      }
      wg_wait<0>();
      reg_fence(accq);
      if (l0) mbar_arrive(bars + 8 * (DQ + 9), 1);
      if (s == 0) TLW(13);
#pragma unroll
      for (int P = 0; P < 5; P++) ln_pair<true>(accq + 8 * P, sb + OFF_CSQ + c * 8 + P * 64, sk, pq + 4 * P);
      if (s == 0) TLW(14);
    }
    const uint32_t rs = sb + s * OFF_R1;
    const uint32_t stoff = (lane >> 4) * 1024 + (16 * w + (lane & 15)) * 16;
    float accg[80];
    {
      uint32_t hp[20];
      const __nv_bfloat16* xr = x + (row0 + g) * 640 + 80 * j + 2 * c;
#pragma unroll
      for (int r = 0; r < 20; r++)
        hp[r] = __ldg(reinterpret_cast<const uint32_t*>(xr + (r & 1) * 8 * 640 + ((r >> 1) & 1) * 8 + 16 * (r < 16 ? (r >> 2) + q : lp4)));
      {
        float o[48];
        mbar_wait(bars + 8 * KVB);
        if (s == 0) TLW(15);
        const uint64_t dkv = mkdesc(sb + OFF_KVB, 128, 1280, 0);
        wg_fence();
#pragma unroll
        for (int ks = 0; ks < 5; ks++)
          wgmma_rs<96, 1>(o, pq[4 * ks], pq[4 * ks + 1], pq[4 * ks + 2], pq[4 * ks + 3], dkv + 16 * (ks < 4 ? ks + q : lp4), ks != 0);
        wg_commit();
        wg_wait<0>();
        reg_fence(o);
        float inv[2][4];
#pragma unroll
        for (int hh = 0; hh < 2; hh++)
#pragma unroll
          for (int h = 0; h < 4; h++) inv[hh][h] = rcp(o[40 + 4 * (h >> 1) + 2 * hh + (h & 1)] + 1e-6f);
        uint32_t r[4];
#pragma unroll
        for (int t = 0; t < 10; t++) {
#pragma unroll
          for (int hh = 0; hh < 2; hh++) {
            const float f = t == 2 ? (c < 2 ? inv[hh][0] : inv[hh][1]) : t == 7 ? (c < 2 ? inv[hh][2] : inv[hh][3]) : inv[hh][(8 * t) / 20];
            r[2 * (t & 1) + hh] = pack2(o[4 * t + 2 * hh] * f, o[4 * t + 2 * hh + 1] * f);
          }
          if (t & 1) stsm4(sb + s * PAGE + stoff + (t >> 1) * 2048, r[0], r[1], r[2], r[3]);
        }
        fence_async_smem();
        __syncwarp();
        if (l0) mbar_arrive(bars + 8 * (AO + 8 * s), 2);
        TLW(16 + s);
      }
      float acc[40];
#pragma unroll
      for (int r = 0; r < 20; r++) { acc[2 * r] = bf_lo(hp[r]); acc[2 * r + 1] = bf_hi(hp[r]); }
      reg_fence(acc);
#pragma unroll 1
      for (int t = 0; t < 8; t++) {
        mbar_wait(bars + 8 * (AO + 8 * s + t));
        mbar_wait(bars + 8 * (FWO + t));
        if (t == 1) TLW(20 + s);
        const uint32_t pg = ((s ? 0x21654321u : 0x01654320u) >> (4 * t)) & 7;
        const uint64_t da = mkdesc(sb + pg * PAGE, 1024, 128, 0), db = mkdesc(sb + 10 * PAGE + t * 15360, 5120, 512, 2);
        wg_fence();
#pragma unroll
        for (int ks = 0; ks < 5; ks++) wgmma_ss<80, 0, 1>(acc, da + 128 * ks, db + 64 * ks, 1);
        wg_commit();
        if (t == 0) wg_wait<0>();
        else wg_wait<1>();
        if (t != 1 && l0) mbar_arrive(bars + 8 * (DW + 8 * s + (t ? t - 1 : 0)), 2);
      }
      wg_wait<0>();
      reg_fence(acc);
      if (l0) mbar_arrive(bars + 8 * (DW + 8 * s + 7), 2);
      TLW(22 + s);
#pragma unroll
      for (int r = 0; r < 20; r++) hp[r] = pack2(acc[2 * r], acc[2 * r + 1]);
      mbar_wait(bars + 8 * (DW + 8 * s + 7));
#pragma unroll
      for (int ks = 0; ks < 5; ks++)
        stsm4(rs + stoff + (ks < 4 ? ks + q : lp4) * 2048, hp[4 * ks], hp[4 * ks + 1], hp[4 * ks + 2], hp[4 * ks + 3]);
      fence_async_smem();
      __syncwarp();
      if (l0) mbar_arrive(bars + 8 * (AH + 8 * s), 2);
      TLW(24 + s);
      float ds[4] = {0.f, 0.f, 0.f, 0.f}, d0[4] = {0.f, 0.f, 0.f, 0.f}, d1[4] = {0.f, 0.f, 0.f, 0.f};
#pragma unroll
      for (int ks = 0; ks < 5; ks++) {
        const uint32_t* a = hp + 4 * ks;
        mma16816(ds, a[0], a[1], a[2], a[3], ONES, ONES);
        mma16816(d0, a[0], a[1], a[2], a[3], a[0], a[2]);
        mma16816(d1, a[0], a[1], a[2], a[3], a[1], a[3]);
      }
      if ((g >> 1) == c) {
        uint4* hs = g_hstat + ((2 * i + s) * 8 + j) * 64 + 16 * w + g;
        ll_store(hs, ds[0], g & 1 ? d0[1] : d0[0], epoch);
        ll_store(hs + 8, ds[2], g & 1 ? d1[3] : d1[2], epoch);
      }
#pragma unroll
      for (int m = 0; m < 10; m++) {
        const float2 b = lds64(sb + OFF_B2 + (8 * m + 2 * c) * 4);
#pragma unroll
        for (int hh = 0; hh < 2; hh++) {
          const float v0 = b.x + bf_lo(hp[2 * m + hh]), v1 = b.y + bf_hi(hp[2 * m + hh]);
          const int e = 4 * m + 2 * hh;
          if (m < 8) { accg[e] = v0; accg[e + 1] = v1; accg[48 + e] = 0.f; accg[49 + e] = 0.f; }
          else { accg[e] = q ? 0.f : v0; accg[e + 1] = q ? 0.f : v1; accg[e + 8] = q ? v0 : 0.f; accg[e + 9] = q ? v1 : 0.f; }
        }
      }
    }
    float accf[96];
    auto f_step = [&](int t, int aslot, int bslot, int first) {
      mbar_wait(bars + 8 * (AH + 8 * s + t));
      mbar_wait(bars + 8 * (FW1 + t));
      if (t == 1) TLW(26 + s);
      const uint64_t da = mkdesc(rs + aslot * PAGE, 1024, 128, 0), db = mkdesc(sb + (7 + 3 * bslot) * PAGE, 10240, 1024, 1);
      wg_fence();
#pragma unroll
      for (int ks = 0; ks < 5; ks++) wgmma_ss<192, 0, 1>(accf, da + 128 * ks, db + 128 * ks, !(first && ks == 0));
      wg_commit();
    };
    f_step(0, 0, 0, 1);
    wg_wait<0>();
    if (l0) mbar_arrive(bars + 8 * (DF + 8 * s), 2);
#pragma unroll 1
    for (int t = 1; t < 8; t++) {
      f_step(t, (0x4924 >> (2 * t)) & 3, t < 5 ? t : t - 5, 0);
      wg_wait<1>();
      if (t > 1 && l0) mbar_arrive(bars + 8 * (DF + 8 * s + t - 1), 2);
    }
    float ra[2], rb[2];
#pragma unroll
    for (int hh = 0; hh < 2; hh++) {
      float2 v = ll_sum<2>(g_hstat + ((2 * i + s) * 8 + 2 * c) * 64 + 16 * w + g + 8 * hh, 64, epoch);
#pragma unroll
      for (int o = 1; o < 4; o <<= 1) {
        v.x += __shfl_xor_sync(0xffffffffu, v.x, o);
        v.y += __shfl_xor_sync(0xffffffffu, v.y, o);
      }
      const float mean = v.x * (1.f / 640.f);
      ra[hh] = rsqrtf(fmaxf(fmaf(-mean, mean, v.y * (1.f / 640.f)), 0.f) + 1e-5f);
      rb[hh] = -ra[hh] * mean;
    }
    mbar_wait(bars + 8 * SIDE2);
    wg_wait<0>();
    reg_fence(accf);
    if (l0) mbar_arrive(bars + 8 * (DF + 8 * s + 7), 2);
    TLW(28 + s);
    mbar_wait(bars + 8 * (DF + 8 * s + 7));
#pragma unroll 1
    for (int t = 0; t < 12; t++) {
      if (t < 3) {
        uint32_t r[4];
#pragma unroll
        for (int n = 0; n < 8; n++) {
          const float4 cb = lds128(sb + OFF_CB1 + (32 * t + 4 * n + c) * 16);
#pragma unroll
          for (int hh = 0; hh < 2; hh++) {
            const float* a = accf + 4 * n + 2 * hh;
            const float y0 = fmaf(ra[hh], a[0], fmaf(rb[hh], cb.x, cb.z)), y1 = fmaf(ra[hh], a[1], fmaf(rb[hh], cb.y, cb.w));
            r[2 * (n & 1) + hh] = pack2(gelu(y0), gelu(y1));
          }
          if (n & 1) stsm4(rs + stoff + t * 8192 + (n >> 1) * 2048, r[0], r[1], r[2], r[3]);
        }
        fence_async_smem();
        __syncwarp();
        if (l0) mbar_arrive(bars + 8 * (AF + 12 * s + t), 2);
#pragma unroll
        for (int e = 0; e < 64; e++) accf[e] = accf[e + 32];
        if (t == 2) TLW(30 + s);
      }
      mbar_wait(bars + 8 * (AF + 12 * s + t));
      mbar_wait(bars + 8 * (FW2 + t));
      if (t == 3) TLW(32 + s);
      const int t7 = t < 7 ? t : t - 7;
      const uint64_t da = mkdesc(rs + (t & 3) * 8192, 1024, 128, 0);
      const uint64_t db = mkdesc(sb + (t7 < 3 ? 16 + 2 * t7 : 1 + 2 * t7) * PAGE, 4096, 512, 2);
      wg_fence();
#pragma unroll
      for (int ks = 0; ks < 4; ks++) wgmma_ss<160, 0, 1>(accg, da + 128 * ks, db + 64 * ks, 1);
      wg_commit();
      wg_wait<1>();
      if (t != 0 && t != 3 && l0) {
        mbar_arrive(bars + 8 * (DG + 12 * s + t - 1), 2);
        if (t == 6 || t == 7) mbar_arrive_remote(sb_peer + OFF_BAR + 8 * (PF + t - 6));
      }
      if (t == 2) {
        wg_wait<0>();
        if (l0) mbar_arrive(bars + 8 * (DG + 12 * s + 2), 2);
      }
    }
    mbar_wait_cluster(bars + 8 * (PF + s));
    wg_wait<0>();
    reg_fence(accg);
    if (l0) mbar_arrive(bars + 8 * (DG + 12 * s + 11), 2);
    TLW(34 + s);
    {
      const uint32_t buf = (11 + 2 * s) * PAGE + tid * 16;
#pragma unroll
      for (int e = 0; e < 8; e++) {
        const float a = accg[32 + e], b = accg[40 + e];
        accg[32 + e] = q ? b : a;
        accg[40 + e] = q ? a : b;
      }
#pragma unroll
      for (int m = 0; m < 10; m++) {
        const float* a = accg + (m < 8 ? 48 + 4 * m : 8 + 4 * m);
        asm volatile("st.async.shared::cluster.mbarrier::complete_tx::bytes.v4.f32 [%0], {%1,%2,%3,%4}, [%5];"
                     ::"r"(sb_peer + buf + m * 2048), "f"(a[0]), "f"(a[1]), "f"(a[2]), "f"(a[3]),
                     "r"(sb_peer + OFF_BAR + 8 * (RX + s)) : "memory");
      }
      TLW(58 + s);
      mbar_wait(bars + 8 * (DG + 12 * s + 11));
      mbar_wait_cluster(bars + 8 * (RX + s));
      TLW(60 + s);
      const uint32_t stg = rs + w * 2816;
      const uint32_t sa = stg + (lane & 15) * 176 + (lane >> 4) * 16;
#pragma unroll
      for (int ks = 0; ks < 5; ks++) {
        const float4 r0 = lds128(sb + buf + (2 * ks) * 2048), r1 = lds128(sb + buf + (2 * ks + 1) * 2048);
        const float* a = accg + 8 * ks;
        stsm4(sa + (ks < 4 ? ks + q : lp4) * 32, pack2(a[0] + r0.x, a[1] + r0.y), pack2(a[2] + r0.z, a[3] + r0.w),
              pack2(a[4] + r1.x, a[5] + r1.y), pack2(a[6] + r1.z, a[7] + r1.w));
      }
      __syncwarp();
      __nv_bfloat16* outp = out + (row0 + (lane >> 1)) * 640 + 80 * j + (lane & 1) * 8;
#pragma unroll
      for (int m = 0; m < 5; m++)
        *reinterpret_cast<float4*>(outp + m * 16) = lds128(stg + (lane >> 1) * 176 + (lane & 1) * 16 + m * 32);
    }
    if (l0) mbar_arrive(bars + 8 * END, 1);
    TLW(36 + s);
  }
}

typedef CUresult (*EncodeFn)(CUtensorMap*, CUtensorMapDataType, cuuint32_t, void*, const cuuint64_t*, const cuuint64_t*,
                             const cuuint32_t*, const cuuint32_t*, CUtensorMapInterleave, CUtensorMapSwizzle,
                             CUtensorMapL2promotion, CUtensorMapFloatOOBfill);

void make_map(EncodeFn enc, CUtensorMap* tm, const void* base, int rows, int cols, int box_rows, int box_cols, CUtensorMapSwizzle sw) {
  const cuuint64_t dims[2] = {(cuuint64_t)cols, (cuuint64_t)rows}, strides[1] = {(cuuint64_t)cols * 2};
  const cuuint32_t box[2] = {(cuuint32_t)box_cols, (cuuint32_t)box_rows}, es[2] = {1, 1};
  enc(tm, CU_TENSOR_MAP_DATA_TYPE_BFLOAT16, 2, const_cast<void*>(base), dims, strides, box, es, CU_TENSOR_MAP_INTERLEAVE_NONE, sw,
      CU_TENSOR_MAP_L2_PROMOTION_L2_128B, CU_TENSOR_MAP_FLOAT_OOB_FILL_NONE);
}

}

extern "C" void kernel_launch(void* const* d_in, const int* in_sizes, int n_in, void* d_out, int out_size) {
  const __nv_bfloat16* x = (const __nv_bfloat16*)d_in[0];
  const __nv_bfloat16* wqkv = (const __nv_bfloat16*)d_in[1];
  const __nv_bfloat16* wo = (const __nv_bfloat16*)d_in[2];
  const __nv_bfloat16* w1 = (const __nv_bfloat16*)d_in[4];
  const __nv_bfloat16* b1 = (const __nv_bfloat16*)d_in[5];
  const __nv_bfloat16* w2 = (const __nv_bfloat16*)d_in[6];
  const __nv_bfloat16* b2 = (const __nv_bfloat16*)d_in[7];

  void* fn = nullptr;
  cudaDriverEntryPointQueryResult qr;
  cudaGetDriverEntryPoint("cuTensorMapEncodeTiled", &fn, cudaEnableDefault, &qr);
  EncodeFn enc = (EncodeFn)fn;
  Maps maps;
  make_map(enc, &maps.m[M_X], x, 2048, 640, 128, 64, CU_TENSOR_MAP_SWIZZLE_128B);
  make_map(enc, &maps.m[M_KV], wqkv, 640, 1920, 32, 32, CU_TENSOR_MAP_SWIZZLE_64B);
  make_map(enc, &maps.m[M_Q], wqkv, 640, 1920, 64, 32, CU_TENSOR_MAP_SWIZZLE_64B);
  make_map(enc, &maps.m[M_QR], wqkv, 640, 1920, 64, 16, CU_TENSOR_MAP_SWIZZLE_64B);
  make_map(enc, &maps.m[M_WO], wo, 640, 640, 80, 32, CU_TENSOR_MAP_SWIZZLE_64B);
  make_map(enc, &maps.m[M_WOR], wo, 640, 640, 80, 16, CU_TENSOR_MAP_SWIZZLE_64B);
  make_map(enc, &maps.m[M_W1], w1, 640, 1536, 80, 64, CU_TENSOR_MAP_SWIZZLE_128B);
  make_map(enc, &maps.m[M_W2], w2, 1536, 640, 64, 32, CU_TENSOR_MAP_SWIZZLE_64B);
  cudaFuncSetAttribute(fused_block_kernel, cudaFuncAttributeMaxDynamicSharedMemorySize, SMEM_BYTES);
  fused_block_kernel<<<128, 384, SMEM_BYTES>>>(maps, x, wqkv, wo, w1, b1, w2, b2, (__nv_bfloat16*)d_out);
}
```

```cpp
#include <cuda_runtime.h>
#include <cuda_bf16.h>
#include <cuda.h>
#include <stdint.h>

namespace {

template <int TA, int TB> __device__ __forceinline__ void wgmma_ss_n48(float (&d)[24], uint64_t da, uint64_t db, int sc) {
  asm volatile("{.reg .pred p; setp.ne.b32 p, %26, 0; wgmma.mma_async.sync.aligned.m64n48k16.f32.bf16.bf16 {%0,%1,%2,%3,%4,%5,%6,%7,%8,%9,%10,%11,%12,%13,%14,%15,%16,%17,%18,%19,%20,%21,%22,%23}, %24, %25, p, 1, 1, %27, %28;}"
    : "+f"(d[0]),"+f"(d[1]),"+f"(d[2]),"+f"(d[3]),"+f"(d[4]),"+f"(d[5]),"+f"(d[6]),"+f"(d[7]),"+f"(d[8]),"+f"(d[9]),"+f"(d[10]),"+f"(d[11]),"+f"(d[12]),"+f"(d[13]),"+f"(d[14]),"+f"(d[15]),"+f"(d[16]),"+f"(d[17]),"+f"(d[18]),"+f"(d[19]),"+f"(d[20]),"+f"(d[21]),"+f"(d[22]),"+f"(d[23])
    : "l"(da), "l"(db), "r"(sc), "n"(TA), "n"(TB));
}
template <int TA, int TB> __device__ __forceinline__ void wgmma_ss_n80(float (&d)[40], uint64_t da, uint64_t db, int sc) {
  asm volatile("{.reg .pred p; setp.ne.b32 p, %42, 0; wgmma.mma_async.sync.aligned.m64n80k16.f32.bf16.bf16 {%0,%1,%2,%3,%4,%5,%6,%7,%8,%9,%10,%11,%12,%13,%14,%15,%16,%17,%18,%19,%20,%21,%22,%23,%24,%25,%26,%27,%28,%29,%30,%31,%32,%33,%34,%35,%36,%37,%38,%39}, %40, %41, p, 1, 1, %43, %44;}"
    : "+f"(d[0]),"+f"(d[1]),"+f"(d[2]),"+f"(d[3]),"+f"(d[4]),"+f"(d[5]),"+f"(d[6]),"+f"(d[7]),"+f"(d[8]),"+f"(d[9]),"+f"(d[10]),"+f"(d[11]),"+f"(d[12]),"+f"(d[13]),"+f"(d[14]),"+f"(d[15]),"+f"(d[16]),"+f"(d[17]),"+f"(d[18]),"+f"(d[19]),"+f"(d[20]),"+f"(d[21]),"+f"(d[22]),"+f"(d[23]),"+f"(d[24]),"+f"(d[25]),"+f"(d[26]),"+f"(d[27]),"+f"(d[28]),"+f"(d[29]),"+f"(d[30]),"+f"(d[31]),"+f"(d[32]),"+f"(d[33]),"+f"(d[34]),"+f"(d[35]),"+f"(d[36]),"+f"(d[37]),"+f"(d[38]),"+f"(d[39])
    : "l"(da), "l"(db), "r"(sc), "n"(TA), "n"(TB));
}
template <int TA, int TB> __device__ __forceinline__ void wgmma_ss_n160(float (&d)[80], uint64_t da, uint64_t db, int sc) {
  asm volatile("{.reg .pred p; setp.ne.b32 p, %82, 0; wgmma.mma_async.sync.aligned.m64n160k16.f32.bf16.bf16 {%0,%1,%2,%3,%4,%5,%6,%7,%8,%9,%10,%11,%12,%13,%14,%15,%16,%17,%18,%19,%20,%21,%22,%23,%24,%25,%26,%27,%28,%29,%30,%31,%32,%33,%34,%35,%36,%37,%38,%39,%40,%41,%42,%43,%44,%45,%46,%47,%48,%49,%50,%51,%52,%53,%54,%55,%56,%57,%58,%59,%60,%61,%62,%63,%64,%65,%66,%67,%68,%69,%70,%71,%72,%73,%74,%75,%76,%77,%78,%79}, %80, %81, p, 1, 1, %83, %84;}"
    : "+f"(d[0]),"+f"(d[1]),"+f"(d[2]),"+f"(d[3]),"+f"(d[4]),"+f"(d[5]),"+f"(d[6]),"+f"(d[7]),"+f"(d[8]),"+f"(d[9]),"+f"(d[10]),"+f"(d[11]),"+f"(d[12]),"+f"(d[13]),"+f"(d[14]),"+f"(d[15]),"+f"(d[16]),"+f"(d[17]),"+f"(d[18]),"+f"(d[19]),"+f"(d[20]),"+f"(d[21]),"+f"(d[22]),"+f"(d[23]),"+f"(d[24]),"+f"(d[25]),"+f"(d[26]),"+f"(d[27]),"+f"(d[28]),"+f"(d[29]),"+f"(d[30]),"+f"(d[31]),"+f"(d[32]),"+f"(d[33]),"+f"(d[34]),"+f"(d[35]),"+f"(d[36]),"+f"(d[37]),"+f"(d[38]),"+f"(d[39]),"+f"(d[40]),"+f"(d[41]),"+f"(d[42]),"+f"(d[43]),"+f"(d[44]),"+f"(d[45]),"+f"(d[46]),"+f"(d[47]),"+f"(d[48]),"+f"(d[49]),"+f"(d[50]),"+f"(d[51]),"+f"(d[52]),"+f"(d[53]),"+f"(d[54]),"+f"(d[55]),"+f"(d[56]),"+f"(d[57]),"+f"(d[58]),"+f"(d[59]),"+f"(d[60]),"+f"(d[61]),"+f"(d[62]),"+f"(d[63]),"+f"(d[64]),"+f"(d[65]),"+f"(d[66]),"+f"(d[67]),"+f"(d[68]),"+f"(d[69]),"+f"(d[70]),"+f"(d[71]),"+f"(d[72]),"+f"(d[73]),"+f"(d[74]),"+f"(d[75]),"+f"(d[76]),"+f"(d[77]),"+f"(d[78]),"+f"(d[79])
    : "l"(da), "l"(db), "r"(sc), "n"(TA), "n"(TB));
}
template <int TA, int TB> __device__ __forceinline__ void wgmma_ss_n192(float (&d)[96], uint64_t da, uint64_t db, int sc) {
  asm volatile("{.reg .pred p; setp.ne.b32 p, %98, 0; wgmma.mma_async.sync.aligned.m64n192k16.f32.bf16.bf16 {%0,%1,%2,%3,%4,%5,%6,%7,%8,%9,%10,%11,%12,%13,%14,%15,%16,%17,%18,%19,%20,%21,%22,%23,%24,%25,%26,%27,%28,%29,%30,%31,%32,%33,%34,%35,%36,%37,%38,%39,%40,%41,%42,%43,%44,%45,%46,%47,%48,%49,%50,%51,%52,%53,%54,%55,%56,%57,%58,%59,%60,%61,%62,%63,%64,%65,%66,%67,%68,%69,%70,%71,%72,%73,%74,%75,%76,%77,%78,%79,%80,%81,%82,%83,%84,%85,%86,%87,%88,%89,%90,%91,%92,%93,%94,%95}, %96, %97, p, 1, 1, %99, %100;}"
    : "+f"(d[0]),"+f"(d[1]),"+f"(d[2]),"+f"(d[3]),"+f"(d[4]),"+f"(d[5]),"+f"(d[6]),"+f"(d[7]),"+f"(d[8]),"+f"(d[9]),"+f"(d[10]),"+f"(d[11]),"+f"(d[12]),"+f"(d[13]),"+f"(d[14]),"+f"(d[15]),"+f"(d[16]),"+f"(d[17]),"+f"(d[18]),"+f"(d[19]),"+f"(d[20]),"+f"(d[21]),"+f"(d[22]),"+f"(d[23]),"+f"(d[24]),"+f"(d[25]),"+f"(d[26]),"+f"(d[27]),"+f"(d[28]),"+f"(d[29]),"+f"(d[30]),"+f"(d[31]),"+f"(d[32]),"+f"(d[33]),"+f"(d[34]),"+f"(d[35]),"+f"(d[36]),"+f"(d[37]),"+f"(d[38]),"+f"(d[39]),"+f"(d[40]),"+f"(d[41]),"+f"(d[42]),"+f"(d[43]),"+f"(d[44]),"+f"(d[45]),"+f"(d[46]),"+f"(d[47]),"+f"(d[48]),"+f"(d[49]),"+f"(d[50]),"+f"(d[51]),"+f"(d[52]),"+f"(d[53]),"+f"(d[54]),"+f"(d[55]),"+f"(d[56]),"+f"(d[57]),"+f"(d[58]),"+f"(d[59]),"+f"(d[60]),"+f"(d[61]),"+f"(d[62]),"+f"(d[63]),"+f"(d[64]),"+f"(d[65]),"+f"(d[66]),"+f"(d[67]),"+f"(d[68]),"+f"(d[69]),"+f"(d[70]),"+f"(d[71]),"+f"(d[72]),"+f"(d[73]),"+f"(d[74]),"+f"(d[75]),"+f"(d[76]),"+f"(d[77]),"+f"(d[78]),"+f"(d[79]),"+f"(d[80]),"+f"(d[81]),"+f"(d[82]),"+f"(d[83]),"+f"(d[84]),"+f"(d[85]),"+f"(d[86]),"+f"(d[87]),"+f"(d[88]),"+f"(d[89]),"+f"(d[90]),"+f"(d[91]),"+f"(d[92]),"+f"(d[93]),"+f"(d[94]),"+f"(d[95])
    : "l"(da), "l"(db), "r"(sc), "n"(TA), "n"(TB));
}
template <int TB> __device__ __forceinline__ void wgmma_rs_n96(float (&d)[48], uint32_t a0, uint32_t a1, uint32_t a2, uint32_t a3, uint64_t db, int sc) {
  asm volatile("{.reg .pred p; setp.ne.b32 p, %53, 0; wgmma.mma_async.sync.aligned.m64n96k16.f32.bf16.bf16 {%0,%1,%2,%3,%4,%5,%6,%7,%8,%9,%10,%11,%12,%13,%14,%15,%16,%17,%18,%19,%20,%21,%22,%23,%24,%25,%26,%27,%28,%29,%30,%31,%32,%33,%34,%35,%36,%37,%38,%39,%40,%41,%42,%43,%44,%45,%46,%47}, {%48,%49,%50,%51}, %52, p, 1, 1, %54;}"
    : "+f"(d[0]),"+f"(d[1]),"+f"(d[2]),"+f"(d[3]),"+f"(d[4]),"+f"(d[5]),"+f"(d[6]),"+f"(d[7]),"+f"(d[8]),"+f"(d[9]),"+f"(d[10]),"+f"(d[11]),"+f"(d[12]),"+f"(d[13]),"+f"(d[14]),"+f"(d[15]),"+f"(d[16]),"+f"(d[17]),"+f"(d[18]),"+f"(d[19]),"+f"(d[20]),"+f"(d[21]),"+f"(d[22]),"+f"(d[23]),"+f"(d[24]),"+f"(d[25]),"+f"(d[26]),"+f"(d[27]),"+f"(d[28]),"+f"(d[29]),"+f"(d[30]),"+f"(d[31]),"+f"(d[32]),"+f"(d[33]),"+f"(d[34]),"+f"(d[35]),"+f"(d[36]),"+f"(d[37]),"+f"(d[38]),"+f"(d[39]),"+f"(d[40]),"+f"(d[41]),"+f"(d[42]),"+f"(d[43]),"+f"(d[44]),"+f"(d[45]),"+f"(d[46]),"+f"(d[47])
    : "r"(a0), "r"(a1), "r"(a2), "r"(a3), "l"(db), "r"(sc), "n"(TB));
}
template <int N, int TA, int TB> __device__ __forceinline__ void wgmma_ss(float (&d)[N / 2], uint64_t da, uint64_t db, int sc) {
  if constexpr (N == 48) wgmma_ss_n48<TA, TB>(d, da, db, sc);
  else if constexpr (N == 80) wgmma_ss_n80<TA, TB>(d, da, db, sc);
  else if constexpr (N == 160) wgmma_ss_n160<TA, TB>(d, da, db, sc);
  else if constexpr (N == 192) wgmma_ss_n192<TA, TB>(d, da, db, sc);
}
template <int N, int TB> __device__ __forceinline__ void wgmma_rs(float (&d)[N / 2], uint32_t a0, uint32_t a1, uint32_t a2, uint32_t a3, uint64_t db, int sc) {
  if constexpr (N == 96) wgmma_rs_n96<TB>(d, a0, a1, a2, a3, db, sc);
}

constexpr uint32_t SMEM_BASE = 1024;
constexpr uint32_t PAGE = 10240;
constexpr uint32_t OFF_RING = 16 * PAGE;
constexpr uint32_t OFF_KVB = 49152;
constexpr uint32_t OFF_R1 = 35840;
constexpr uint32_t OFF_MISC = 22 * PAGE;
constexpr uint32_t OFF_BAR = OFF_MISC;
constexpr uint32_t OFF_LN1 = OFF_MISC + 2048;
constexpr uint32_t OFF_CSKV = OFF_MISC + 3072;
constexpr uint32_t OFF_CSQ = OFF_MISC + 3712;
constexpr uint32_t OFF_CB1 = OFF_MISC + 4032;
constexpr uint32_t OFF_B2 = OFF_MISC + 5568;
constexpr uint32_t OFF_EPOCH = OFF_MISC + 5888;
constexpr uint32_t SMEM_BYTES = OFF_MISC + 5904;

enum : int {
  FX = 0, FKV = 13, FQ = 33, FWO = 43, FW1 = 51, FW2 = 59,
  AO = 71, AH = 87, AF = 103,
  DKV = 127, DQ = 147, DW = 157, DF = 173, DG = 189,
  SO = 213, SFB = 215,
  RX = 217, RXK = 219, SIDE = 220, SIDE2 = 221, KVB = 222, PX = 223, PF = 224, END = 226, N_BARS = 227
};

__device__ uint32_t g_epoch;
__device__ uint4 g_ln1[2048];
__device__ uint4 g_cs[2 * 1728];
__device__ uint4 g_hstat[32 * 8 * 64];
__device__ __align__(128) float2 g_kv1[8 * 16 * 16 * 64];
__device__ __align__(128) uint2 g_kv2[8 * 960];
__device__ __align__(128) uint32_t g_flag[3 * 32 * 32];
__device__ __align__(128) uint8_t g_act[3 * 32 * 8 * 24576];

struct Maps { CUtensorMap m[10]; };
enum : int { M_X, M_KV4, M_KV1, M_Q2, M_QR, M_WO2, M_WOR, M_W1, M_W22, M_W21 };

#define TL(id)
#define TLW(id)
#define TL0(id)

constexpr int SPIN_LIMIT = 1 << 19;

__device__ __forceinline__ bool elect_one() {
  uint32_t p;
  asm volatile("{.reg .pred P; elect.sync _|P, 0xffffffff; selp.u32 %0,1,0,P;}" : "=r"(p));
  return p;
}
__device__ __forceinline__ void mbar_wait(uint32_t bar) {
  asm volatile("{.reg .pred p;\nW: mbarrier.try_wait.parity.shared::cta.b64 p, [%0], 0;\n@!p bra W;}" ::"r"(bar) : "memory");
}
__device__ __forceinline__ void mbar_wait_cluster(uint32_t bar) {
  asm volatile("{.reg .pred p;\nW: mbarrier.try_wait.parity.acquire.cluster.shared::cta.b64 p, [%0], 0;\n@!p bra W;}" ::"r"(bar) : "memory");
}
__device__ __forceinline__ void mbar_wait_wd(uint32_t bar) {
  asm volatile("{.reg .pred p; .reg .u32 n; mov.u32 n, 0;\n"
               "W: mbarrier.try_wait.parity.shared::cta.b64 p, [%0], 0;\n"
               "@p bra D; add.u32 n, n, 1; setp.gt.u32 p, n, %1; @p trap; bra W;\n"
               "D: }" ::"r"(bar), "n"(SPIN_LIMIT) : "memory");
}
__device__ __forceinline__ void mbar_arrive(uint32_t bar, uint32_t n) {
  asm volatile("mbarrier.arrive.shared::cta.b64 _, [%0], %1;" ::"r"(bar), "r"(n) : "memory");
}
__device__ __forceinline__ void mbar_arrive_if0(int z, uint32_t bar, uint32_t n) {
  asm volatile("{.reg .pred p; setp.eq.s32 p, %2, 0; @p mbarrier.arrive.shared::cta.b64 _, [%0], %1;}" ::"r"(bar), "r"(n), "r"(z) : "memory");
}
__device__ __forceinline__ void mbar_arrive_remote_if0(int z, uint32_t bar) {
  asm volatile("{.reg .pred p; setp.eq.s32 p, %1, 0; @p mbarrier.arrive.shared::cluster.b64 _, [%0];}" ::"r"(bar), "r"(z) : "memory");
}
__device__ __forceinline__ void mbar_expect(uint32_t bar, uint32_t bytes) {
  asm volatile("mbarrier.arrive.expect_tx.shared::cta.b64 _, [%0], %1;" ::"r"(bar), "r"(bytes) : "memory");
  asm volatile("mbarrier.arrive.shared::cta.b64 _, [%0], 7;" ::"r"(bar) : "memory");
}
__device__ __forceinline__ void tma2d(uint32_t dst, const CUtensorMap* tm, uint32_t bar, int c0, int c1) {
  asm volatile("cp.async.bulk.tensor.2d.shared::cluster.global.mbarrier::complete_tx::bytes [%0],[%1,{%3,%4}],[%2];"
               ::"r"(dst), "l"(tm), "r"(bar), "r"(c0), "r"(c1) : "memory");
}
__device__ __forceinline__ void tma3d(uint32_t dst, const CUtensorMap* tm, uint32_t bar, int c0, int c1, int c2) {
  asm volatile("cp.async.bulk.tensor.3d.shared::cluster.global.mbarrier::complete_tx::bytes [%0],[%1,{%3,%4,%5}],[%2];"
               ::"r"(dst), "l"(tm), "r"(bar), "r"(c0), "r"(c1), "r"(c2) : "memory");
}
__device__ __forceinline__ void tma4d(uint32_t dst, const CUtensorMap* tm, uint32_t bar, int c0, int c1, int c2, int c3) {
  asm volatile("cp.async.bulk.tensor.4d.shared::cluster.global.mbarrier::complete_tx::bytes [%0],[%1,{%3,%4,%5,%6}],[%2];"
               ::"r"(dst), "l"(tm), "r"(bar), "r"(c0), "r"(c1), "r"(c2), "r"(c3) : "memory");
}
__device__ __forceinline__ void bulk_load(uint32_t dst, const void* src, uint32_t bytes, uint32_t bar) {
  asm volatile("cp.async.bulk.shared::cluster.global.mbarrier::complete_tx::bytes [%0],[%1],%2,[%3];"
               ::"r"(dst), "l"(src), "r"(bytes), "r"(bar) : "memory");
}
__device__ __forceinline__ void bulk_store(void* dst, uint32_t src, uint32_t bytes) {
  asm volatile("cp.async.bulk.global.shared::cta.bulk_group [%0],[%1],%2;" ::"l"(dst), "r"(src), "r"(bytes) : "memory");
}
__device__ __forceinline__ void bulk_commit_wait() {
  asm volatile("cp.async.bulk.commit_group;" ::: "memory");
  asm volatile("cp.async.bulk.wait_group 0;" ::: "memory");
}
__device__ __forceinline__ void l2_prefetch(const void* src, uint32_t bytes) {
  asm volatile("cp.async.bulk.prefetch.L2.global [%0], %1;" ::"l"(src), "r"(bytes) : "memory");
}
__device__ __forceinline__ void fence_gpu() { asm volatile("fence.acq_rel.gpu;" ::: "memory"); }
__device__ __forceinline__ void fence_async_smem() { asm volatile("fence.proxy.async.shared::cta;" ::: "memory"); }
__device__ __forceinline__ void fence_async_global() { asm volatile("fence.proxy.async.global;" ::: "memory"); }
__device__ __forceinline__ void st_flag(uint32_t* p, uint32_t v) {
  asm volatile("st.relaxed.gpu.global.u32 [%0], %1;" ::"l"(p), "r"(v) : "memory");
}
__device__ __forceinline__ uint32_t ld_acq(const uint32_t* p) {
  uint32_t v;
  asm volatile("ld.acquire.gpu.global.u32 %0, [%1];" : "=r"(v) : "l"(p) : "memory");
  return v;
}
__device__ __forceinline__ void wg_fence() { asm volatile("wgmma.fence.sync.aligned;" ::: "memory"); }
__device__ __forceinline__ void wg_commit() { asm volatile("wgmma.commit_group.sync.aligned;" ::: "memory"); }
template <int N> __device__ __forceinline__ void wg_wait() { asm volatile("wgmma.wait_group.sync.aligned %0;" ::"n"(N) : "memory"); }
template <int N> __device__ __forceinline__ void reg_fence(float (&a)[N]) {
#pragma unroll
  for (int i = 0; i < N; i++) asm volatile("" : "+f"(a[i])::"memory");
}
template <int ID, int N> __device__ __forceinline__ void named_bar() { asm volatile("bar.sync %0, %1;" ::"n"(ID), "n"(N) : "memory"); }
template <int N> __device__ __forceinline__ void reg_fence(uint32_t (&a)[N]) {
#pragma unroll
  for (int i = 0; i < N; i++) asm volatile("" : "+r"(a[i])::"memory");
}
__device__ __forceinline__ uint64_t mkdesc(uint32_t off, uint32_t lbo, uint32_t sbo, uint32_t swz) {
  return (uint64_t)(((off + SMEM_BASE) >> 4) + ((lbo >> 4) << 16)) | ((uint64_t)((sbo >> 4) | (swz << 30)) << 32);
}
__device__ __forceinline__ uint32_t pack2(float lo, float hi) {
  uint32_t r;
  asm("cvt.rn.bf16x2.f32 %0, %1, %2;" : "=r"(r) : "f"(hi), "f"(lo));
  return r;
}
__device__ __forceinline__ float bf_lo(uint32_t v) { return __uint_as_float(v << 16); }
__device__ __forceinline__ float bf_hi(uint32_t v) { return __uint_as_float(v & 0xffff0000u); }
__device__ __forceinline__ void stsm4(uint32_t addr, uint32_t a, uint32_t b, uint32_t c, uint32_t d) {
  asm volatile("stmatrix.sync.aligned.m8n8.x4.shared.b16 [%0], {%1,%2,%3,%4};" ::"r"(addr), "r"(a), "r"(b), "r"(c), "r"(d) : "memory");
}
__device__ __forceinline__ float2 lds64(uint32_t a) {
  float2 v;
  asm volatile("ld.shared.v2.f32 {%0,%1}, [%2];" : "=f"(v.x), "=f"(v.y) : "r"(a) : "memory");
  return v;
}
__device__ __forceinline__ float4 lds128(uint32_t a) {
  float4 v;
  asm volatile("ld.shared.v4.f32 {%0,%1,%2,%3}, [%4];" : "=f"(v.x), "=f"(v.y), "=f"(v.z), "=f"(v.w) : "r"(a) : "memory");
  return v;
}
__device__ __forceinline__ uint32_t lds32(uint32_t a) {
  uint32_t v;
  asm volatile("ld.shared.u32 %0, [%1];" : "=r"(v) : "r"(a) : "memory");
  return v;
}
__device__ __forceinline__ void sts32(uint32_t a, uint32_t v) { asm volatile("st.shared.u32 [%0], %1;" ::"r"(a), "r"(v) : "memory"); }
__device__ __forceinline__ void sts64(uint32_t a, uint32_t x, uint32_t y) {
  asm volatile("st.shared.v2.u32 [%0], {%1,%2};" ::"r"(a), "r"(x), "r"(y) : "memory");
}
__device__ __forceinline__ void sts128(uint32_t a, uint32_t x, uint32_t y, uint32_t z, uint32_t w) {
  asm volatile("st.shared.v4.u32 [%0], {%1,%2,%3,%4};" ::"r"(a), "r"(x), "r"(y), "r"(z), "r"(w) : "memory");
}
__device__ __forceinline__ float ex2(float x) {
  float r;
  asm("ex2.approx.ftz.f32 %0, %1;" : "=f"(r) : "f"(x));
  return r;
}
__device__ __forceinline__ float rcp(float x) {
  float r;
  asm("rcp.approx.ftz.f32 %0, %1;" : "=f"(r) : "f"(x));
  return r;
}
constexpr float LOG2E = 1.4426950408889634f, LN2 = 0.6931471805599453f;
__device__ __forceinline__ float phi2(float t2) { return fmaf(fmaxf(t2, 0.f), LN2, ex2(fminf(t2, 0.f))) + 1e-6f; }
__device__ __forceinline__ float gelu(float y) {
  float p = fmaf(y * y, 0.044715f * 0.7978845608028654f, 0.7978845608028654f);
  float th;
  asm("tanh.approx.f32 %0, %1;" : "=f"(th) : "f"(y * p));
  float hy = 0.5f * y;
  return fmaf(hy, th, hy);
}
constexpr uint32_t ONES = 0x3F803F80u;
__device__ __forceinline__ void ll_store(uint4* p, float a, float b, uint32_t tag) {
  asm volatile("st.relaxed.gpu.global.v4.u32 [%0], {%1,%2,%3,%2};" ::"l"(p), "r"(__float_as_uint(a)), "r"(tag), "r"(__float_as_uint(b)) : "memory");
}
__device__ __forceinline__ uint4 ll_load(const void* p) {
  uint4 v;
  asm volatile("ld.relaxed.gpu.global.v4.u32 {%0,%1,%2,%3}, [%4];" : "=r"(v.x), "=r"(v.y), "=r"(v.z), "=r"(v.w) : "l"(p) : "memory");
  return v;
}
template <int N>
__device__ __forceinline__ void ll_wait(uint4 (&v)[N], const uint4* p, int stride, uint32_t tag) {
  uint32_t bad;
  int it = 0;
  do {
    bad = 0;
#pragma unroll
    for (int m = 0; m < N; m++) v[m] = ll_load(p + m * stride);
#pragma unroll
    for (int m = 0; m < N; m++) bad |= (v[m].y ^ tag) | (v[m].w ^ tag);
  } while (bad && ++it < SPIN_LIMIT);
}
__device__ __forceinline__ void poll_flag(const uint32_t* f, int bit, uint32_t& mask, uint32_t epoch) {
  while (!(mask >> bit & 1)) {
    mask = __ballot_sync(0xffffffffu, ld_acq(f) == epoch);
    fence_async_global();
  }
}
template <bool PHI>
__device__ __forceinline__ void ln_pair(const float* a, const float2* cs, const float2 (&st)[2], uint32_t* o) {
#pragma unroll
  for (int tt = 0; tt < 2; tt++) {
#pragma unroll
    for (int hh = 0; hh < 2; hh++) {
      float y0 = fmaf(st[hh].x, a[4 * tt + 2 * hh], st[hh].y * cs[tt].x), y1 = fmaf(st[hh].x, a[4 * tt + 2 * hh + 1], st[hh].y * cs[tt].y);
      if (PHI) { y0 = phi2(y0); y1 = phi2(y1); }
      o[2 * tt + hh] = pack2(y0, y1);
    }
  }
}

__global__ void __cluster_dims__(2, 1, 1) __launch_bounds__(384, 1)
fused_block_kernel(const __grid_constant__ Maps maps, const __nv_bfloat16* __restrict__ x, const __nv_bfloat16* __restrict__ wqkv,
                   const __nv_bfloat16* __restrict__ wo, const __nv_bfloat16* __restrict__ w1,
                   const __nv_bfloat16* __restrict__ b1, const __nv_bfloat16* __restrict__ w2,
                   const __nv_bfloat16* __restrict__ b2, __nv_bfloat16* __restrict__ out) {
  extern __shared__ __align__(1024) uint8_t smem_raw[];
  const uint32_t sb = (uint32_t)__cvta_generic_to_shared(smem_raw);
  const uint32_t bars = sb + OFF_BAR;
  const int warp = __shfl_sync(0xffffffffu, threadIdx.x >> 5, 0);
  const int lane = threadIdx.x & 31;

  const int cl = blockIdx.x >> 1, q = blockIdx.x & 1;
  const int u7 = ((cl - 36) * 37) >> 8;
  const int oct = cl < 4 ? 0 : cl < 36 ? 1 + 2 * ((cl - 4) & 7) : 2 + 2 * (cl - 36 - 7 * u7);
  const int u4 = cl < 4 ? cl : cl < 36 ? (cl - 4) >> 3 : u7;
  const int i = 2 * (oct & 7) + (u4 >> 1), p = 2 * (oct >> 3) + (u4 & 1);
  const int j = 2 * p + q;
  const int a2 = 5 * p + 3 * q;

  auto load_kv = [&](int s, int slot) {
    const uint32_t dst = sb + OFF_RING + slot * PAGE, bar = bars + 8 * (FKV + s);
    mbar_expect(bar, 10240);
    tma4d(dst, &maps.m[M_KV4], bar, 0, 32 * s, a2, 1);
    tma2d(dst + 8192, &maps.m[M_KV1], bar, 704 + 160 * p + 640 * q, 32 * s);
  };
  auto load_x = [&](int c, int b, int slot) {
    mbar_expect(bars + 8 * (FX + b), 16384);
    tma2d(sb + slot * 16384, &maps.m[M_X], bars + 8 * (FX + b), 64 * c, 128 * i);
  };

  if (warp == 8) {
    if (elect_one()) {
#pragma unroll
      for (int n = 0; n < 10; n++)
        asm volatile("mbarrier.init.shared::cta.b64 [%0], 8;" ::"r"(bars + 8 * (n < 4 ? FX + n : FKV + n - 4)) : "memory");
      load_x(0, 0, 0);
#pragma unroll 1
      for (int c = 0; c < 3; c++) {
        load_kv(2 * c, 2 * c);
        load_x(c + 1, c + 1, c + 1);
        load_kv(2 * c + 1, 2 * c + 1);
      }
    }
    TL(40);
  } else if (warp < 8) {
    if (elect_one()) {
      if (warp > 0) asm volatile("prefetch.tensormap [%0];" ::"l"(&maps.m[2 + warp]) : "memory");
#pragma unroll 1
      for (int n = 4 + warp; n < N_BARS; n += 8)
        if (n < FKV || n >= FKV + 6) asm volatile("mbarrier.init.shared::cta.b64 [%0], 8;" ::"r"(bars + 8 * n) : "memory");
      asm volatile("fence.mbarrier_init.release.cluster;" ::: "memory");
    }
  }

  if (warp >= 8) {
    asm volatile("setmaxnreg.dec.sync.aligned.u32 72;");
    if (warp == 8) {
      named_bar<0, 288>();
      asm volatile("barrier.cluster.arrive.relaxed.aligned;" ::: "memory");
#pragma unroll 1
      for (int s = 6, slot = 0; s < 20; s += 2) {
        mbar_wait(bars + 8 * (DKV + s - 6));
        if (elect_one()) load_kv(s, slot);
        mbar_wait(bars + 8 * (DKV + s - 5));
        if (elect_one()) {
          if (s < 18) load_x(s / 2 + 1, s / 2 + 1, s / 2 + 1);
          load_kv(s + 1, slot + 1);
        }
        slot = slot == 4 ? 0 : slot + 2;
      }
      const int crem = 80 * j + 64 - 64 * q;
#pragma unroll 1
      for (int t = 0, slot = 2; t < 10; t++) {
        mbar_wait(bars + 8 * (DKV + 15 + t + (t == 3)));
        if (elect_one()) {
          if (t >= 6 && t < 9) load_x(t - 6, t + 4, t - 2);
          const uint32_t dst = sb + OFF_RING + slot * 12288, bar = bars + 8 * (FQ + t);
          const int k0 = 64 * (t < 7 ? t + 3 : t - 7);
          mbar_expect(bar, 10240);
          tma3d(dst, &maps.m[M_Q2], bar, 0, k0, a2);
          tma2d(dst + 8192, &maps.m[M_QR], bar, crem, k0);
        }
        slot = slot == 4 ? 0 : slot + 1;
      }
#pragma unroll 1
      for (int n = 0; n < 32; n += 4) {
        mbar_wait(bars + 8 * (DQ + ((0x99976665u >> n) & 15)));
        if (elect_one()) {
          const int t = (0x54076321u >> n) & 7, k0 = 80 * (t == 0 ? j : t - (t <= j));
          const uint32_t dst = sb + 10 * PAGE + t * 15360, bar = bars + 8 * (FWO + t);
          mbar_expect(bar, 12800);
          tma3d(dst, &maps.m[M_WO2], bar, 0, k0, a2);
          tma2d(dst + 10240, &maps.m[M_WOR], bar, crem, k0);
        }
      }
#pragma unroll 1
      for (int t = 0; t < 8; t++) {
        const uint32_t wb = bars + 8 * (t == 0 ? DQ + 1 : t < 5 ? DW + 2 * t - 1 : DF + t - 5);
        mbar_wait(wb);
        mbar_wait(wb + 64);
        if (elect_one()) {
          mbar_expect(bars + 8 * (FW1 + t), 30720);
          tma3d(sb + (7 + 3 * (t < 5 ? t : t - 5)) * PAGE, &maps.m[M_W1], bars + 8 * (FW1 + t), 0, 80 * (t == 0 ? j : t - (t <= j)), 3 * j);
        }
      }
#pragma unroll 1
      for (int t = 0; t < 12; t++) {
        const int t7 = t < 7 ? t : t - 7;
        const uint32_t wb = bars + 8 * (t < 7 ? DF + ((0x7665443 >> (4 * t)) & 7) : DG + t7);
        const int uu = (0xA95024 >> (2 * t)) & 3, n = (0x924900 >> (2 * t)) & 3;
        const int k0 = 192 * (t < 3 ? j : 2 * (n + (n >= p)) + q) + 64 * uu;
        const uint32_t dst = sb + (t7 < 3 ? 16 + 2 * t7 : 1 + 2 * t7) * PAGE, bar = bars + 8 * (FW2 + t);
        mbar_wait(wb);
        mbar_wait(wb + (t < 7 ? 64 : 96));
        if (elect_one()) {
          mbar_expect(bar, 20480);
          tma3d(dst, &maps.m[M_W22], bar, 0, k0, a2);
          tma2d(dst + 8192, &maps.m[M_W21], bar, 160 * p + 64, k0);
          tma3d(dst + 12288, &maps.m[M_W22], bar, 0, k0, 5 * p + 3 - 3 * q);
        }
      }
    } else {
      asm volatile("barrier.cluster.arrive.relaxed.aligned;" ::: "memory");
      uint32_t epoch;
      asm volatile("ld.relaxed.gpu.global.u32 %0, [%1];" : "=r"(epoch) : "l"(&g_epoch) : "memory");
      epoch += 1;
      const int g = lane >> 2, c = lane & 3, unit = i * 8 + j, hw = warp - 9, ht = hw * 32 + lane;
      auto colsum = [&](const __nv_bfloat16* wp, int ld, uint4* dst) {
        float d[8];
#pragma unroll
        for (int e = 0; e < 8; e++) d[e] = 0.f;
        wp += g * ld + c * 8;
#pragma unroll 1
        for (int r = 0; r < 4; r++) {
          uint4 v[10];
#pragma unroll
          for (int m = 0; m < 10; m++) v[m] = __ldg(reinterpret_cast<const uint4*>(wp + m * 8 * ld));
          wp += 80 * ld;
#pragma unroll
          for (int m = 0; m < 10; m++) {
            d[0] += bf_lo(v[m].x); d[1] += bf_hi(v[m].x); d[2] += bf_lo(v[m].y); d[3] += bf_hi(v[m].y);
            d[4] += bf_lo(v[m].z); d[5] += bf_hi(v[m].z); d[6] += bf_lo(v[m].w); d[7] += bf_hi(v[m].w);
          }
        }
#pragma unroll 1
        for (int o = 4; o < 32; o <<= 1) {
#pragma unroll
          for (int e = 0; e < 8; e++) d[e] += __shfl_xor_sync(0xffffffffu, d[e], o);
        }
        if (g & 2) { d[0] = d[4]; d[1] = d[5]; d[2] = d[6]; d[3] = d[7]; }
        if (g < 4) ll_store(dst + 4 * c + g, g & 1 ? d[2] : d[0], g & 1 ? d[3] : d[1], epoch);
      };
#pragma unroll 1
      for (int pass = 0; pass < 2; pass++) {
        if (hw == 2) {
          const int nu = pass ? 48 : 60, half = unit >= nu, cg = unit - nu * half;
          if (cg < nu) colsum((pass ? w1 : wqkv) + half * 320 * 32 * nu + 32 * cg, 32 * nu, g_cs + half * 1728 + 960 * pass + 16 * cg);
          if (pass) break;
          TL(8);
        } else {
          const int row = 128 * i + 16 * j + 8 * hw + g;
          float sm = 0.f, sq = 0.f;
#pragma unroll 1
          for (int r = 0; r < 4; r++) {
            uint4 v[5];
#pragma unroll
            for (int m = 0; m < 5; m++) v[m] = __ldg(reinterpret_cast<const uint4*>(x + row * 640) + c + 4 * m + 20 * r);
#pragma unroll
            for (int m = 0; m < 5; m++) {
              const uint32_t vv[4] = {v[m].x, v[m].y, v[m].z, v[m].w};
#pragma unroll
              for (int e = 0; e < 4; e++) {
                const float a = bf_lo(vv[e]), b = bf_hi(vv[e]);
                sm += a + b;
                sq = fmaf(a, a, fmaf(b, b, sq));
              }
            }
          }
#pragma unroll
          for (int o = 1; o < 4; o <<= 1) {
            sm += __shfl_xor_sync(0xffffffffu, sm, o);
            sq += __shfl_xor_sync(0xffffffffu, sq, o);
          }
          const float mean = sm * (1.f / 640.f);
          const float rstd = rsqrtf(fmaxf(fmaf(-mean, mean, sq * (1.f / 640.f)), 0.f) + 1e-5f);
          if (c == 0) ll_store(g_ln1 + row, rstd, -rstd * mean, epoch);
          if (hw == 0) TL(10);
        }
        asm volatile("bar.sync 3, 352;" ::: "memory");
        if (lane == 0) {
          const uint32_t nb = hw ? 15360 : 6400;
          l2_prefetch(reinterpret_cast<const uint8_t*>(hw == 0 ? wo : hw == 1 ? w1 : w2) + blockIdx.x * nb, nb);
          mbar_expect(bars + 8 * (RX + hw), hw == 2 ? 4096 : 20480);
          sts32(sb + OFF_EPOCH, epoch);
        }
        if (hw < 2) {
          uint4 v[2];
          ll_wait(v, g_ln1 + 128 * i + ht, 64, epoch);
          sts64(sb + OFF_LN1 + ht * 8, v[0].x, v[0].z);
          sts64(sb + OFF_LN1 + ht * 8 + 512, v[1].x, v[1].z);
        }
#pragma unroll 1
        for (int n = 2 * ht; n < 240; n += 192) {
          int col;
          if (n < 160) col = 160 * p + n + (n < 64 ? 640 + 96 * q : n < 128 ? 1216 + 96 * q : 576 + 640 * q);
          else {
            col = 80 * j + n - 160 + (q ? (n < 224 ? 16 : -64) : 0);
            const uint32_t bb = *reinterpret_cast<const uint32_t*>(b2 + col);
            sts64(sb + OFF_B2 + (n - 160) * 4, bb << 16, bb & 0xffff0000u);
          }
          uint4 v[2];
          ll_wait(v, g_cs + (col >> 1), 1728, epoch);
          sts64(sb + OFF_CSKV + n * 4, __float_as_uint(__uint_as_float(v[0].x) + __uint_as_float(v[1].x)),
                __float_as_uint(__uint_as_float(v[0].z) + __uint_as_float(v[1].z)));
        }
        __syncwarp();
        mbar_arrive_if0(lane, bars + 8 * SIDE, hw == 2 ? 2 : 3);
        if (hw == 0) TL(11);
        mbar_wait_wd(bars + 8 * DQ);
        if (hw == 2) {
#pragma unroll 1
          for (int m = 0; m < 30; m++) sts128(sb + OFF_KVB + (m * 32 + lane) * 16, 0, 0, 0, 0);
        } else if (ht < 60) {
          const float2* src = g_kv1 + (j * 16 + i) * 1024 + ht;
          const uint32_t tag = epoch & 15;
          float sa, sc;
          uint32_t bad;
          int it = 0;
          do {
            uint32_t a[16], b[16];
#pragma unroll
            for (int m = 0; m < 16; m++)
              asm volatile("ld.relaxed.gpu.global.v2.u32 {%0,%1}, [%2];" : "=r"(a[m]), "=r"(b[m]) : "l"(src + m * 64) : "memory");
            sa = sc = 0.f;
            bad = 0;
#pragma unroll
            for (int m = 0; m < 16; m++) {
              bad |= (a[m] ^ tag) | (b[m] ^ tag);
              sa += __uint_as_float(a[m]);
              sc += __uint_as_float(b[m]);
            }
          } while ((bad & 15) && ++it < SPIN_LIMIT);
          asm volatile("st.relaxed.gpu.global.v2.u32 [%0], {%1,%2};" ::"l"(g_kv2 + j * 960 + i * 60 + ht), "r"(pack2(sa, sc)), "r"(epoch) : "memory");
        }
        if (hw == 0) TL(5);
        {
          uint4 v[5];
          ll_wait(v, reinterpret_cast<const uint4*>(g_kv2 + j * 960) + ht, 96, epoch);
          if (hw == 0) TL(6);
          named_bar<2, 96>();
          const int d0 = ht / 6, part = ht - 6 * d0;
#pragma unroll
          for (int m = 0; m < 5; m++) {
            const int d = d0 + 16 * m, head = (d * 205) >> 12, n = 20 * head + 4 * part;
            const uint32_t a = sb + OFF_KVB + d * 16;
            const uint32_t z = head & 1 ? v[m].x << 16 : v[m].x & 0xffffu;
            if (part < 5) sts64(a + (n >> 3) * 1280 + (n & 7) * 2, v[m].x, v[m].z);
            else sts128(a + (10 + (head >> 1)) * 1280, z, z, z, z);
          }
        }
        fence_async_smem();
        __syncwarp();
        mbar_arrive_if0(lane, bars + 8 * KVB, hw == 2 ? 2 : 3);
        if (hw == 0) TL(7);
        if (hw < 2) break;
      }

      if (hw == 2) {
#pragma unroll 1
        for (int n = lane; n < 96; n += 32) {
          const uint32_t bb = *reinterpret_cast<const uint32_t*>(b1 + 192 * j + 2 * n);
          uint4 v[2];
          ll_wait(v, g_cs + 960 + 96 * j + n, 1728, epoch);
          sts128(sb + OFF_CB1 + n * 16, __float_as_uint(__uint_as_float(v[0].x) + __uint_as_float(v[1].x)),
                 __float_as_uint(__uint_as_float(v[0].z) + __uint_as_float(v[1].z)), bb << 16, bb & 0xffff0000u);
        }
        __syncwarp();
        mbar_arrive_if0(lane, bars + 8 * SIDE2, 8);
        TL(18);
#pragma unroll 1
        for (int s = 0; s < 2; s++) {
          uint8_t* dst = g_act + ((64 + 2 * i + s) * 8 + j) * 24576;
          mbar_wait_wd(bars + 8 * (AF + 12 * s + 1));
          if (lane == 0) bulk_store(dst + 8192, sb + s * OFF_R1 + 8192, 8192);
          __syncwarp();
          mbar_wait_wd(bars + 8 * (AF + 12 * s + 2));
          if (lane == 0) {
            bulk_store(dst + 16384, sb + s * OFF_R1 + 16384, 8192);
            bulk_commit_wait();
            mbar_arrive(bars + 8 * (SFB + s), 8);
            fence_gpu();
            st_flag(g_flag + (64 + 2 * i + s) * 32 + 8 + j, epoch);
          }
          __syncwarp();
          TL(50 + s);
        }
        mbar_wait_wd(bars + 8 * END);
        if (blockIdx.x == 0 && lane == 0) g_epoch = epoch;
      } else {
        const int s = hw;
#pragma unroll 1
        for (int ph = 0; ph < 3; ph++) {
          uint32_t ab = bars + 8 * (ph < 2 ? AO + 16 * ph + 8 * s : AF + 12 * s);
          const uint32_t bytes = ph < 2 ? 10240 : 8192, base = sb + (ph ? s * OFF_R1 : 0);
          uint8_t* gb = g_act + (ph * 32 + 2 * i + s) * 8 * 24576;
          uint32_t* fl = g_flag + (ph * 32 + 2 * i + s) * 32;
          mbar_wait(ab);
          if (elect_one()) {
            bulk_store(gb + j * 24576, sb + s * (ph ? OFF_R1 : PAGE), bytes);
            bulk_commit_wait();
            if (ph == 0) mbar_arrive(bars + 8 * (SO + s), 8);
            fence_gpu();
            st_flag(fl + j, epoch);
          }
          __syncwarp();
          TL(44 + 2 * ph + s);
          uint32_t slots;
          uint64_t waits;
          if (ph == 0) {
            slots = s ? 02165432u : 00165432u;
            waits = s ? 011060504030201ull : 000101010101010ull;
            if (s == 0) mbar_wait(bars + 8 * (SO + 1));
          } else if (ph == 1) {
            slots = 01021021u;
            waits = 024232221201717ull + (s ? 010101010100000ull : 0);
          } else {
            slots = 0321032103u;
            waits = 0474645444342414027ull + (s ? 0141414141414141410ull : 0);
            ab += 16;
          }
          uint32_t mask = 0;
#pragma unroll 1
          for (int r = 0; r < (ph < 2 ? 7 : 9); r++) {
            int cc = r + (r >= j), bit = cc;
            uint32_t off = 0;
            if (ph == 2) {
              const int uu = (r * 11) >> 5, n = r - 3 * uu;
              cc = 2 * (n + (n >= p)) + q;
              bit = cc + (uu ? 8 : 0);
              off = uu * 8192;
              if (r == 2) mbar_wait(bars + 8 * (SFB + s));
            }
            ab += 8;
            mbar_wait(bars + 8 * (DW + ((uint32_t)waits & 63)));
            poll_flag(fl + lane, bit, mask, epoch);
            if (r == 0) TL(52 + 2 * ph + s);
            if (elect_one()) {
              mbar_expect(ab, bytes);
              bulk_load(base + (slots & 7) * bytes, gb + cc * 24576 + off, bytes, ab);
            }
            slots >>= 3;
            waits >>= 6;
          }
        }
      }
    }
    __syncwarp();
    asm volatile("barrier.cluster.wait.aligned;" ::: "memory");
  } else {
    asm volatile("setmaxnreg.inc.sync.aligned.u32 216;");
    asm volatile("bar.arrive 3, 352;" ::: "memory");
    named_bar<0, 288>();
    asm volatile("barrier.cluster.arrive.relaxed.aligned;" ::: "memory");
    const int s = warp >> 2, w = warp & 3, tid = threadIdx.x & 127, c = lane & 3, g = lane >> 2;
    uint32_t sb_peer;
    asm volatile("mapa.shared::cluster.u32 %0, %1, %2;" : "=r"(sb_peer) : "r"(sb), "r"(q ^ 1));
    const int lp4 = 4 - 4 * q;
    const int row0 = 128 * i + 64 * s + 16 * w;
    const uint32_t bs8 = bars + 64 * s, bs12 = bars + 96 * s;
    uint32_t pq[20], hp[20];
    uint32_t epoch;
    {
      float acc[80];
      const uint64_t dx = mkdesc(s * 8192, 16, 1024, 1);
#pragma unroll
      for (int st = 0; st < 20; st++) {
        if ((st & 1) == 0) mbar_wait(bars + 8 * (FX + (st >> 1)));
        mbar_wait(bars + 8 * (FKV + st));
        const uint64_t da = dx + (st >> 1) * 1024 + (st & 1) * 4, db = mkdesc(OFF_RING + (st % 6) * PAGE, 2048, 512, 2);
        wg_fence();
        wgmma_ss<160, 0, 1>(acc, da, db, st != 0);
        wgmma_ss<160, 0, 1>(acc, da + 2, db + 64, 1);
        wg_commit();
        if (st == 0) TL0(0);
        if (st > 0) {
          wg_wait<1>();
          mbar_arrive_if0(lane, bars + 8 * (DKV + st - 1), 1);
        }
        if (st == 8) {
          asm volatile("barrier.cluster.wait.aligned;" ::: "memory");
          mbar_arrive_remote_if0(lane, sb_peer + OFF_BAR + 8 * PX);
        }
      }
      TL0(12);
      float accq[40];
      auto q_step = [&](int t) {
        if (t >= 7) mbar_wait(bars + 8 * (FX + 3 + t));
        mbar_wait(bars + 8 * (FQ + t));
        const uint64_t da = dx + (t < 7 ? t + 3 : t - 3) * 1024, db = mkdesc(OFF_RING + ((t + 2) % 5) * 12288, 4096, 512, 2);
        wg_fence();
#pragma unroll
        for (int ks = 0; ks < 4; ks++) wgmma_ss<80, 0, 1>(accq, da + 2 * ks, db + 64 * ks, (t | ks) != 0);
        wg_commit();
      };
      mbar_wait(bars + 8 * SIDE);
      epoch = lds32(sb + OFF_EPOCH);
      float2 sk[2], sv[2], cs[20];
#pragma unroll
      for (int r = 0; r < 2; r++) {
        sv[r] = lds64(sb + OFF_LN1 + (64 * s + 16 * w + g + 8 * r) * 8);
        sk[r] = make_float2(sv[r].x * LOG2E, sv[r].y * LOG2E);
      }
#pragma unroll
      for (int n = 0; n < 20; n++) cs[n] = lds64(sb + OFF_CSKV + c * 8 + n * 32);
      mbar_wait_cluster(bars + 8 * PX);
      q_step(0);
      wg_wait<1>();
      reg_fence(acc);
      mbar_arrive_if0(lane, bars + 8 * (DKV + 19), 1);
      TL0(1);
      const uint32_t kbase = q ? 0 : 22528, vbase = q ? 20480 : 0;
      const int hi = lane >> 4;
      const uint32_t rowoff = sb + (64 * s + 16 * w + (lane & 15)) * 16;
      {
        uint32_t keep[4], send[4];
        if (q == 0) {
          ln_pair<true>(acc + 64, cs + 16, sk, keep);
          ln_pair<true>(acc + 72, cs + 18, sk, send);
        } else {
          ln_pair<false>(acc + 64, cs + 16, sv, send);
          ln_pair<false>(acc + 72, cs + 18, sv, keep);
        }
#pragma unroll
        for (int r = 0; r < 4; r++)
          asm volatile("st.async.shared::cluster.mbarrier::complete_tx::bytes.b32 [%0], %1, [%2];"
                       ::"r"(sb_peer + (r >> 1) * 2048 + (64 * s + 16 * w + 8 * (r & 1)) * 16 + lane * 4),
                       "r"(send[r]), "r"(sb_peer + OFF_BAR + 8 * RXK) : "memory");
        stsm4((q ? vbase + 6 * 2048 : kbase + 8 * 2048) + hi * 2048 + rowoff, keep[0], keep[1], keep[2], keep[3]);
      }
      q_step(1);
#pragma unroll
      for (int P = 0; P < 4; P++) {
        uint32_t r[4];
        ln_pair<true>(acc + 8 * P, cs + 2 * P, sk, r);
        stsm4(kbase + (2 * (P + q) + hi) * 2048 + rowoff, r[0], r[1], r[2], r[3]);
        if (P == 1) q_step(2);
      }
#pragma unroll
      for (int P = 4; P < 8; P++) {
        uint32_t r[4];
        ln_pair<false>(acc + 8 * P, cs + 2 * P, sv, r);
        const uint32_t pos = (uint32_t)(0x10432A9876ull >> (8 * (P - 4))) >> (8 * q + 4 * hi) & 15;
        stsm4(vbase + pos * 2048 + rowoff, r[0], r[1], r[2], r[3]);
      }
      sts128(vbase + 5 * 2048 + rowoff, ONES, ONES, ONES, ONES);
      TL0(2);
      mbar_wait_cluster(bars + 8 * RXK);
      fence_async_smem();
      named_bar<1, 256>();
      TL0(3);
      float kv[24];
      {
        const uint64_t da = mkdesc(kbase + s * 10240, 128, 2048, 0), db = mkdesc(vbase + 10240 - s * 10240, 128, 2048, 0);
        wg_fence();
#pragma unroll
        for (int kk = 0; kk < 8; kk++) wgmma_ss<48, 1, 1>(kv, da + 16 * kk, db + 16 * kk, kk != 0);
        wg_commit();
      }
      wg_wait<1>();
      mbar_arrive_if0(lane >= 3, bars + 8 * (DQ + lane), 1);
      q_step(3);
      wg_wait<1>();
      reg_fence(kv);
      TL0(4);
#pragma unroll
      for (int hh = 0; hh < 2; hh++) {
        const int r = 16 * w + g + 8 * hh, d = 40 * s + r, own = (d * 205) >> 10;
        const int e0 = c - (r < 20 ? 0 : r < 40 ? 10 : 99);
        float2* gp = g_kv1 + ((j * 16 + own) * 16 + i) * 64 + (d - 5 * own) * 12;
#pragma unroll
        for (int tt = 0; tt < 6; tt++) {
          const bool isz = s ? tt == 5 : tt == 0;
          const int e = e0 + 4 * (s ? (tt + 3) % 5 : tt - 1);
          const bool ok = isz ? (c < 2 && r < 40) : (unsigned)e < 10u;
          asm volatile("{.reg .pred p; setp.ne.u32 p, %3, 0; @p st.relaxed.gpu.global.v2.u32 [%0], {%1,%2};}"
                       ::"l"(gp + (isz ? 10 + c : e)), "r"((__float_as_uint(kv[4 * tt + 2 * hh]) & ~15u) | (epoch & 15)),
                       "r"((__float_as_uint(kv[4 * tt + 2 * hh + 1]) & ~15u) | (epoch & 15)), "r"((uint32_t)ok) : "memory");
        }
      }
      TL0(9);
      const __nv_bfloat16* xr = x + (row0 + g) * 640 + 80 * j + 2 * c;
#pragma unroll
      for (int t = 4; t < 10; t++) {
        q_step(t);
        if (t < 9) {
          const __nv_bfloat16* xp = xr + 16 * (t < 8 ? t - 4 + q : lp4);
#pragma unroll
          for (int r = 0; r < 4; r++)
            asm volatile("ld.global.nc.u32 %0, [%1];" : "=r"(hp[4 * (t - 4) + r]) : "l"(xp + (r & 1) * 8 * 640 + (r >> 1) * 8));
        } else {
#pragma unroll
          for (int n = 0; n < 10; n++) cs[n] = lds64(sb + OFF_CSQ + c * 8 + n * 32);
        }
        wg_wait<1>();
        mbar_arrive_if0(lane, bars + 8 * (DQ + t - 1), 1);
      }
      wg_wait<0>();
      reg_fence(accq);
      mbar_arrive_if0(lane, bars + 8 * (DQ + 9), 1);
      TL0(13);
#pragma unroll
      for (int P = 0; P < 5; P++) ln_pair<true>(accq + 8 * P, cs + 2 * P, sk, pq + 4 * P);
      reg_fence(pq);
      TL0(14);
    }
    const uint32_t rs = sb + s * OFF_R1;
    const uint32_t stoff = (lane >> 4) * 1024 + (16 * w + (lane & 15)) * 16;
    const uint64_t drs = mkdesc(s * OFF_R1, 1024, 128, 0);
    float accg[80];
    {
      {
        float o[48];
        mbar_wait(bars + 8 * KVB);
        TL0(15);
        const uint64_t dkv = mkdesc(OFF_KVB, 128, 1280, 0);
        wg_fence();
#pragma unroll
        for (int ks = 0; ks < 5; ks++)
          wgmma_rs<96, 1>(o, pq[4 * ks], pq[4 * ks + 1], pq[4 * ks + 2], pq[4 * ks + 3], dkv + 16 * (ks < 4 ? ks + q : lp4), ks != 0);
        wg_commit();
        wg_wait<0>();
        reg_fence(o);
        float inv[2][4];
#pragma unroll
        for (int hh = 0; hh < 2; hh++)
#pragma unroll
          for (int h = 0; h < 4; h++) inv[hh][h] = rcp(o[40 + 4 * (h >> 1) + 2 * hh + (h & 1)] + 1e-6f);
        uint32_t r[4];
#pragma unroll
        for (int t = 0; t < 10; t++) {
#pragma unroll
          for (int hh = 0; hh < 2; hh++) {
            const float f = t == 2 ? (c < 2 ? inv[hh][0] : inv[hh][1]) : t == 7 ? (c < 2 ? inv[hh][2] : inv[hh][3]) : inv[hh][(8 * t) / 20];
            r[2 * (t & 1) + hh] = pack2(o[4 * t + 2 * hh] * f, o[4 * t + 2 * hh + 1] * f);
          }
          if (t & 1) stsm4(sb + s * PAGE + stoff + (t >> 1) * 2048, r[0], r[1], r[2], r[3]);
        }
        fence_async_smem();
        __syncwarp();
        mbar_arrive_if0(lane, bs8 + 8 * AO, 2);
        TLW(16 + s);
      }
      float acc[40];
#pragma unroll
      for (int r = 0; r < 20; r++) { acc[2 * r] = bf_lo(hp[r]); acc[2 * r + 1] = bf_hi(hp[r]); }
      reg_fence(acc);
#pragma unroll
      for (int t = 0; t < 8; t++) {
        mbar_wait(bars + 8 * (FWO + t));
        mbar_wait(bs8 + 8 * (AO + t));
        if (t == 1) TLW(20 + s);
        const uint64_t da = mkdesc((t == 0 ? s : t < 6 ? t + 1 : t == 6 ? 1 : 2 * s) * PAGE, 1024, 128, 0);
        const uint64_t db = mkdesc(10 * PAGE + t * 15360, 5120, 512, 2);
        wg_fence();
#pragma unroll
        for (int ks = 0; ks < 5; ks++) wgmma_ss<80, 0, 1>(acc, da + 128 * ks, db + 64 * ks, 1);
        wg_commit();
        if (t == 0) wg_wait<0>();
        else if (t > 1) wg_wait<1>();
        if (t != 1) mbar_arrive_if0(lane, bs8 + 8 * (DW + (t ? t - 1 : 0)), 2);
      }
      wg_wait<0>();
      reg_fence(acc);
      mbar_arrive_if0(lane, bs8 + 8 * (DW + 7), 2);
      TLW(22 + s);
#pragma unroll
      for (int r = 0; r < 20; r++) hp[r] = pack2(acc[2 * r], acc[2 * r + 1]);
      mbar_wait(bs8 + 8 * (DW + 7));
#pragma unroll
      for (int ks = 0; ks < 5; ks++)
        stsm4(rs + stoff + (ks < 4 ? ks + q : lp4) * 2048, hp[4 * ks], hp[4 * ks + 1], hp[4 * ks + 2], hp[4 * ks + 3]);
      fence_async_smem();
      __syncwarp();
      mbar_arrive_if0(lane, bs8 + 8 * AH, 2);
      reg_fence(hp);
      TLW(24 + s);
    }
    float accf[96];
    uint4 hs[4];
#pragma unroll
    for (int t = 0; t < 8; t++) {
      mbar_wait(bars + 8 * (FW1 + t));
      mbar_wait(bs8 + 8 * (AH + t));
      if (t == 1) TLW(26 + s);
      const uint64_t da = drs + (t % 3) * (PAGE / 16), db = mkdesc((7 + 3 * (t % 5)) * PAGE, 10240, 1024, 1);
      wg_fence();
#pragma unroll
      for (int ks = 0; ks < 5; ks++) wgmma_ss<192, 0, 1>(accf, da + 128 * ks, db + 128 * ks, (t | ks) != 0);
      wg_commit();
      if (t == 0) {
        float sm[2] = {0.f, 0.f}, sq[2] = {0.f, 0.f};
#pragma unroll
        for (int m = 0; m < 10; m++) {
          const float2 b = lds64(sb + OFF_B2 + (8 * m + 2 * c) * 4);
#pragma unroll
          for (int hh = 0; hh < 2; hh++) {
            const float h0 = bf_lo(hp[2 * m + hh]), h1 = bf_hi(hp[2 * m + hh]);
            sm[hh] += h0 + h1;
            sq[hh] = fmaf(h0, h0, fmaf(h1, h1, sq[hh]));
            const float v0 = b.x + h0, v1 = b.y + h1;
            const int e = 4 * m + 2 * hh;
            if (m < 8) { accg[e] = v0; accg[e + 1] = v1; accg[48 + e] = 0.f; accg[49 + e] = 0.f; }
            else { accg[e] = q ? 0.f : v0; accg[e + 1] = q ? 0.f : v1; accg[e + 8] = q ? v0 : 0.f; accg[e + 9] = q ? v1 : 0.f; }
          }
        }
        reg_fence(accg);
#pragma unroll
        for (int o = 1; o < 4; o <<= 1) {
#pragma unroll
          for (int hh = 0; hh < 2; hh++) {
            sm[hh] += __shfl_xor_sync(0xffffffffu, sm[hh], o);
            sq[hh] += __shfl_xor_sync(0xffffffffu, sq[hh], o);
          }
        }
        if (c < 2) ll_store(g_hstat + ((2 * i + s) * 8 + j) * 64 + 16 * w + g + 8 * c, c ? sm[1] : sm[0], c ? sq[1] : sq[0], epoch);
        wg_wait<0>();
      } else if (t > 1) wg_wait<1>();
      if (t != 1) mbar_arrive_if0(lane, bs8 + 8 * (DF + (t ? t - 1 : 0)), 2);
      if (t == 5) {
#pragma unroll
        for (int m = 0; m < 4; m++) hs[m] = ll_load(g_hstat + ((2 * i + s) * 8 + 2 * c + (m >> 1)) * 64 + 16 * w + g + 8 * (m & 1));
      }
    }
    float ra[2], rb[2];
    while (((hs[0].y ^ epoch) | (hs[0].w ^ epoch) | (hs[1].y ^ epoch) | (hs[1].w ^ epoch) | (hs[2].y ^ epoch) | (hs[2].w ^ epoch) |
            (hs[3].y ^ epoch) | (hs[3].w ^ epoch)) != 0) {
#pragma unroll
      for (int m = 0; m < 4; m++) hs[m] = ll_load(g_hstat + ((2 * i + s) * 8 + 2 * c + (m >> 1)) * 64 + 16 * w + g + 8 * (m & 1));
    }
    __syncwarp();
#pragma unroll
    for (int hh = 0; hh < 2; hh++) {
      float sm = __uint_as_float(hs[hh].x) + __uint_as_float(hs[2 + hh].x), sq = __uint_as_float(hs[hh].z) + __uint_as_float(hs[2 + hh].z);
#pragma unroll
      for (int o = 1; o < 4; o <<= 1) {
        sm += __shfl_xor_sync(0xffffffffu, sm, o);
        sq += __shfl_xor_sync(0xffffffffu, sq, o);
      }
      const float mean = sm * (1.f / 640.f);
      ra[hh] = rsqrtf(fmaxf(fmaf(-mean, mean, sq * (1.f / 640.f)), 0.f) + 1e-5f);
      rb[hh] = -ra[hh] * mean;
    }
    mbar_wait(bars + 8 * SIDE2);
    reg_fence(ra);
    reg_fence(rb);
    wg_wait<0>();
    reg_fence(accf);
    mbar_arrive_if0(lane, bs8 + 8 * (DF + 7), 2);
    TLW(28 + s);
    auto g_step = [&](int t, int page) {
      mbar_wait(bars + 8 * (FW2 + t));
      mbar_wait(bs12 + 8 * (AF + t));
      if (t == 3) TLW(32 + s);
      const uint64_t da = drs + (t & 3) * 512, db = mkdesc(page * PAGE, 4096, 512, 2);
      wg_fence();
#pragma unroll
      for (int ks = 0; ks < 4; ks++) wgmma_ss<160, 0, 1>(accg, da + 128 * ks, db + 64 * ks, 1);
      wg_commit();
    };
#pragma unroll 1
    for (int t = 0; t < 3; t++) {
      uint32_t r[16];
#pragma unroll
      for (int n = 0; n < 8; n++) {
        const float4 cb = lds128(sb + OFF_CB1 + (32 * t + 4 * n + c) * 16);
#pragma unroll
        for (int hh = 0; hh < 2; hh++) {
          const float* a = accf + 4 * n + 2 * hh;
          const float y0 = fmaf(ra[hh], a[0], fmaf(rb[hh], cb.x, cb.z)), y1 = fmaf(ra[hh], a[1], fmaf(rb[hh], cb.y, cb.w));
          r[2 * n + hh] = pack2(gelu(y0), gelu(y1));
        }
      }
      mbar_wait(bs8 + 8 * (DF + 7));
#pragma unroll
      for (int n = 0; n < 4; n++) stsm4(rs + stoff + t * 8192 + n * 2048, r[4 * n], r[4 * n + 1], r[4 * n + 2], r[4 * n + 3]);
      fence_async_smem();
      __syncwarp();
      mbar_arrive_if0(lane, bs12 + 8 * (AF + t), 2);
#pragma unroll
      for (int e = 0; e < 64; e++) accf[e] = accf[e + 32];
      g_step(t, 16 + 2 * t);
      wg_wait<1>();
      mbar_arrive_if0(lane | (t == 0), bs12 + 8 * (DG + t - 1), 2);
    }
    TLW(30 + s);
    wg_wait<0>();
    mbar_arrive_if0(lane, bs12 + 8 * (DG + 2), 2);
#pragma unroll
    for (int t = 3; t < 12; t++) {
      g_step(t, t % 7 < 3 ? 16 + 2 * (t % 7) : 1 + 2 * (t % 7));
      if (t > 3) {
        wg_wait<1>();
        mbar_arrive_if0(lane, bs12 + 8 * (DG + t - 1), 2);
        if (t == 6 || t == 7) mbar_arrive_remote_if0(lane, sb_peer + OFF_BAR + 8 * (PF + t - 6));
      }
    }
    mbar_wait_cluster(bars + 8 * (PF + s));
    wg_wait<0>();
    reg_fence(accg);
    mbar_arrive_if0(lane, bs12 + 8 * (DG + 11), 2);
    TLW(34 + s);
    {
      const uint32_t buf = (11 + 2 * s) * PAGE + tid * 16;
#pragma unroll
      for (int e = 0; e < 8; e++) {
        const float a = accg[32 + e], b = accg[40 + e];
        accg[32 + e] = q ? b : a;
        accg[40 + e] = q ? a : b;
      }
#pragma unroll
      for (int m = 0; m < 10; m++) {
        const float* a = accg + (m < 8 ? 48 + 4 * m : 8 + 4 * m);
        asm volatile("st.async.shared::cluster.mbarrier::complete_tx::bytes.v4.f32 [%0], {%1,%2,%3,%4}, [%5];"
                     ::"r"(sb_peer + buf + m * 2048), "f"(a[0]), "f"(a[1]), "f"(a[2]), "f"(a[3]),
                     "r"(sb_peer + OFF_BAR + 8 * (RX + s)) : "memory");
      }
      TLW(58 + s);
      mbar_wait(bs12 + 8 * (DG + 11));
      mbar_wait_cluster(bars + 8 * (RX + s));
      TLW(60 + s);
      float4 rx[10];
#pragma unroll
      for (int m = 0; m < 10; m++) rx[m] = lds128(sb + buf + m * 2048);
      const uint32_t stg = rs + w * 2816;
      const uint32_t sa = stg + (lane & 15) * 176 + (lane >> 4) * 16;
#pragma unroll
      for (int ks = 0; ks < 5; ks++) {
        const float4 r0 = rx[2 * ks], r1 = rx[2 * ks + 1];
        const float* a = accg + 8 * ks;
        stsm4(sa + (ks < 4 ? ks + q : lp4) * 32, pack2(a[0] + r0.x, a[1] + r0.y), pack2(a[2] + r0.z, a[3] + r0.w),
              pack2(a[4] + r1.x, a[5] + r1.y), pack2(a[6] + r1.z, a[7] + r1.w));
      }
      __syncwarp();
      __nv_bfloat16* outp = out + (row0 + (lane >> 1)) * 640 + 80 * j + (lane & 1) * 8;
#pragma unroll
      for (int m = 0; m < 5; m++) rx[m] = lds128(stg + (lane >> 1) * 176 + (lane & 1) * 16 + m * 32);
#pragma unroll
      for (int m = 0; m < 5; m++) *reinterpret_cast<float4*>(outp + m * 16) = rx[m];
    }
    mbar_arrive_if0(lane, bars + 8 * END, 1);
    TLW(36 + s);
  }
}

typedef CUresult (*EncodeFn)(CUtensorMap*, CUtensorMapDataType, cuuint32_t, void*, const cuuint64_t*, const cuuint64_t*,
                             const cuuint32_t*, const cuuint32_t*, CUtensorMapInterleave, CUtensorMapSwizzle,
                             CUtensorMapL2promotion, CUtensorMapFloatOOBfill);

void make_map(EncodeFn enc, CUtensorMap* tm, const void* base, int rank, int rows, int cols, int box_rows, int atom, int natom,
              CUtensorMapSwizzle sw) {
  const cuuint64_t dims[4] = {(cuuint64_t)(rank == 2 ? cols : atom), (cuuint64_t)rows, (cuuint64_t)((rank == 3 ? cols : 640) / atom),
                              (cuuint64_t)(cols / 640)};
  const cuuint64_t strides[3] = {(cuuint64_t)cols * 2, (cuuint64_t)atom * 2, 1280};
  const cuuint32_t box[4] = {(cuuint32_t)atom, (cuuint32_t)box_rows, (cuuint32_t)natom, 2}, es[4] = {1, 1, 1, 1};
  enc(tm, CU_TENSOR_MAP_DATA_TYPE_BFLOAT16, rank, const_cast<void*>(base), dims, strides, box, es, CU_TENSOR_MAP_INTERLEAVE_NONE, sw,
      CU_TENSOR_MAP_L2_PROMOTION_L2_128B, CU_TENSOR_MAP_FLOAT_OOB_FILL_NONE);
}

}

extern "C" void kernel_launch(void* const* d_in, const int* in_sizes, int n_in, void* d_out, int out_size) {
  const __nv_bfloat16* x = (const __nv_bfloat16*)d_in[0];
  const __nv_bfloat16* wqkv = (const __nv_bfloat16*)d_in[1];
  const __nv_bfloat16* wo = (const __nv_bfloat16*)d_in[2];
  const __nv_bfloat16* w1 = (const __nv_bfloat16*)d_in[4];
  const __nv_bfloat16* b1 = (const __nv_bfloat16*)d_in[5];
  const __nv_bfloat16* w2 = (const __nv_bfloat16*)d_in[6];
  const __nv_bfloat16* b2 = (const __nv_bfloat16*)d_in[7];

  void* fn = nullptr;
  cudaDriverEntryPointQueryResult qr;
  cudaGetDriverEntryPoint("cuTensorMapEncodeTiled", &fn, cudaEnableDefault, &qr);
  EncodeFn enc = (EncodeFn)fn;
  const CUtensorMapSwizzle S128 = CU_TENSOR_MAP_SWIZZLE_128B, S64 = CU_TENSOR_MAP_SWIZZLE_64B;
  Maps maps;
  make_map(enc, &maps.m[M_X], x, 2, 2048, 640, 128, 64, 1, S128);
  make_map(enc, &maps.m[M_KV4], wqkv, 4, 640, 1920, 32, 32, 2, S64);
  make_map(enc, &maps.m[M_KV1], wqkv, 2, 640, 1920, 32, 32, 1, S64);
  make_map(enc, &maps.m[M_Q2], wqkv, 3, 640, 1920, 64, 32, 2, S64);
  make_map(enc, &maps.m[M_QR], wqkv, 2, 640, 1920, 64, 16, 1, S64);
  make_map(enc, &maps.m[M_WO2], wo, 3, 640, 640, 80, 32, 2, S64);
  make_map(enc, &maps.m[M_WOR], wo, 2, 640, 640, 80, 16, 1, S64);
  make_map(enc, &maps.m[M_W1], w1, 3, 640, 1536, 80, 64, 3, S128);
  make_map(enc, &maps.m[M_W22], w2, 3, 1536, 640, 64, 32, 2, S64);
  make_map(enc, &maps.m[M_W21], w2, 2, 1536, 640, 64, 32, 1, S64);
  cudaFuncSetAttribute(fused_block_kernel, cudaFuncAttributeMaxDynamicSharedMemorySize, SMEM_BYTES);
  fused_block_kernel<<<128, 384, SMEM_BYTES>>>(maps, x, wqkv, wo, w1, b1, w2, b2, (__nv_bfloat16*)d_out);
}
```

```cpp
#include <cuda_runtime.h>
#include <cuda_bf16.h>
#include <cuda.h>
#include <stdint.h>

namespace {

struct Desc { uint32_t base, off, hi; };
__device__ __forceinline__ Desc operator+(Desc d, uint32_t o) { return Desc{d.base, d.off + o, d.hi}; }
template <int TA, int TB> __device__ __forceinline__ void wgmma_ss_n48(float (&d)[24], Desc a, Desc b, int sc) {
  asm volatile("{.reg .pred p; .reg .b32 t, u; .reg .b64 da, db; setp.ne.b32 p, %30, 0; add.u32 t, %24, %25; mov.b64 da, {t, %26}; add.u32 u, %27, %28; mov.b64 db, {u, %29};"
    "wgmma.mma_async.sync.aligned.m64n48k16.f32.bf16.bf16 {%0,%1,%2,%3,%4,%5,%6,%7,%8,%9,%10,%11,%12,%13,%14,%15,%16,%17,%18,%19,%20,%21,%22,%23}, da, db, p, 1, 1, %31, %32;}"
    : "+f"(d[0]),"+f"(d[1]),"+f"(d[2]),"+f"(d[3]),"+f"(d[4]),"+f"(d[5]),"+f"(d[6]),"+f"(d[7]),"+f"(d[8]),"+f"(d[9]),"+f"(d[10]),"+f"(d[11]),"+f"(d[12]),"+f"(d[13]),"+f"(d[14]),"+f"(d[15]),"+f"(d[16]),"+f"(d[17]),"+f"(d[18]),"+f"(d[19]),"+f"(d[20]),"+f"(d[21]),"+f"(d[22]),"+f"(d[23])
    : "r"(a.base), "r"(a.off), "r"(a.hi), "r"(b.base), "r"(b.off), "r"(b.hi), "r"(sc), "n"(TA), "n"(TB));
}
template <int TA, int TB> __device__ __forceinline__ void wgmma_ss_n80(float (&d)[40], Desc a, Desc b, int sc) {
  asm volatile("{.reg .pred p; .reg .b32 t, u; .reg .b64 da, db; setp.ne.b32 p, %46, 0; add.u32 t, %40, %41; mov.b64 da, {t, %42}; add.u32 u, %43, %44; mov.b64 db, {u, %45};"
    "wgmma.mma_async.sync.aligned.m64n80k16.f32.bf16.bf16 {%0,%1,%2,%3,%4,%5,%6,%7,%8,%9,%10,%11,%12,%13,%14,%15,%16,%17,%18,%19,%20,%21,%22,%23,%24,%25,%26,%27,%28,%29,%30,%31,%32,%33,%34,%35,%36,%37,%38,%39}, da, db, p, 1, 1, %47, %48;}"
    : "+f"(d[0]),"+f"(d[1]),"+f"(d[2]),"+f"(d[3]),"+f"(d[4]),"+f"(d[5]),"+f"(d[6]),"+f"(d[7]),"+f"(d[8]),"+f"(d[9]),"+f"(d[10]),"+f"(d[11]),"+f"(d[12]),"+f"(d[13]),"+f"(d[14]),"+f"(d[15]),"+f"(d[16]),"+f"(d[17]),"+f"(d[18]),"+f"(d[19]),"+f"(d[20]),"+f"(d[21]),"+f"(d[22]),"+f"(d[23]),"+f"(d[24]),"+f"(d[25]),"+f"(d[26]),"+f"(d[27]),"+f"(d[28]),"+f"(d[29]),"+f"(d[30]),"+f"(d[31]),"+f"(d[32]),"+f"(d[33]),"+f"(d[34]),"+f"(d[35]),"+f"(d[36]),"+f"(d[37]),"+f"(d[38]),"+f"(d[39])
    : "r"(a.base), "r"(a.off), "r"(a.hi), "r"(b.base), "r"(b.off), "r"(b.hi), "r"(sc), "n"(TA), "n"(TB));
}
template <int TA, int TB> __device__ __forceinline__ void wgmma_ss_n160(float (&d)[80], Desc a, Desc b, int sc) {
  asm volatile("{.reg .pred p; .reg .b32 t, u; .reg .b64 da, db; setp.ne.b32 p, %86, 0; add.u32 t, %80, %81; mov.b64 da, {t, %82}; add.u32 u, %83, %84; mov.b64 db, {u, %85};"
    "wgmma.mma_async.sync.aligned.m64n160k16.f32.bf16.bf16 {%0,%1,%2,%3,%4,%5,%6,%7,%8,%9,%10,%11,%12,%13,%14,%15,%16,%17,%18,%19,%20,%21,%22,%23,%24,%25,%26,%27,%28,%29,%30,%31,%32,%33,%34,%35,%36,%37,%38,%39,%40,%41,%42,%43,%44,%45,%46,%47,%48,%49,%50,%51,%52,%53,%54,%55,%56,%57,%58,%59,%60,%61,%62,%63,%64,%65,%66,%67,%68,%69,%70,%71,%72,%73,%74,%75,%76,%77,%78,%79}, da, db, p, 1, 1, %87, %88;}"
    : "+f"(d[0]),"+f"(d[1]),"+f"(d[2]),"+f"(d[3]),"+f"(d[4]),"+f"(d[5]),"+f"(d[6]),"+f"(d[7]),"+f"(d[8]),"+f"(d[9]),"+f"(d[10]),"+f"(d[11]),"+f"(d[12]),"+f"(d[13]),"+f"(d[14]),"+f"(d[15]),"+f"(d[16]),"+f"(d[17]),"+f"(d[18]),"+f"(d[19]),"+f"(d[20]),"+f"(d[21]),"+f"(d[22]),"+f"(d[23]),"+f"(d[24]),"+f"(d[25]),"+f"(d[26]),"+f"(d[27]),"+f"(d[28]),"+f"(d[29]),"+f"(d[30]),"+f"(d[31]),"+f"(d[32]),"+f"(d[33]),"+f"(d[34]),"+f"(d[35]),"+f"(d[36]),"+f"(d[37]),"+f"(d[38]),"+f"(d[39]),"+f"(d[40]),"+f"(d[41]),"+f"(d[42]),"+f"(d[43]),"+f"(d[44]),"+f"(d[45]),"+f"(d[46]),"+f"(d[47]),"+f"(d[48]),"+f"(d[49]),"+f"(d[50]),"+f"(d[51]),"+f"(d[52]),"+f"(d[53]),"+f"(d[54]),"+f"(d[55]),"+f"(d[56]),"+f"(d[57]),"+f"(d[58]),"+f"(d[59]),"+f"(d[60]),"+f"(d[61]),"+f"(d[62]),"+f"(d[63]),"+f"(d[64]),"+f"(d[65]),"+f"(d[66]),"+f"(d[67]),"+f"(d[68]),"+f"(d[69]),"+f"(d[70]),"+f"(d[71]),"+f"(d[72]),"+f"(d[73]),"+f"(d[74]),"+f"(d[75]),"+f"(d[76]),"+f"(d[77]),"+f"(d[78]),"+f"(d[79])
    : "r"(a.base), "r"(a.off), "r"(a.hi), "r"(b.base), "r"(b.off), "r"(b.hi), "r"(sc), "n"(TA), "n"(TB));
}
template <int TA, int TB> __device__ __forceinline__ void wgmma_ss_n192(float (&d)[96], Desc a, Desc b, int sc) {
  asm volatile("{.reg .pred p; .reg .b32 t, u; .reg .b64 da, db; setp.ne.b32 p, %102, 0; add.u32 t, %96, %97; mov.b64 da, {t, %98}; add.u32 u, %99, %100; mov.b64 db, {u, %101};"
    "wgmma.mma_async.sync.aligned.m64n192k16.f32.bf16.bf16 {%0,%1,%2,%3,%4,%5,%6,%7,%8,%9,%10,%11,%12,%13,%14,%15,%16,%17,%18,%19,%20,%21,%22,%23,%24,%25,%26,%27,%28,%29,%30,%31,%32,%33,%34,%35,%36,%37,%38,%39,%40,%41,%42,%43,%44,%45,%46,%47,%48,%49,%50,%51,%52,%53,%54,%55,%56,%57,%58,%59,%60,%61,%62,%63,%64,%65,%66,%67,%68,%69,%70,%71,%72,%73,%74,%75,%76,%77,%78,%79,%80,%81,%82,%83,%84,%85,%86,%87,%88,%89,%90,%91,%92,%93,%94,%95}, da, db, p, 1, 1, %103, %104;}"
    : "+f"(d[0]),"+f"(d[1]),"+f"(d[2]),"+f"(d[3]),"+f"(d[4]),"+f"(d[5]),"+f"(d[6]),"+f"(d[7]),"+f"(d[8]),"+f"(d[9]),"+f"(d[10]),"+f"(d[11]),"+f"(d[12]),"+f"(d[13]),"+f"(d[14]),"+f"(d[15]),"+f"(d[16]),"+f"(d[17]),"+f"(d[18]),"+f"(d[19]),"+f"(d[20]),"+f"(d[21]),"+f"(d[22]),"+f"(d[23]),"+f"(d[24]),"+f"(d[25]),"+f"(d[26]),"+f"(d[27]),"+f"(d[28]),"+f"(d[29]),"+f"(d[30]),"+f"(d[31]),"+f"(d[32]),"+f"(d[33]),"+f"(d[34]),"+f"(d[35]),"+f"(d[36]),"+f"(d[37]),"+f"(d[38]),"+f"(d[39]),"+f"(d[40]),"+f"(d[41]),"+f"(d[42]),"+f"(d[43]),"+f"(d[44]),"+f"(d[45]),"+f"(d[46]),"+f"(d[47]),"+f"(d[48]),"+f"(d[49]),"+f"(d[50]),"+f"(d[51]),"+f"(d[52]),"+f"(d[53]),"+f"(d[54]),"+f"(d[55]),"+f"(d[56]),"+f"(d[57]),"+f"(d[58]),"+f"(d[59]),"+f"(d[60]),"+f"(d[61]),"+f"(d[62]),"+f"(d[63]),"+f"(d[64]),"+f"(d[65]),"+f"(d[66]),"+f"(d[67]),"+f"(d[68]),"+f"(d[69]),"+f"(d[70]),"+f"(d[71]),"+f"(d[72]),"+f"(d[73]),"+f"(d[74]),"+f"(d[75]),"+f"(d[76]),"+f"(d[77]),"+f"(d[78]),"+f"(d[79]),"+f"(d[80]),"+f"(d[81]),"+f"(d[82]),"+f"(d[83]),"+f"(d[84]),"+f"(d[85]),"+f"(d[86]),"+f"(d[87]),"+f"(d[88]),"+f"(d[89]),"+f"(d[90]),"+f"(d[91]),"+f"(d[92]),"+f"(d[93]),"+f"(d[94]),"+f"(d[95])
    : "r"(a.base), "r"(a.off), "r"(a.hi), "r"(b.base), "r"(b.off), "r"(b.hi), "r"(sc), "n"(TA), "n"(TB));
}
template <int TB> __device__ __forceinline__ void wgmma_rs_n96(float (&d)[48], uint32_t a0, uint32_t a1, uint32_t a2, uint32_t a3, Desc b, int sc) {
  asm volatile("{.reg .pred p; .reg .b32 u; .reg .b64 db; setp.ne.b32 p, %55, 0; add.u32 u, %52, %53; mov.b64 db, {u, %54};"
    "wgmma.mma_async.sync.aligned.m64n96k16.f32.bf16.bf16 {%0,%1,%2,%3,%4,%5,%6,%7,%8,%9,%10,%11,%12,%13,%14,%15,%16,%17,%18,%19,%20,%21,%22,%23,%24,%25,%26,%27,%28,%29,%30,%31,%32,%33,%34,%35,%36,%37,%38,%39,%40,%41,%42,%43,%44,%45,%46,%47}, {%48,%49,%50,%51}, db, p, 1, 1, %56;}"
    : "+f"(d[0]),"+f"(d[1]),"+f"(d[2]),"+f"(d[3]),"+f"(d[4]),"+f"(d[5]),"+f"(d[6]),"+f"(d[7]),"+f"(d[8]),"+f"(d[9]),"+f"(d[10]),"+f"(d[11]),"+f"(d[12]),"+f"(d[13]),"+f"(d[14]),"+f"(d[15]),"+f"(d[16]),"+f"(d[17]),"+f"(d[18]),"+f"(d[19]),"+f"(d[20]),"+f"(d[21]),"+f"(d[22]),"+f"(d[23]),"+f"(d[24]),"+f"(d[25]),"+f"(d[26]),"+f"(d[27]),"+f"(d[28]),"+f"(d[29]),"+f"(d[30]),"+f"(d[31]),"+f"(d[32]),"+f"(d[33]),"+f"(d[34]),"+f"(d[35]),"+f"(d[36]),"+f"(d[37]),"+f"(d[38]),"+f"(d[39]),"+f"(d[40]),"+f"(d[41]),"+f"(d[42]),"+f"(d[43]),"+f"(d[44]),"+f"(d[45]),"+f"(d[46]),"+f"(d[47])
    : "r"(a0), "r"(a1), "r"(a2), "r"(a3), "r"(b.base), "r"(b.off), "r"(b.hi), "r"(sc), "n"(TB));
}
template <int N, int TA, int TB> __device__ __forceinline__ void wgmma_ss(float (&d)[N / 2], Desc a, Desc b, int sc) {
  if constexpr (N == 48) wgmma_ss_n48<TA, TB>(d, a, b, sc);
  else if constexpr (N == 80) wgmma_ss_n80<TA, TB>(d, a, b, sc);
  else if constexpr (N == 160) wgmma_ss_n160<TA, TB>(d, a, b, sc);
  else if constexpr (N == 192) wgmma_ss_n192<TA, TB>(d, a, b, sc);
}
template <int N, int TB> __device__ __forceinline__ void wgmma_rs(float (&d)[N / 2], uint32_t a0, uint32_t a1, uint32_t a2, uint32_t a3, Desc b, int sc) {
  if constexpr (N == 96) wgmma_rs_n96<TB>(d, a0, a1, a2, a3, b, sc);
}

constexpr uint32_t SMEM_BASE = 1024;
constexpr uint32_t PAGE = 10240;
constexpr uint32_t OFF_RING = 16 * PAGE;
constexpr uint32_t OFF_KVB = 49152;
constexpr uint32_t OFF_R1 = 35840;
constexpr uint32_t OFF_MISC = 22 * PAGE;
constexpr uint32_t OFF_W2 = OFF_MISC - 6 * 24576;
constexpr uint32_t OFF_BAR = OFF_MISC;
constexpr uint32_t OFF_LN1 = OFF_MISC + 2048;
constexpr uint32_t OFF_CSKV = OFF_MISC + 3072;
constexpr uint32_t OFF_CSQ = OFF_MISC + 3712;
constexpr uint32_t OFF_CB1 = OFF_MISC + 4032;
constexpr uint32_t OFF_B2 = OFF_MISC + 5568;
constexpr uint32_t OFF_EPOCH = OFF_MISC + 5888;
constexpr uint32_t SMEM_BYTES = OFF_MISC + 5904;

enum : int {
  FX = 0, FKV = 13, FQ = 33, FWO = 43, FW1 = 51, FW2 = 59,
  AO = 71, AH = 87, AF = 103,
  DKV = 127, DQ = 147, DW = 157, DF = 173, DG = 189,
  SO = 213, SFB = 215,
  RX = 217, RXK = 219, SIDE = 220, SIDE2 = 221, KVB = 222, PX = 223, PF = 224, END = 225, RKV = 226
};

__device__ uint32_t g_epoch;
__device__ uint4 g_ln1[2048];
__device__ uint4 g_cs[4 * 1728];
__device__ uint4 g_hstat[32 * 8 * 64];
__device__ __align__(128) float2 g_kv1[8 * 16 * 16 * 64];
__device__ __align__(128) uint2 g_kv2[8 * 960];
__device__ __align__(128) uint32_t g_flag[3 * 32 * 32];
__device__ __align__(128) uint8_t g_act[3 * 32 * 8 * 24576];

struct Maps { CUtensorMap m[11]; };
enum : int { M_X, M_KVF, M_KVH, M_Q2, M_QR, M_WO2, M_WOR, M_W1, M_W1R, M_W2F, M_W2H };

#define TL(id)
#define TLW(id)
#define TL0(id)

constexpr int SPIN_LIMIT = 1 << 19;

__device__ __forceinline__ bool elect_one() {
  uint32_t p;
  asm volatile("{.reg .pred P; elect.sync _|P, 0xffffffff; selp.u32 %0,1,0,P;}" : "=r"(p));
  return p;
}
__device__ __forceinline__ void mbar_wait(uint32_t bar) {
  asm volatile("{.reg .pred p;\nW: mbarrier.try_wait.parity.shared::cta.b64 p, [%0], 0;\n@!p bra W;}" ::"r"(bar) : "memory");
}
__device__ __forceinline__ void mbar_wait_cluster(uint32_t bar) {
  asm volatile("{.reg .pred p;\nW: mbarrier.try_wait.parity.acquire.cluster.shared::cta.b64 p, [%0], 0;\n@!p bra W;}" ::"r"(bar) : "memory");
}
__device__ __forceinline__ void mbar_wait_wd(uint32_t bar) {
  asm volatile("{.reg .pred p; .reg .u32 n; mov.u32 n, 0;\n"
               "W: mbarrier.try_wait.parity.shared::cta.b64 p, [%0], 0;\n"
               "@p bra D; add.u32 n, n, 1; setp.gt.u32 p, n, %1; @p trap; bra W;\n"
               "D: }" ::"r"(bar), "n"(SPIN_LIMIT) : "memory");
}
__device__ __forceinline__ void mbar_arrive(uint32_t bar, uint32_t n) {
  asm volatile("mbarrier.arrive.shared::cta.b64 _, [%0], %1;" ::"r"(bar), "r"(n) : "memory");
}
__device__ __forceinline__ void mbar_arrive_if0(int z, uint32_t bar, uint32_t n) {
  asm volatile("{.reg .pred p; setp.eq.s32 p, %2, 0; @p mbarrier.arrive.shared::cta.b64 _, [%0], %1;}" ::"r"(bar), "r"(n), "r"(z) : "memory");
}
__device__ __forceinline__ void mbar_arrive_remote_if0(int z, uint32_t bar) {
  asm volatile("{.reg .pred p; setp.eq.s32 p, %1, 0; @p mbarrier.arrive.shared::cluster.b64 _, [%0];}" ::"r"(bar), "r"(z) : "memory");
}
__device__ __forceinline__ void mbar_expect(uint32_t bar, uint32_t bytes) {
  asm volatile("mbarrier.arrive.expect_tx.shared::cta.b64 _, [%0], %1;" ::"r"(bar), "r"(bytes) : "memory");
  asm volatile("mbarrier.arrive.shared::cta.b64 _, [%0], 7;" ::"r"(bar) : "memory");
}
__device__ __forceinline__ void tma2d(uint32_t dst, const CUtensorMap* tm, uint32_t bar, int c0, int c1) {
  asm volatile("cp.async.bulk.tensor.2d.shared::cluster.global.mbarrier::complete_tx::bytes [%0],[%1,{%3,%4}],[%2];"
               ::"r"(dst), "l"(tm), "r"(bar), "r"(c0), "r"(c1) : "memory");
}
__device__ __forceinline__ void tma3d(uint32_t dst, const CUtensorMap* tm, uint32_t bar, int c0, int c1, int c2) {
  asm volatile("cp.async.bulk.tensor.3d.shared::cluster.global.mbarrier::complete_tx::bytes [%0],[%1,{%3,%4,%5}],[%2];"
               ::"r"(dst), "l"(tm), "r"(bar), "r"(c0), "r"(c1), "r"(c2) : "memory");
}
__device__ __forceinline__ void tma2d_pair(uint32_t dst, const CUtensorMap* tm, uint32_t bar, int c0, int c1) {
  asm volatile("cp.async.bulk.tensor.2d.shared::cluster.global.mbarrier::complete_tx::bytes.multicast::cluster [%0],[%1,{%3,%4}],[%2],%5;"
               ::"r"(dst), "l"(tm), "r"(bar), "r"(c0), "r"(c1), "h"((uint16_t)3) : "memory");
}
__device__ __forceinline__ void bulk_load(uint32_t dst, const void* src, uint32_t bytes, uint32_t bar) {
  asm volatile("cp.async.bulk.shared::cluster.global.mbarrier::complete_tx::bytes [%0],[%1],%2,[%3];"
               ::"r"(dst), "l"(src), "r"(bytes), "r"(bar) : "memory");
}
__device__ __forceinline__ void bulk_store(void* dst, uint32_t src, uint32_t bytes) {
  asm volatile("cp.async.bulk.global.shared::cta.bulk_group [%0],[%1],%2;" ::"l"(dst), "r"(src), "r"(bytes) : "memory");
}
__device__ __forceinline__ void bulk_commit_wait() {
  asm volatile("cp.async.bulk.commit_group;" ::: "memory");
  asm volatile("cp.async.bulk.wait_group 0;" ::: "memory");
}
__device__ __forceinline__ void l2_prefetch(const void* src, uint32_t bytes) {
  asm volatile("cp.async.bulk.prefetch.L2.global [%0], %1;" ::"l"(src), "r"(bytes) : "memory");
}
__device__ __forceinline__ void fence_gpu() { asm volatile("fence.acq_rel.gpu;" ::: "memory"); }
__device__ __forceinline__ void fence_async_smem() { asm volatile("fence.proxy.async.shared::cta;" ::: "memory"); }
__device__ __forceinline__ void fence_async_global() { asm volatile("fence.proxy.async.global;" ::: "memory"); }
__device__ __forceinline__ void st_flag(uint32_t* p, uint32_t v) {
  asm volatile("st.relaxed.gpu.global.u32 [%0], %1;" ::"l"(p), "r"(v) : "memory");
}
__device__ __forceinline__ uint32_t ld_acq(const uint32_t* p) {
  uint32_t v;
  asm volatile("ld.acquire.gpu.global.u32 %0, [%1];" : "=r"(v) : "l"(p) : "memory");
  return v;
}
__device__ __forceinline__ void wg_fence() { asm volatile("wgmma.fence.sync.aligned;" ::: "memory"); }
__device__ __forceinline__ void wg_commit() { asm volatile("wgmma.commit_group.sync.aligned;" ::: "memory"); }
template <int N> __device__ __forceinline__ void wg_wait() { asm volatile("wgmma.wait_group.sync.aligned %0;" ::"n"(N) : "memory"); }
template <int N> __device__ __forceinline__ void reg_fence(float (&a)[N]) {
#pragma unroll
  for (int i = 0; i < N; i++) asm volatile("" : "+f"(a[i])::"memory");
}
template <int ID, int N> __device__ __forceinline__ void named_bar() { asm volatile("bar.sync %0, %1;" ::"n"(ID), "n"(N) : "memory"); }
template <int N> __device__ __forceinline__ void reg_fence(uint32_t (&a)[N]) {
#pragma unroll
  for (int i = 0; i < N; i++) asm volatile("" : "+r"(a[i])::"memory");
}
__device__ __forceinline__ Desc mkdesc(uint32_t dyn, uint32_t off, uint32_t lbo, uint32_t sbo, uint32_t swz) {
  return Desc{dyn, ((off + SMEM_BASE) >> 4) + ((lbo >> 4) << 16), (sbo >> 4) | (swz << 30)};
}
__device__ __forceinline__ uint32_t pack2(float lo, float hi) {
  uint32_t r;
  asm("cvt.rn.bf16x2.f32 %0, %1, %2;" : "=r"(r) : "f"(hi), "f"(lo));
  return r;
}
__device__ __forceinline__ float bf_lo(uint32_t v) { return __uint_as_float(v << 16); }
__device__ __forceinline__ float bf_hi(uint32_t v) { return __uint_as_float(v & 0xffff0000u); }
__device__ __forceinline__ void stsm4(uint32_t addr, uint32_t a, uint32_t b, uint32_t c, uint32_t d) {
  asm volatile("stmatrix.sync.aligned.m8n8.x4.shared.b16 [%0], {%1,%2,%3,%4};" ::"r"(addr), "r"(a), "r"(b), "r"(c), "r"(d) : "memory");
}
__device__ __forceinline__ void ldsm4(uint32_t addr, uint32_t* r) {
  asm volatile("ldmatrix.sync.aligned.m8n8.x4.shared.b16 {%0,%1,%2,%3}, [%4];" : "=r"(r[0]), "=r"(r[1]), "=r"(r[2]), "=r"(r[3]) : "r"(addr) : "memory");
}
__device__ __forceinline__ float2 lds64(uint32_t a) {
  float2 v;
  asm volatile("ld.shared.v2.f32 {%0,%1}, [%2];" : "=f"(v.x), "=f"(v.y) : "r"(a) : "memory");
  return v;
}
__device__ __forceinline__ float4 lds128(uint32_t a) {
  float4 v;
  asm volatile("ld.shared.v4.f32 {%0,%1,%2,%3}, [%4];" : "=f"(v.x), "=f"(v.y), "=f"(v.z), "=f"(v.w) : "r"(a) : "memory");
  return v;
}
__device__ __forceinline__ uint32_t lds32(uint32_t a) {
  uint32_t v;
  asm volatile("ld.shared.u32 %0, [%1];" : "=r"(v) : "r"(a) : "memory");
  return v;
}
__device__ __forceinline__ void sts32(uint32_t a, uint32_t v) { asm volatile("st.shared.u32 [%0], %1;" ::"r"(a), "r"(v) : "memory"); }
__device__ __forceinline__ void sts64(uint32_t a, uint32_t x, uint32_t y) {
  asm volatile("st.shared.v2.u32 [%0], {%1,%2};" ::"r"(a), "r"(x), "r"(y) : "memory");
}
__device__ __forceinline__ void sts128(uint32_t a, uint32_t x, uint32_t y, uint32_t z, uint32_t w) {
  asm volatile("st.shared.v4.u32 [%0], {%1,%2,%3,%4};" ::"r"(a), "r"(x), "r"(y), "r"(z), "r"(w) : "memory");
}
__device__ __forceinline__ float ex2(float x) {
  float r;
  asm("ex2.approx.ftz.f32 %0, %1;" : "=f"(r) : "f"(x));
  return r;
}
__device__ __forceinline__ float rcp(float x) {
  float r;
  asm("rcp.approx.ftz.f32 %0, %1;" : "=f"(r) : "f"(x));
  return r;
}
constexpr float LOG2E = 1.4426950408889634f, LN2 = 0.6931471805599453f;
__device__ __forceinline__ float phi2(float t2) { return fmaf(fmaxf(t2, 0.f), LN2, ex2(fminf(t2, 0.f))) + 1e-6f; }
__device__ __forceinline__ float gelu(float y) {
  float p = fmaf(y * y, 0.044715f * 0.7978845608028654f, 0.7978845608028654f);
  float th;
  asm("tanh.approx.f32 %0, %1;" : "=f"(th) : "f"(y * p));
  float hy = 0.5f * y;
  return fmaf(hy, th, hy);
}
constexpr uint32_t ONES = 0x3F803F80u;
__device__ __forceinline__ void ll_store(uint4* p, float a, float b, uint32_t tag) {
  asm volatile("st.relaxed.gpu.global.v4.u32 [%0], {%1,%2,%3,%2};" ::"l"(p), "r"(__float_as_uint(a)), "r"(tag), "r"(__float_as_uint(b)) : "memory");
}
__device__ __forceinline__ uint4 ll_load(const void* p) {
  uint4 v;
  asm volatile("ld.relaxed.gpu.global.v4.u32 {%0,%1,%2,%3}, [%4];" : "=r"(v.x), "=r"(v.y), "=r"(v.z), "=r"(v.w) : "l"(p) : "memory");
  return v;
}
template <int N>
__device__ __forceinline__ void ll_wait(uint4 (&v)[N], const uint4* p, int stride, uint32_t tag) {
  uint32_t bad;
  int it = 0;
  do {
    bad = 0;
#pragma unroll
    for (int m = 0; m < N; m++) v[m] = ll_load(p + m * stride);
#pragma unroll
    for (int m = 0; m < N; m++) bad |= (v[m].y ^ tag) | (v[m].w ^ tag);
  } while (bad && ++it < SPIN_LIMIT);
}
__device__ __forceinline__ float2 ll_sum4(const uint4* p, uint32_t tag) {
  uint4 v[4];
  ll_wait(v, p, 1728, tag);
  return make_float2((__uint_as_float(v[0].x) + __uint_as_float(v[1].x)) + (__uint_as_float(v[2].x) + __uint_as_float(v[3].x)),
                     (__uint_as_float(v[0].z) + __uint_as_float(v[1].z)) + (__uint_as_float(v[2].z) + __uint_as_float(v[3].z)));
}
__device__ __forceinline__ void poll_flag(const uint32_t* f, int bit, uint32_t& mask, uint32_t epoch) {
  while (!(mask >> bit & 1)) {
    mask = __ballot_sync(0xffffffffu, ld_acq(f) == epoch);
    fence_async_global();
  }
}
template <bool PHI>
__device__ __forceinline__ void ln_pair(const float* a, const float2* cs, const float2 (&st)[2], uint32_t* o) {
#pragma unroll
  for (int tt = 0; tt < 2; tt++) {
#pragma unroll
    for (int hh = 0; hh < 2; hh++) {
      float y0 = fmaf(st[hh].x, a[4 * tt + 2 * hh], st[hh].y * cs[tt].x), y1 = fmaf(st[hh].x, a[4 * tt + 2 * hh + 1], st[hh].y * cs[tt].y);
      if (PHI) { y0 = phi2(y0); y1 = phi2(y1); }
      o[2 * tt + hh] = pack2(y0, y1);
    }
  }
}

__global__ void __cluster_dims__(2, 1, 1) __launch_bounds__(384, 1)
fused_block_kernel(const __grid_constant__ Maps maps, const __nv_bfloat16* __restrict__ x, const __nv_bfloat16* __restrict__ wqkv,
                   const __nv_bfloat16* __restrict__ wo, const __nv_bfloat16* __restrict__ w1,
                   const __nv_bfloat16* __restrict__ b1, const __nv_bfloat16* __restrict__ w2,
                   const __nv_bfloat16* __restrict__ b2, __nv_bfloat16* __restrict__ out) {
  extern __shared__ __align__(1024) uint8_t smem_raw[];
  const uint32_t sb = (uint32_t)__cvta_generic_to_shared(smem_raw);
  const uint32_t bars = sb + OFF_BAR;
  const int warp = __shfl_sync(0xffffffffu, threadIdx.x >> 5, 0);
  const int lane = threadIdx.x & 31;

  const int cl = blockIdx.x >> 1, q = blockIdx.x & 1;
  const int u7 = ((cl - 36) * 37) >> 8;
  const int oct = cl < 4 ? 0 : cl < 36 ? 1 + 2 * ((cl - 4) & 7) : 2 + 2 * (cl - 36 - 7 * u7);
  const int u4 = cl < 4 ? cl : cl < 36 ? (cl - 4) >> 3 : u7;
  const int i = 2 * (oct & 7) + (u4 >> 1), p = 2 * (oct >> 3) + (u4 & 1);
  const int j = 2 * p + q;
  auto col_f = [](int jj) { return 160 * (jj >> 1) + 16 * (jj & 2) + 64 * (jj & 1); };
  auto col_r = [](int jj) { return 160 * (jj >> 1) + 128 - 64 * (jj & 2) + 16 * (jj & 1); };
  const int cF = col_f(j), cR = col_r(j), role = q ^ (p & 1);

  auto load_kv = [&](int s, int slot) {
    const uint32_t dst = sb + OFF_RING + slot * 12288, bar = bars + 8 * (FKV + s);
    mbar_expect(bar, 10240);
    tma3d(dst, &maps.m[M_KVF], bar, cF, 32 * s, 1);
    tma2d(dst + 8192, &maps.m[M_KVH], bar, 640 + 640 * role + cR - 16 * q, 32 * s);
  };
  auto load_x = [&](int c, int b, int slot) {
    mbar_expect(bars + 8 * (FX + b), 16384);
    tma2d(sb + slot * 16384, &maps.m[M_X], bars + 8 * (FX + b), 64 * c, 128 * i);
    tma2d(sb + slot * 16384 + 8192, &maps.m[M_X], bars + 8 * (FX + b), 64 * c, 128 * i + 64);
  };
  auto load_x_pair = [&](int c) {
    mbar_expect(bars + 8 * (FX + c), 16384);
    tma2d_pair(sb + c * 16384 + q * 8192, &maps.m[M_X], bars + 8 * (FX + c), 64 * c, 128 * i + 64 * q);
  };

  if (warp < 11 && elect_one()) asm volatile("prefetch.tensormap [%0];" ::"l"(&maps.m[warp]) : "memory");
  if (warp >= 1 && warp <= 8) {
    const uint32_t b0 = bars + 256 * (warp & 7);
    if (elect_one()) {
#pragma unroll
      for (int n = 0; n < 32; n++) asm volatile("mbarrier.init.shared::cta.b64 [%0], 8;" ::"r"(b0 + 8 * n) : "memory");
      asm volatile("fence.mbarrier_init.release.cluster;" ::: "memory");
    }
    __syncwarp();
    if (warp == 8 && elect_one()) {
      load_x(0, 0, 0);
      load_kv(0, 0);
      load_kv(1, 1);
    }
  }
  asm volatile("fence.release.sync_restrict::shared::cta.cluster;" ::: "memory");
  asm volatile("barrier.cluster.arrive.relaxed.aligned;" ::: "memory");

  if (warp >= 8) {
    asm volatile("setmaxnreg.dec.sync.aligned.u32 88;");
    if (warp == 8) {
      asm volatile("barrier.cluster.wait.aligned;" ::: "memory");
      if (elect_one()) {
        load_x_pair(1);
        load_kv(2, 2);
        load_kv(3, 3);
        load_x_pair(2);
        load_kv(4, 4);
      }
      TL(40);
#pragma unroll 1
      for (int s = 5, slot = 0; s < 20; s++) {
        mbar_wait(bars + 8 * (DKV + s - 5));
        if (elect_one()) {
          if ((s & 1) && s < 18) load_x_pair((s + 1) >> 1);
          load_kv(s, slot);
        }
        slot = slot == 4 ? 0 : slot + 1;
      }
#pragma unroll 1
      for (int t = 0, slot = 0; t < 10; t++) {
        mbar_wait(bars + 8 * (DKV + 15 + t));
        if (elect_one()) {
          if (t >= 6 && t < 9) load_x(t - 6, t + 4, t - 2);
          const uint32_t dst = sb + OFF_RING + slot * 12288, bar = bars + 8 * (FQ + t);
          const int k0 = 64 * (t < 7 ? t + 3 : t - 7);
          mbar_expect(bar, 10240);
          tma3d(dst, &maps.m[M_Q2], bar, 0, k0, 5 * p + 3 * q);
          tma2d(dst + 8192, &maps.m[M_QR], bar, 80 * j + 64 - 64 * q, k0);
        }
        slot = slot == 4 ? 0 : slot + 1;
      }
#pragma unroll 1
      for (int n = 0, tp = 0; n < 32; n += 4) {
        mbar_wait(bars + 8 * (DQ + ((0x99876665u >> n) & 15)));
        if (n) mbar_wait(bars + 8 * (FWO + tp));
        const int t = (0x70654321u >> n) & 7, k0 = 80 * (t == 0 ? j : t - (t <= j));
        tp = t;
        if (elect_one()) {
          const uint32_t dst = sb + 10 * PAGE + t * 15360, bar = bars + 8 * (FWO + t);
          mbar_expect(bar, 12800);
          tma3d(dst, &maps.m[M_WO2], bar, 0, k0, cF >> 5);
          tma2d(dst + 10240, &maps.m[M_WOR], bar, cR, k0);
        }
      }
#pragma unroll 1
      for (int t = 0; t < 8; t++) {
        const uint32_t wb = bars + 8 * (t == 0 ? FWO - 1 : t < 5 ? DW + 2 * t - 1 : DF + t - 5);
        const int jj = t == 0 ? j : t - (t <= j);
        mbar_wait(wb);
        mbar_wait(wb + 64);
        if (elect_one()) {
          const uint32_t dst = sb + (7 + 3 * (t < 5 ? t : t - 5)) * PAGE, bar = bars + 8 * (FW1 + t);
          mbar_expect(bar, 30720);
          tma3d(dst, &maps.m[M_W1], bar, 0, col_f(jj), 3 * j);
          tma3d(dst + 24576, &maps.m[M_W1R], bar, 0, col_r(jj), 3 * j);
        }
      }
#pragma unroll 1
      for (int t = 0; t < 12; t++) {
        const int t6 = t < 6 ? t : t - 6;
        const uint32_t wb = bars + 8 * (t < 6 ? DF + ((0x776544 >> (4 * t)) & 7) : DG + t6);
        const int uu = (0xA95024 >> (2 * t)) & 3, n = (0x924900 >> (2 * t)) & 3;
        const int k0 = 192 * (t < 3 ? j : 2 * (n + (n >= p)) + q) + 64 * uu;
        const uint32_t dst = sb + OFF_W2 + ((0x321045 >> (4 * t6)) & 7) * 24576, bar = bars + 8 * (FW2 + t);
        mbar_wait(wb);
        mbar_wait(wb + (t < 6 ? 64 : 96));
        if (elect_one()) {
          mbar_expect(bar, 20480);
          tma2d(dst, &maps.m[M_W2F], bar, cF, k0);
          tma2d(dst + 8192, &maps.m[M_W2F], bar, cF + 64 - 128 * q, k0);
          tma2d(dst + 16384, &maps.m[M_W2H], bar, cR - 16 * q, k0);
        }
      }
    } else {
      uint32_t epoch;
      asm volatile("ld.relaxed.gpu.global.u32 %0, [%1];" : "=r"(epoch) : "l"(&g_epoch) : "memory");
      epoch += 1;
      const int unit = i * 8 + j, hw = warp - 9, ht = hw * 32 + lane;
#pragma unroll 1
      for (int pass = 0; pass < 2; pass++) {
        const int r4 = lane >> 3, v8 = lane & 7;
        if (hw == 2) {
          const int ld = pass ? 1536 : 1920, part = unit & 3, cg = unit >> 2;
          if (64 * cg < ld) {
            const __nv_bfloat16* wp = (pass ? w1 : wqkv) + (part * 160 + r4) * ld + 64 * cg + 8 * v8;
            float d[8];
#pragma unroll
            for (int e = 0; e < 8; e++) d[e] = 0.f;
#pragma unroll 1
            for (int r = 0; r < 4; r++) {
              uint4 v[10];
#pragma unroll
              for (int m = 0; m < 10; m++) v[m] = __ldg(reinterpret_cast<const uint4*>(wp + m * 4 * ld));
              wp += 40 * ld;
#pragma unroll
              for (int m = 0; m < 10; m++) {
                d[0] += bf_lo(v[m].x); d[1] += bf_hi(v[m].x); d[2] += bf_lo(v[m].y); d[3] += bf_hi(v[m].y);
                d[4] += bf_lo(v[m].z); d[5] += bf_hi(v[m].z); d[6] += bf_lo(v[m].w); d[7] += bf_hi(v[m].w);
              }
            }
#pragma unroll 1
            for (int o = 8; o < 32; o <<= 1) {
#pragma unroll
              for (int e = 0; e < 8; e++) d[e] += __shfl_xor_sync(0xffffffffu, d[e], o);
            }
            if (r4 & 2) { d[0] = d[4]; d[1] = d[5]; d[2] = d[6]; d[3] = d[7]; }
            ll_store(g_cs + part * 1728 + 960 * pass + 32 * cg + 4 * v8 + r4, r4 & 1 ? d[2] : d[0], r4 & 1 ? d[3] : d[1], epoch);
          }
          if (pass) break;
          TL(8);
        } else {
#pragma unroll 1
          for (int r = 0; r < 2; r++) {
            const int row = 128 * i + 16 * j + 8 * hw + 4 * r + r4;
            float sm = 0.f, sq = 0.f;
            uint4 v[10];
#pragma unroll
            for (int m = 0; m < 10; m++) v[m] = __ldg(reinterpret_cast<const uint4*>(x + row * 640) + v8 + 8 * m);
#pragma unroll
            for (int m = 0; m < 10; m++) {
              const uint32_t vv[4] = {v[m].x, v[m].y, v[m].z, v[m].w};
#pragma unroll
              for (int e = 0; e < 4; e++) {
                const float a = bf_lo(vv[e]), b = bf_hi(vv[e]);
                sm += a + b;
                sq = fmaf(a, a, fmaf(b, b, sq));
              }
            }
#pragma unroll
            for (int o = 1; o < 8; o <<= 1) {
              sm += __shfl_xor_sync(0xffffffffu, sm, o);
              sq += __shfl_xor_sync(0xffffffffu, sq, o);
            }
            const float mean = sm * (1.f / 640.f);
            const float rstd = rsqrtf(fmaxf(fmaf(-mean, mean, sq * (1.f / 640.f)), 0.f) + 1e-5f);
            if (v8 == 0) ll_store(g_ln1 + row, rstd, -rstd * mean, epoch);
          }
          if (hw == 0) TL(10);
        }
        asm volatile("barrier.cluster.wait.aligned;" ::: "memory");
        named_bar<2, 96>();
        if (lane == 0) {
          const uint32_t nb = hw ? 15360 : 6400;
          l2_prefetch(reinterpret_cast<const uint8_t*>(hw == 0 ? wo : hw == 1 ? w1 : w2) + blockIdx.x * nb, nb);
          mbar_expect(bars + 8 * (RX + hw), hw == 2 ? 8192 : 10240);
          sts32(sb + OFF_EPOCH, epoch);
        }
        if (hw < 2) {
          uint4 v[2];
          ll_wait(v, g_ln1 + 128 * i + ht, 64, epoch);
          sts64(sb + OFF_LN1 + ht * 8, v[0].x, v[0].z);
          sts64(sb + OFF_LN1 + ht * 8 + 512, v[1].x, v[1].z);
        }
#pragma unroll 1
        for (int n = 2 * ht; n < 240; n += 192) {
          int col;
          if (n < 160) col = n + (n < 64 ? 640 + cF : n < 128 ? 1216 + cF : 512 + 640 * role + cR - 16 * q);
          else {
            col = 80 * j + n - 160 + (q ? (n < 224 ? 16 : -64) : 0);
            const uint32_t bb = *reinterpret_cast<const uint32_t*>(b2 + (n < 224 ? cF + n - 160 : cR + n - 224));
            sts64(sb + OFF_B2 + (n - 160) * 4, bb << 16, bb & 0xffff0000u);
          }
          const float2 v = ll_sum4(g_cs + (col >> 1), epoch);
          sts64(sb + OFF_CSKV + n * 4, __float_as_uint(v.x), __float_as_uint(v.y));
        }
        __syncwarp();
        mbar_arrive_if0(lane, bars + 8 * SIDE, hw == 2 ? 2 : 3);
        if (hw == 0) TL(11);
        mbar_wait_wd(bars + 8 * (hw == 2 ? DQ : RKV));
        if (hw == 2) {
#pragma unroll 1
          for (int m = 0; m < 30; m++) sts128(sb + OFF_KVB + (m * 32 + lane) * 16, 0, 0, 0, 0);
        } else if (ht < 60) {
          const float2* src = g_kv1 + (j * 16 + i) * 1024 + ht;
          const uint32_t tag = epoch & 15;
          float sa, sc;
          uint32_t bad;
          int it = 0;
          do {
            uint32_t a[16], b[16];
#pragma unroll
            for (int m = 0; m < 16; m++)
              asm volatile("ld.relaxed.gpu.global.v2.u32 {%0,%1}, [%2];" : "=r"(a[m]), "=r"(b[m]) : "l"(src + m * 64) : "memory");
            sa = sc = 0.f;
            bad = 0;
#pragma unroll
            for (int m = 0; m < 16; m++) {
              bad |= (a[m] ^ tag) | (b[m] ^ tag);
              sa += __uint_as_float(a[m]);
              sc += __uint_as_float(b[m]);
            }
          } while ((bad & 15) && ++it < SPIN_LIMIT);
          asm volatile("st.relaxed.gpu.global.v2.u32 [%0], {%1,%2};" ::"l"(g_kv2 + j * 960 + i * 60 + ht), "r"(pack2(sa, sc)), "r"(epoch) : "memory");
        }
        if (hw == 0) TL(5);
        named_bar<2, 96>();
        {
          uint4 v[5];
          ll_wait(v, reinterpret_cast<const uint4*>(g_kv2 + j * 960) + ht, 96, epoch);
          if (hw == 0) TL(6);
          const int d0 = ht / 6, part = ht - 6 * d0;
#pragma unroll
          for (int m = 0; m < 5; m++) {
            const int d = d0 + 16 * m, head = (d * 205) >> 12, n = 20 * head + 4 * part;
            const uint32_t a = sb + OFF_KVB + d * 16;
            const uint32_t z = head & 1 ? v[m].x << 16 : v[m].x & 0xffffu;
            if (part < 5) sts64(a + (n >> 3) * 1280 + (n & 7) * 2, v[m].x, v[m].z);
            else sts128(a + (10 + (head >> 1)) * 1280, z, z, z, z);
          }
        }
        fence_async_smem();
        __syncwarp();
        mbar_arrive_if0(lane, bars + 8 * KVB, hw == 2 ? 2 : 3);
        if (hw == 0) TL(7);
        if (hw < 2) break;
      }

      if (hw == 2) {
#pragma unroll 1
        for (int n = lane; n < 96; n += 32) {
          const uint32_t bb = *reinterpret_cast<const uint32_t*>(b1 + 192 * j + 2 * n);
          const float2 v = ll_sum4(g_cs + 960 + 96 * j + n, epoch);
          sts128(sb + OFF_CB1 + n * 16, __float_as_uint(v.x), __float_as_uint(v.y), bb << 16, bb & 0xffff0000u);
        }
        __syncwarp();
        mbar_arrive_if0(lane, bars + 8 * SIDE2, 8);
        TL(18);
#pragma unroll 1
        for (int s = 0; s < 2; s++) {
          uint8_t* dst = g_act + ((64 + 2 * i + s) * 8 + j) * 24576;
          mbar_wait_wd(bars + 8 * (AF + 12 * s + 1));
          if (lane == 0) bulk_store(dst + 8192, sb + s * OFF_R1 + 8192, 8192);
          __syncwarp();
          mbar_wait_wd(bars + 8 * (AF + 12 * s + 2));
          if (lane == 0) {
            bulk_store(dst + 16384, sb + s * OFF_R1 + 16384, 8192);
            bulk_commit_wait();
            mbar_arrive(bars + 8 * (SFB + s), 8);
            fence_gpu();
            st_flag(g_flag + (64 + 2 * i + s) * 32 + 8 + j, epoch);
          }
          __syncwarp();
          TL(50 + s);
        }
        mbar_wait_wd(bars + 8 * END);
        if (blockIdx.x == 0 && lane == 0) g_epoch = epoch;
      } else {
        const int s = hw;
#pragma unroll 1
        for (int ph = 0; ph < 3; ph++) {
          uint32_t ab = bars + 8 * (ph < 2 ? AO + 16 * ph + 8 * s : AF + 12 * s);
          const uint32_t bytes = ph < 2 ? 10240 : 8192, base = sb + (ph ? s * OFF_R1 : 0);
          uint8_t* gb = g_act + (ph * 32 + 2 * i + s) * 8 * 24576;
          uint32_t* fl = g_flag + (ph * 32 + 2 * i + s) * 32;
          mbar_wait(ab);
          if (elect_one()) {
            bulk_store(gb + j * 24576, sb + s * (ph ? OFF_R1 : PAGE), bytes);
            bulk_commit_wait();
            if (ph == 0) mbar_arrive(bars + 8 * (SO + s), 8);
            fence_gpu();
            st_flag(fl + j, epoch);
          }
          __syncwarp();
          TL(44 + 2 * ph + s);
          uint32_t slots;
          uint64_t waits;
          if (ph == 0) {
            slots = s ? 02165432u : 00165432u;
            waits = s ? 011060504030201ull : 000101010101010ull;
            if (s == 0) mbar_wait(bars + 8 * (SO + 1));
          } else if (ph == 1) {
            slots = 01021021u;
            waits = 024232221201717ull + (s ? 010101010100000ull : 0);
          } else {
            slots = 0321032103u;
            waits = 0474645444342414027ull + (s ? 0141414141414141410ull : 0);
            ab += 16;
          }
          uint32_t mask = 0;
#pragma unroll 1
          for (int r = 0; r < (ph < 2 ? 7 : 9); r++) {
            int cc = r + (r >= j), bit = cc;
            uint32_t off = 0;
            if (ph == 2) {
              const int uu = (r * 11) >> 5, n = r - 3 * uu;
              cc = 2 * (n + (n >= p)) + q;
              bit = cc + (uu ? 8 : 0);
              off = uu * 8192;
              if (r == 2) mbar_wait(bars + 8 * (SFB + s));
            }
            ab += 8;
            mbar_wait(bars + 8 * (DW + ((uint32_t)waits & 63)));
            poll_flag(fl + lane, bit, mask, epoch);
            if (r == 0) TL(52 + 2 * ph + s);
            if (elect_one()) {
              mbar_expect(ab, bytes);
              bulk_load(base + (slots & 7) * bytes, gb + cc * 24576 + off, bytes, ab);
            }
            slots >>= 3;
            waits >>= 6;
          }
        }
      }
    }
  } else {
    asm volatile("setmaxnreg.inc.sync.aligned.u32 208;");
    asm volatile("barrier.cluster.wait.aligned;" ::: "memory");
    const int s = warp >> 2, w = warp & 3, tid = threadIdx.x & 127, c = lane & 3, g = lane >> 2;
    uint32_t sb_peer;
    asm volatile("mapa.shared::cluster.u32 %0, %1, %2;" : "=r"(sb_peer) : "r"(sb), "r"(q ^ 1));
    const int row0 = 128 * i + 64 * s + 16 * w;
    const uint32_t bs8 = bars + 64 * s, bs12 = bars + 96 * s;
    uint32_t pq[20], hp[20];
    uint32_t epoch;
    {
      float acc[80];
      const Desc dx = mkdesc(s * 512, 0, 16, 1024, 1);
#pragma unroll
      for (int st = 0; st < 20; st++) {
        if ((st & 1) == 0) mbar_wait(bars + 8 * (FX + (st >> 1)));
        mbar_wait(bars + 8 * (FKV + st));
        const Desc da = dx + (st >> 1) * 1024 + (st & 1) * 4, db = mkdesc(0, OFF_RING + (st % 5) * 12288, 4096, 1024, 1);
        wg_fence();
        wgmma_ss<160, 0, 1>(acc, da, db, st != 0);
        wgmma_ss<160, 0, 1>(acc, da + 2, db + 128, 1);
        wg_commit();
        if (st == 0) TL0(0);
        if (st == 18) {
          const uint32_t xa = sb + (64 * s + 16 * w + (lane & 15)) * 128;
#pragma unroll
          for (int ks = 0; ks < 5; ks++) {
            const int col = ks < 4 ? cF + 16 * ks : cR;
            ldsm4(xa + (col >> 6) * 16384 + (((((col & 63) >> 3) + (lane >> 4)) ^ (lane & 7)) << 4), hp + 4 * ks);
          }
          reg_fence(hp);
          mbar_arrive_remote_if0(lane, sb_peer + OFF_BAR + 8 * PX);
        }
        if (st > 0) {
          wg_wait<1>();
          mbar_arrive_if0(lane, bars + 8 * (DKV + st - 1), 1);
        }
      }
      TL0(12);
      float accq[40];
      auto q_step = [&](int t) {
        if (t >= 7) mbar_wait(bars + 8 * (FX + 3 + t));
        mbar_wait(bars + 8 * (FQ + t));
        const Desc da = dx + (t < 7 ? t + 3 : t - 3) * 1024, db = mkdesc(0, OFF_RING + (t % 5) * 12288, 4096, 512, 2);
        wg_fence();
#pragma unroll
        for (int ks = 0; ks < 4; ks++) wgmma_ss<80, 0, 1>(accq, da + 2 * ks, db + 64 * ks, (t | ks) != 0);
        wg_commit();
      };
      mbar_wait(bars + 8 * SIDE);
      epoch = lds32(sb + OFF_EPOCH);
      float2 sk[2], sv[2], cs[20];
#pragma unroll
      for (int r = 0; r < 2; r++) {
        sv[r] = lds64(sb + OFF_LN1 + (64 * s + 16 * w + g + 8 * r) * 8);
        sk[r] = make_float2(sv[r].x * LOG2E, sv[r].y * LOG2E);
      }
#pragma unroll
      for (int n = 0; n < 20; n++) cs[n] = lds64(sb + OFF_CSKV + c * 8 + n * 32);
      q_step(0);
      mbar_wait(bars + 8 * (DKV + 17));
      mbar_wait_cluster(bars + 8 * PX);
      wg_wait<1>();
      reg_fence(acc);
      mbar_arrive_if0(lane, bars + 8 * (DKV + 19), 1);
      TL0(1);
      const int hi = lane >> 4;
      const uint32_t rowoff = sb + (64 * s + 16 * w + (lane & 15)) * 16;
      auto put = [&](const uint32_t* r, int L, int isv, bool maybe_remote) {
        const int m2 = 2 * (L < 5 ? L : L - 5);
        if (maybe_remote && (L >= 5) != q) {
          const uint32_t a = sb_peer + (m2 + (isv ? 10 + (m2 > 4) : 0)) * 2048 + (64 * s + 16 * w) * 16 + lane * 4;
#pragma unroll
          for (int e = 0; e < 4; e++)
            asm volatile("st.async.shared::cluster.mbarrier::complete_tx::bytes.b32 [%0], %1, [%2];"
                         ::"r"(a + (e >> 1) * 2048 + (e & 1) * 128), "r"(r[e]), "r"(sb_peer + OFF_BAR + 8 * RXK) : "memory");
        } else {
          const int gq = m2 + hi;
          stsm4(rowoff + (gq + (isv ? 10 + (gq > 4) : 0)) * 2048, r[0], r[1], r[2], r[3]);
        }
      };
      const int LF = 2 * (p & 1) + 4 * q, LH = 8 - 8 * (p & 1);
      uint32_t r[4], r2[4];
      if (role == 0) {
        ln_pair<true>(acc + 64, cs + 16, sk, r);
        ln_pair<true>(acc + 72, cs + 18, sk, r2);
      } else {
        ln_pair<false>(acc + 64, cs + 16, sv, r);
        ln_pair<false>(acc + 72, cs + 18, sv, r2);
      }
      put(r, LH, role, true);
      put(r2, LH + 1, role, true);
      q_step(1);
#pragma unroll
      for (int n = 0; n < 4; n++) {
        const int P = n == 0 ? 0 : n == 1 ? 3 : n - 1;
        ln_pair<true>(acc + 8 * P, cs + 2 * P, sk, r);
        ln_pair<false>(acc + 32 + 8 * P, cs + 8 + 2 * P, sv, r2);
        put(r, LF + P, 0, n < 2);
        put(r2, LF + P, 1, n < 2);
        if (n == 1) q_step(2);
      }
      sts128(rowoff + 15 * 2048, ONES, ONES, ONES, ONES);
      TL0(2);
      mbar_wait_cluster(bars + 8 * RXK);
      fence_async_smem();
      named_bar<1, 256>();
      TL0(3);
      float kv[24];
      {
        const Desc da = mkdesc(s * 640, 0, 128, 2048, 0), db = da + 1280;
        wg_fence();
#pragma unroll
        for (int kk = 0; kk < 8; kk++) wgmma_ss<48, 1, 1>(kv, da + 16 * kk, db + 16 * kk, kk != 0);
        wg_commit();
      }
      wg_wait<1>();
      mbar_arrive_if0(lane >= 3, bars + 8 * (DQ + lane), 1);
      q_step(3);
      wg_wait<1>();
      reg_fence(kv);
      TL0(4);
#pragma unroll
      for (int hh = 0; hh < 2; hh++) {
        const int r = 16 * w + g + 8 * hh, d = 40 * s + r, own = (d * 205) >> 10;
        const int e0 = c - (r < 20 ? 0 : r < 40 ? 10 : 99);
        float2* gp = g_kv1 + ((j * 16 + own) * 16 + i) * 64 + (d - 5 * own) * 12;
#pragma unroll
        for (int tt = 0; tt < 6; tt++) {
          const bool isz = s ? tt == 0 : tt == 5;
          const int e = e0 + 4 * (tt - s);
          const bool ok = isz ? (c < 2 && r < 40) : (unsigned)e < 10u;
          asm volatile("{.reg .pred p; setp.ne.u32 p, %3, 0; @p st.relaxed.gpu.global.v2.u32 [%0], {%1,%2};}"
                       ::"l"(gp + (isz ? 10 + c : e)), "r"((__float_as_uint(kv[4 * tt + 2 * hh]) & ~15u) | (epoch & 15)),
                       "r"((__float_as_uint(kv[4 * tt + 2 * hh + 1]) & ~15u) | (epoch & 15)), "r"((uint32_t)ok) : "memory");
        }
      }
      mbar_arrive_if0(lane, bars + 8 * RKV, 1);
      TL0(9);
#pragma unroll
      for (int t = 4; t < 10; t++) {
        q_step(t);
        if (t == 9) {
#pragma unroll
          for (int n = 0; n < 10; n++) cs[n] = lds64(sb + OFF_CSQ + c * 8 + n * 32);
        }
        wg_wait<1>();
        mbar_arrive_if0(lane, bars + 8 * (DQ + t - 1), 1);
      }
      wg_wait<0>();
      reg_fence(accq);
      mbar_arrive_if0(lane, bars + 8 * (DQ + 9), 1);
      TL0(13);
#pragma unroll
      for (int P = 0; P < 5; P++) ln_pair<true>(accq + 8 * P, cs + 2 * P, sk, pq + 4 * P);
      reg_fence(pq);
      TL0(14);
    }
    const uint32_t rs = sb + s * OFF_R1;
    const uint32_t stoff = (lane >> 4) * 1024 + (16 * w + (lane & 15)) * 16;
    const Desc drs = mkdesc(s * (OFF_R1 / 16), 0, 1024, 128, 0);
    float accg[80];
    {
      {
        float o[48];
        mbar_wait(bars + 8 * KVB);
        TL0(15);
        wg_fence();
#pragma unroll
        for (int ks = 0; ks < 5; ks++)
          wgmma_rs<96, 1>(o, pq[4 * ks], pq[4 * ks + 1], pq[4 * ks + 2], pq[4 * ks + 3], mkdesc(ks < 4 ? 16 * q : -64 * q, OFF_KVB + 256 * ks, 128, 1280, 0), ks != 0);
        wg_commit();
        wg_wait<0>();
        reg_fence(o);
        float inv[2][4];
#pragma unroll
        for (int hh = 0; hh < 2; hh++)
#pragma unroll
          for (int h = 0; h < 4; h++) inv[hh][h] = rcp(o[40 + 4 * (h >> 1) + 2 * hh + (h & 1)] + 1e-6f);
        uint32_t r[4];
#pragma unroll
        for (int t = 0; t < 10; t++) {
#pragma unroll
          for (int hh = 0; hh < 2; hh++) {
            const float f = t == 2 ? (c < 2 ? inv[hh][0] : inv[hh][1]) : t == 7 ? (c < 2 ? inv[hh][2] : inv[hh][3]) : inv[hh][(8 * t) / 20];
            r[2 * (t & 1) + hh] = pack2(o[4 * t + 2 * hh] * f, o[4 * t + 2 * hh + 1] * f);
          }
          if (t & 1) stsm4(sb + s * PAGE + stoff + (t >> 1) * 2048, r[0], r[1], r[2], r[3]);
        }
        fence_async_smem();
        __syncwarp();
        mbar_arrive_if0(lane, bs8 + 8 * AO, 2);
        TLW(16 + s);
      }
      float acc[40];
#pragma unroll
      for (int r = 0; r < 20; r++) { acc[2 * r] = bf_lo(hp[r]); acc[2 * r + 1] = bf_hi(hp[r]); }
      reg_fence(acc);
#pragma unroll
      for (int t = 0; t < 8; t++) {
        mbar_wait(bars + 8 * (FWO + t));
        mbar_wait(bs8 + 8 * (AO + t));
        if (t == 1) TLW(20 + s);
        const Desc da = mkdesc(t == 0 ? s * 640 : t == 7 ? s * 1280 : 0, (t == 0 || t == 7 ? 0 : t < 6 ? t + 1 : 1) * PAGE, 1024, 128, 0);
        const Desc db = mkdesc(0, 10 * PAGE + t * 15360, 5120, 512, 2);
        wg_fence();
#pragma unroll
        for (int ks = 0; ks < 5; ks++) wgmma_ss<80, 0, 1>(acc, da + 128 * ks, db + 64 * ks, 1);
        wg_commit();
        if (t == 0) wg_wait<0>();
        else if (t > 1) wg_wait<1>();
        if (t != 1) mbar_arrive_if0(lane, bs8 + 8 * (DW + (t ? t - 1 : 0)), 2);
      }
      wg_wait<0>();
      reg_fence(acc);
      mbar_arrive_if0(lane, bs8 + 8 * (DW + 7), 2);
      TLW(22 + s);
#pragma unroll
      for (int r = 0; r < 20; r++) hp[r] = pack2(acc[2 * r], acc[2 * r + 1]);
      mbar_wait(bs8 + 8 * (DW + 7));
#pragma unroll
      for (int ks = 0; ks < 5; ks++)
        stsm4(rs + stoff + ks * 2048, hp[4 * ks], hp[4 * ks + 1], hp[4 * ks + 2], hp[4 * ks + 3]);
      fence_async_smem();
      __syncwarp();
      mbar_arrive_if0(lane, bs8 + 8 * AH, 2);
      reg_fence(hp);
      TLW(24 + s);
    }
    float accf[96];
    uint4 hs[4];
#pragma unroll
    for (int t = 0; t < 8; t++) {
      mbar_wait(bars + 8 * (FW1 + t));
      mbar_wait(bs8 + 8 * (AH + t));
      if (t == 1) TLW(26 + s);
      const Desc da = drs + (t % 3) * (PAGE / 16), db = mkdesc(0, (7 + 3 * (t % 5)) * PAGE, 8192, 1024, 1);
      wg_fence();
#pragma unroll
      for (int ks = 0; ks < 4; ks++) wgmma_ss<192, 0, 1>(accf, da + 128 * ks, db + 128 * ks, (t | ks) != 0);
      wgmma_ss<192, 0, 1>(accf, da + 512, mkdesc(0, (7 + 3 * (t % 5)) * PAGE + 24576, 2048, 1024, 1), 1);
      wg_commit();
      if (t == 0) {
        float sm[2] = {0.f, 0.f}, sq[2] = {0.f, 0.f};
#pragma unroll
        for (int m = 0; m < 10; m++) {
          const float2 b = lds64(sb + OFF_B2 + (8 * m + 2 * c) * 4);
#pragma unroll
          for (int hh = 0; hh < 2; hh++) {
            const float h0 = bf_lo(hp[2 * m + hh]), h1 = bf_hi(hp[2 * m + hh]);
            sm[hh] += h0 + h1;
            sq[hh] = fmaf(h0, h0, fmaf(h1, h1, sq[hh]));
            const float v0 = b.x + h0, v1 = b.y + h1;
            const int e = 4 * m + 2 * hh;
            if (m < 8) { accg[e] = v0; accg[e + 1] = v1; accg[32 + e] = 0.f; accg[33 + e] = 0.f; }
            else { accg[e + 32] = q ? 0.f : v0; accg[e + 33] = q ? 0.f : v1; accg[e + 40] = q ? v0 : 0.f; accg[e + 41] = q ? v1 : 0.f; }
          }
        }
        reg_fence(accg);
#pragma unroll
        for (int o = 1; o < 4; o <<= 1) {
#pragma unroll
          for (int hh = 0; hh < 2; hh++) {
            sm[hh] += __shfl_xor_sync(0xffffffffu, sm[hh], o);
            sq[hh] += __shfl_xor_sync(0xffffffffu, sq[hh], o);
          }
        }
        if (c < 2) ll_store(g_hstat + ((2 * i + s) * 8 + j) * 64 + 16 * w + g + 8 * c, c ? sm[1] : sm[0], c ? sq[1] : sq[0], epoch);
        wg_wait<0>();
      } else if (t > 1) wg_wait<1>();
      if (t != 1) mbar_arrive_if0(lane, bs8 + 8 * (DF + (t ? t - 1 : 0)), 2);
      if (t == 5) {
#pragma unroll
        for (int m = 0; m < 4; m++) hs[m] = ll_load(g_hstat + ((2 * i + s) * 8 + 2 * c + (m >> 1)) * 64 + 16 * w + g + 8 * (m & 1));
      }
    }
    float ra[2], rb[2];
    while (((hs[0].y ^ epoch) | (hs[0].w ^ epoch) | (hs[1].y ^ epoch) | (hs[1].w ^ epoch) | (hs[2].y ^ epoch) | (hs[2].w ^ epoch) |
            (hs[3].y ^ epoch) | (hs[3].w ^ epoch)) != 0) {
#pragma unroll
      for (int m = 0; m < 4; m++) hs[m] = ll_load(g_hstat + ((2 * i + s) * 8 + 2 * c + (m >> 1)) * 64 + 16 * w + g + 8 * (m & 1));
    }
    __syncwarp();
#pragma unroll
    for (int hh = 0; hh < 2; hh++) {
      float sm = __uint_as_float(hs[hh].x) + __uint_as_float(hs[2 + hh].x), sq = __uint_as_float(hs[hh].z) + __uint_as_float(hs[2 + hh].z);
#pragma unroll
      for (int o = 1; o < 4; o <<= 1) {
        sm += __shfl_xor_sync(0xffffffffu, sm, o);
        sq += __shfl_xor_sync(0xffffffffu, sq, o);
      }
      const float mean = sm * (1.f / 640.f);
      ra[hh] = rsqrtf(fmaxf(fmaf(-mean, mean, sq * (1.f / 640.f)), 0.f) + 1e-5f);
      rb[hh] = -ra[hh] * mean;
    }
    mbar_wait(bars + 8 * SIDE2);
    reg_fence(ra);
    reg_fence(rb);
    wg_wait<0>();
    reg_fence(accf);
    mbar_arrive_if0(lane, bs8 + 8 * (DF + 7), 2);
    TLW(28 + s);
    auto g_step = [&](int t, int slot) {
      mbar_wait(bars + 8 * (FW2 + t));
      mbar_wait(bs12 + 8 * (AF + t));
      if (t == 3) TLW(32 + s);
      const Desc da = mkdesc(drs.base + (t & 3) * 512, 0, 1024, 128, 0), db = mkdesc(slot * 1536, OFF_W2, 8192, 1024, 1);
      wg_fence();
#pragma unroll
      for (int ks = 0; ks < 4; ks++) wgmma_ss<160, 0, 1>(accg, da + 128 * ks, db + 128 * ks, 1);
      wg_commit();
    };
#pragma unroll 1
    for (int t = 0; t < 3; t++) {
      uint32_t r[16];
#pragma unroll
      for (int n = 0; n < 8; n++) {
        const float4 cb = lds128(sb + OFF_CB1 + (32 * t + 4 * n + c) * 16);
#pragma unroll
        for (int hh = 0; hh < 2; hh++) {
          const float* a = accf + 4 * n + 2 * hh;
          const float y0 = fmaf(ra[hh], a[0], fmaf(rb[hh], cb.x, cb.z)), y1 = fmaf(ra[hh], a[1], fmaf(rb[hh], cb.y, cb.w));
          r[2 * n + hh] = pack2(gelu(y0), gelu(y1));
        }
      }
      mbar_wait(bs8 + 8 * (DF + 7));
#pragma unroll
      for (int n = 0; n < 4; n++) stsm4(rs + stoff + t * 8192 + n * 2048, r[4 * n], r[4 * n + 1], r[4 * n + 2], r[4 * n + 3]);
      fence_async_smem();
      __syncwarp();
      mbar_arrive_if0(lane, bs12 + 8 * (AF + t), 2);
#pragma unroll
      for (int e = 0; e < 64; e++) accf[e] = accf[e + 32];
      g_step(t, (0x045 >> (4 * t)) & 7);
      wg_wait<1>();
      mbar_arrive_if0(lane | (t == 0), bs12 + 8 * (DG + t - 1), 2);
    }
    TLW(30 + s);
    wg_wait<0>();
    mbar_arrive_if0(lane, bs12 + 8 * (DG + 2), 2);
#pragma unroll
    for (int t = 3; t < 12; t++) {
      g_step(t, (0x321045 >> (4 * (t % 6))) & 7);
      if (t > 3) {
        wg_wait<1>();
        mbar_arrive_if0(lane, bs12 + 8 * (DG + t - 1), 2);
        if (t == 7) mbar_arrive_remote_if0(lane, sb_peer + OFF_BAR + 8 * PF);
      }
    }
    mbar_wait_cluster(bars + 8 * PF);
    wg_wait<0>();
    reg_fence(accg);
    mbar_arrive_if0(lane, bs12 + 8 * (DG + 11), 2);
    TLW(34 + s);
    {
      const uint32_t buf = OFF_W2 + 5 * 24576 + s * PAGE + tid * 16;
#pragma unroll
      for (int e = 0; e < 8; e++) {
        const float a = accg[64 + e], b = accg[72 + e];
        accg[64 + e] = q ? a : b;
        accg[72 + e] = q ? b : a;
      }
#pragma unroll
      for (int m = 0; m < 5; m++) {
        const float* a = accg + 32 + 8 * m;
        asm volatile("st.async.shared::cluster.mbarrier::complete_tx::bytes.v4.b32 [%0], {%1,%2,%3,%4}, [%5];"
                     ::"r"(sb_peer + buf + m * 2048), "r"(pack2(a[0], a[1])), "r"(pack2(a[2], a[3])), "r"(pack2(a[4], a[5])),
                     "r"(pack2(a[6], a[7])), "r"(sb_peer + OFF_BAR + 8 * (RX + s)) : "memory");
      }
      TLW(58 + s);
      mbar_wait(bs12 + 8 * (DG + 11));
      mbar_wait_cluster(bars + 8 * (RX + s));
      TLW(60 + s);
      float4 rx[5];
#pragma unroll
      for (int m = 0; m < 5; m++) rx[m] = lds128(sb + buf + m * 2048);
      const uint32_t stg = rs + w * 2816;
      const uint32_t sa = stg + (lane & 15) * 176 + (lane >> 4) * 16;
#pragma unroll
      for (int ks = 0; ks < 5; ks++) {
        const uint32_t u[4] = {__float_as_uint(rx[ks].x), __float_as_uint(rx[ks].y), __float_as_uint(rx[ks].z), __float_as_uint(rx[ks].w)};
        const float* a = accg + (ks < 4 ? 8 * ks : 72);
        stsm4(sa + ks * 32, pack2(a[0] + bf_lo(u[0]), a[1] + bf_hi(u[0])), pack2(a[2] + bf_lo(u[1]), a[3] + bf_hi(u[1])),
              pack2(a[4] + bf_lo(u[2]), a[5] + bf_hi(u[2])), pack2(a[6] + bf_lo(u[3]), a[7] + bf_hi(u[3])));
      }
      __syncwarp();
#pragma unroll
      for (int m = 0; m < 4; m++) rx[m] = lds128(stg + (4 * m + (lane >> 3)) * 176 + (lane & 7) * 16);
      rx[4] = lds128(stg + (lane >> 1) * 176 + 128 + (lane & 1) * 16);
      __nv_bfloat16* outp = out + (row0 + (lane >> 3)) * 640 + cF + (lane & 7) * 8;
#pragma unroll
      for (int m = 0; m < 4; m++) *reinterpret_cast<float4*>(outp + m * 4 * 640) = rx[m];
      *reinterpret_cast<float4*>(out + (row0 + (lane >> 1)) * 640 + cR + (lane & 1) * 8) = rx[4];
    }
    mbar_arrive_if0(lane, bars + 8 * END, 1);
    TLW(36 + s);
  }
}

typedef CUresult (*EncodeFn)(CUtensorMap*, CUtensorMapDataType, cuuint32_t, void*, const cuuint64_t*, const cuuint64_t*,
                             const cuuint32_t*, const cuuint32_t*, CUtensorMapInterleave, CUtensorMapSwizzle,
                             CUtensorMapL2promotion, CUtensorMapFloatOOBfill);

void make_map(EncodeFn enc, CUtensorMap* tm, const void* base, int rows, int cols, int box_rows, int box_cols, int group, int natom,
              CUtensorMapSwizzle sw) {
  const cuuint64_t dims[3] = {(cuuint64_t)(natom ? group : cols), (cuuint64_t)rows, (cuuint64_t)(cols / group)};
  const cuuint64_t strides[2] = {(cuuint64_t)cols * 2, (cuuint64_t)group * 2};
  const cuuint32_t box[3] = {(cuuint32_t)box_cols, (cuuint32_t)box_rows, (cuuint32_t)natom}, es[3] = {1, 1, 1};
  enc(tm, CU_TENSOR_MAP_DATA_TYPE_BFLOAT16, natom ? 3 : 2, const_cast<void*>(base), dims, strides, box, es,
      CU_TENSOR_MAP_INTERLEAVE_NONE, sw, CU_TENSOR_MAP_L2_PROMOTION_L2_128B, CU_TENSOR_MAP_FLOAT_OOB_FILL_NONE);
}

}

extern "C" void kernel_launch(void* const* d_in, const int* in_sizes, int n_in, void* d_out, int out_size) {
  const __nv_bfloat16* x = (const __nv_bfloat16*)d_in[0];
  const __nv_bfloat16* wqkv = (const __nv_bfloat16*)d_in[1];
  const __nv_bfloat16* wo = (const __nv_bfloat16*)d_in[2];
  const __nv_bfloat16* w1 = (const __nv_bfloat16*)d_in[4];
  const __nv_bfloat16* b1 = (const __nv_bfloat16*)d_in[5];
  const __nv_bfloat16* w2 = (const __nv_bfloat16*)d_in[6];
  const __nv_bfloat16* b2 = (const __nv_bfloat16*)d_in[7];

  void* fn = nullptr;
  cudaDriverEntryPointQueryResult qr;
  cudaGetDriverEntryPoint("cuTensorMapEncodeTiled", &fn, cudaEnableDefault, &qr);
  EncodeFn enc = (EncodeFn)fn;
  const CUtensorMapSwizzle S128 = CU_TENSOR_MAP_SWIZZLE_128B, S64 = CU_TENSOR_MAP_SWIZZLE_64B;
  Maps maps;
  make_map(enc, &maps.m[M_X], x, 2048, 640, 64, 64, 64, 0, S128);
  make_map(enc, &maps.m[M_KVF], wqkv, 640, 1920, 32, 64, 640, 2, S128);
  make_map(enc, &maps.m[M_KVH], wqkv, 640, 1920, 32, 32, 64, 0, S128);
  make_map(enc, &maps.m[M_Q2], wqkv, 640, 1920, 64, 32, 32, 2, S64);
  make_map(enc, &maps.m[M_QR], wqkv, 640, 1920, 64, 16, 64, 0, S64);
  make_map(enc, &maps.m[M_WO2], wo, 640, 640, 80, 32, 32, 2, S64);
  make_map(enc, &maps.m[M_WOR], wo, 640, 640, 80, 16, 64, 0, S64);
  make_map(enc, &maps.m[M_W1], w1, 640, 1536, 64, 64, 64, 3, S128);
  make_map(enc, &maps.m[M_W1R], w1, 640, 1536, 16, 64, 64, 3, S128);
  make_map(enc, &maps.m[M_W2F], w2, 1536, 640, 64, 64, 64, 0, S128);
  make_map(enc, &maps.m[M_W2H], w2, 1536, 640, 64, 32, 64, 0, S128);
  cudaFuncSetAttribute(fused_block_kernel, cudaFuncAttributeMaxDynamicSharedMemorySize, SMEM_BYTES);
  fused_block_kernel<<<128, 384, SMEM_BYTES>>>(maps, x, wqkv, wo, w1, b1, w2, b2, (__nv_bfloat16*)d_out);
}
```

```cpp
#include <cuda_runtime.h>
#include <cuda_bf16.h>
#include <cuda.h>
#include <stdint.h>

namespace {

struct Desc { uint32_t base, off, hi; };
__device__ __forceinline__ Desc operator+(Desc d, uint32_t o) { return Desc{d.base, d.off + o, d.hi}; }
template <int TA, int TB> __device__ __forceinline__ void wgmma_ss_n48(float (&d)[24], Desc a, Desc b, int sc) {
  asm volatile("{.reg .pred p; .reg .b32 t, u; .reg .b64 da, db; setp.ne.b32 p, %30, 0; add.u32 t, %24, %25; mov.b64 da, {t, %26}; add.u32 u, %27, %28; mov.b64 db, {u, %29};"
    "wgmma.mma_async.sync.aligned.m64n48k16.f32.bf16.bf16 {%0,%1,%2,%3,%4,%5,%6,%7,%8,%9,%10,%11,%12,%13,%14,%15,%16,%17,%18,%19,%20,%21,%22,%23}, da, db, p, 1, 1, %31, %32;}"
    : "+f"(d[0]),"+f"(d[1]),"+f"(d[2]),"+f"(d[3]),"+f"(d[4]),"+f"(d[5]),"+f"(d[6]),"+f"(d[7]),"+f"(d[8]),"+f"(d[9]),"+f"(d[10]),"+f"(d[11]),"+f"(d[12]),"+f"(d[13]),"+f"(d[14]),"+f"(d[15]),"+f"(d[16]),"+f"(d[17]),"+f"(d[18]),"+f"(d[19]),"+f"(d[20]),"+f"(d[21]),"+f"(d[22]),"+f"(d[23])
    : "r"(a.base), "r"(a.off), "r"(a.hi), "r"(b.base), "r"(b.off), "r"(b.hi), "r"(sc), "n"(TA), "n"(TB));
}
template <int TA, int TB> __device__ __forceinline__ void wgmma_ss_n80(float (&d)[40], Desc a, Desc b, int sc) {
  asm volatile("{.reg .pred p; .reg .b32 t, u; .reg .b64 da, db; setp.ne.b32 p, %46, 0; add.u32 t, %40, %41; mov.b64 da, {t, %42}; add.u32 u, %43, %44; mov.b64 db, {u, %45};"
    "wgmma.mma_async.sync.aligned.m64n80k16.f32.bf16.bf16 {%0,%1,%2,%3,%4,%5,%6,%7,%8,%9,%10,%11,%12,%13,%14,%15,%16,%17,%18,%19,%20,%21,%22,%23,%24,%25,%26,%27,%28,%29,%30,%31,%32,%33,%34,%35,%36,%37,%38,%39}, da, db, p, 1, 1, %47, %48;}"
    : "+f"(d[0]),"+f"(d[1]),"+f"(d[2]),"+f"(d[3]),"+f"(d[4]),"+f"(d[5]),"+f"(d[6]),"+f"(d[7]),"+f"(d[8]),"+f"(d[9]),"+f"(d[10]),"+f"(d[11]),"+f"(d[12]),"+f"(d[13]),"+f"(d[14]),"+f"(d[15]),"+f"(d[16]),"+f"(d[17]),"+f"(d[18]),"+f"(d[19]),"+f"(d[20]),"+f"(d[21]),"+f"(d[22]),"+f"(d[23]),"+f"(d[24]),"+f"(d[25]),"+f"(d[26]),"+f"(d[27]),"+f"(d[28]),"+f"(d[29]),"+f"(d[30]),"+f"(d[31]),"+f"(d[32]),"+f"(d[33]),"+f"(d[34]),"+f"(d[35]),"+f"(d[36]),"+f"(d[37]),"+f"(d[38]),"+f"(d[39])
    : "r"(a.base), "r"(a.off), "r"(a.hi), "r"(b.base), "r"(b.off), "r"(b.hi), "r"(sc), "n"(TA), "n"(TB));
}
template <int TA, int TB> __device__ __forceinline__ void wgmma_ss_n160(float (&d)[80], Desc a, Desc b, int sc) {
  asm volatile("{.reg .pred p; .reg .b32 t, u; .reg .b64 da, db; setp.ne.b32 p, %86, 0; add.u32 t, %80, %81; mov.b64 da, {t, %82}; add.u32 u, %83, %84; mov.b64 db, {u, %85};"
    "wgmma.mma_async.sync.aligned.m64n160k16.f32.bf16.bf16 {%0,%1,%2,%3,%4,%5,%6,%7,%8,%9,%10,%11,%12,%13,%14,%15,%16,%17,%18,%19,%20,%21,%22,%23,%24,%25,%26,%27,%28,%29,%30,%31,%32,%33,%34,%35,%36,%37,%38,%39,%40,%41,%42,%43,%44,%45,%46,%47,%48,%49,%50,%51,%52,%53,%54,%55,%56,%57,%58,%59,%60,%61,%62,%63,%64,%65,%66,%67,%68,%69,%70,%71,%72,%73,%74,%75,%76,%77,%78,%79}, da, db, p, 1, 1, %87, %88;}"
    : "+f"(d[0]),"+f"(d[1]),"+f"(d[2]),"+f"(d[3]),"+f"(d[4]),"+f"(d[5]),"+f"(d[6]),"+f"(d[7]),"+f"(d[8]),"+f"(d[9]),"+f"(d[10]),"+f"(d[11]),"+f"(d[12]),"+f"(d[13]),"+f"(d[14]),"+f"(d[15]),"+f"(d[16]),"+f"(d[17]),"+f"(d[18]),"+f"(d[19]),"+f"(d[20]),"+f"(d[21]),"+f"(d[22]),"+f"(d[23]),"+f"(d[24]),"+f"(d[25]),"+f"(d[26]),"+f"(d[27]),"+f"(d[28]),"+f"(d[29]),"+f"(d[30]),"+f"(d[31]),"+f"(d[32]),"+f"(d[33]),"+f"(d[34]),"+f"(d[35]),"+f"(d[36]),"+f"(d[37]),"+f"(d[38]),"+f"(d[39]),"+f"(d[40]),"+f"(d[41]),"+f"(d[42]),"+f"(d[43]),"+f"(d[44]),"+f"(d[45]),"+f"(d[46]),"+f"(d[47]),"+f"(d[48]),"+f"(d[49]),"+f"(d[50]),"+f"(d[51]),"+f"(d[52]),"+f"(d[53]),"+f"(d[54]),"+f"(d[55]),"+f"(d[56]),"+f"(d[57]),"+f"(d[58]),"+f"(d[59]),"+f"(d[60]),"+f"(d[61]),"+f"(d[62]),"+f"(d[63]),"+f"(d[64]),"+f"(d[65]),"+f"(d[66]),"+f"(d[67]),"+f"(d[68]),"+f"(d[69]),"+f"(d[70]),"+f"(d[71]),"+f"(d[72]),"+f"(d[73]),"+f"(d[74]),"+f"(d[75]),"+f"(d[76]),"+f"(d[77]),"+f"(d[78]),"+f"(d[79])
    : "r"(a.base), "r"(a.off), "r"(a.hi), "r"(b.base), "r"(b.off), "r"(b.hi), "r"(sc), "n"(TA), "n"(TB));
}
template <int TA, int TB> __device__ __forceinline__ void wgmma_ss_n192(float (&d)[96], Desc a, Desc b, int sc) {
  asm volatile("{.reg .pred p; .reg .b32 t, u; .reg .b64 da, db; setp.ne.b32 p, %102, 0; add.u32 t, %96, %97; mov.b64 da, {t, %98}; add.u32 u, %99, %100; mov.b64 db, {u, %101};"
    "wgmma.mma_async.sync.aligned.m64n192k16.f32.bf16.bf16 {%0,%1,%2,%3,%4,%5,%6,%7,%8,%9,%10,%11,%12,%13,%14,%15,%16,%17,%18,%19,%20,%21,%22,%23,%24,%25,%26,%27,%28,%29,%30,%31,%32,%33,%34,%35,%36,%37,%38,%39,%40,%41,%42,%43,%44,%45,%46,%47,%48,%49,%50,%51,%52,%53,%54,%55,%56,%57,%58,%59,%60,%61,%62,%63,%64,%65,%66,%67,%68,%69,%70,%71,%72,%73,%74,%75,%76,%77,%78,%79,%80,%81,%82,%83,%84,%85,%86,%87,%88,%89,%90,%91,%92,%93,%94,%95}, da, db, p, 1, 1, %103, %104;}"
    : "+f"(d[0]),"+f"(d[1]),"+f"(d[2]),"+f"(d[3]),"+f"(d[4]),"+f"(d[5]),"+f"(d[6]),"+f"(d[7]),"+f"(d[8]),"+f"(d[9]),"+f"(d[10]),"+f"(d[11]),"+f"(d[12]),"+f"(d[13]),"+f"(d[14]),"+f"(d[15]),"+f"(d[16]),"+f"(d[17]),"+f"(d[18]),"+f"(d[19]),"+f"(d[20]),"+f"(d[21]),"+f"(d[22]),"+f"(d[23]),"+f"(d[24]),"+f"(d[25]),"+f"(d[26]),"+f"(d[27]),"+f"(d[28]),"+f"(d[29]),"+f"(d[30]),"+f"(d[31]),"+f"(d[32]),"+f"(d[33]),"+f"(d[34]),"+f"(d[35]),"+f"(d[36]),"+f"(d[37]),"+f"(d[38]),"+f"(d[39]),"+f"(d[40]),"+f"(d[41]),"+f"(d[42]),"+f"(d[43]),"+f"(d[44]),"+f"(d[45]),"+f"(d[46]),"+f"(d[47]),"+f"(d[48]),"+f"(d[49]),"+f"(d[50]),"+f"(d[51]),"+f"(d[52]),"+f"(d[53]),"+f"(d[54]),"+f"(d[55]),"+f"(d[56]),"+f"(d[57]),"+f"(d[58]),"+f"(d[59]),"+f"(d[60]),"+f"(d[61]),"+f"(d[62]),"+f"(d[63]),"+f"(d[64]),"+f"(d[65]),"+f"(d[66]),"+f"(d[67]),"+f"(d[68]),"+f"(d[69]),"+f"(d[70]),"+f"(d[71]),"+f"(d[72]),"+f"(d[73]),"+f"(d[74]),"+f"(d[75]),"+f"(d[76]),"+f"(d[77]),"+f"(d[78]),"+f"(d[79]),"+f"(d[80]),"+f"(d[81]),"+f"(d[82]),"+f"(d[83]),"+f"(d[84]),"+f"(d[85]),"+f"(d[86]),"+f"(d[87]),"+f"(d[88]),"+f"(d[89]),"+f"(d[90]),"+f"(d[91]),"+f"(d[92]),"+f"(d[93]),"+f"(d[94]),"+f"(d[95])
    : "r"(a.base), "r"(a.off), "r"(a.hi), "r"(b.base), "r"(b.off), "r"(b.hi), "r"(sc), "n"(TA), "n"(TB));
}
template <int TB> __device__ __forceinline__ void wgmma_rs_n80(float (&d)[40], uint32_t a0, uint32_t a1, uint32_t a2, uint32_t a3, Desc b, int sc) {
  asm volatile("{.reg .pred p; .reg .b32 u; .reg .b64 db; setp.ne.b32 p, %47, 0; add.u32 u, %44, %45; mov.b64 db, {u, %46};"
    "wgmma.mma_async.sync.aligned.m64n80k16.f32.bf16.bf16 {%0,%1,%2,%3,%4,%5,%6,%7,%8,%9,%10,%11,%12,%13,%14,%15,%16,%17,%18,%19,%20,%21,%22,%23,%24,%25,%26,%27,%28,%29,%30,%31,%32,%33,%34,%35,%36,%37,%38,%39}, {%40,%41,%42,%43}, db, p, 1, 1, %48;}"
    : "+f"(d[0]),"+f"(d[1]),"+f"(d[2]),"+f"(d[3]),"+f"(d[4]),"+f"(d[5]),"+f"(d[6]),"+f"(d[7]),"+f"(d[8]),"+f"(d[9]),"+f"(d[10]),"+f"(d[11]),"+f"(d[12]),"+f"(d[13]),"+f"(d[14]),"+f"(d[15]),"+f"(d[16]),"+f"(d[17]),"+f"(d[18]),"+f"(d[19]),"+f"(d[20]),"+f"(d[21]),"+f"(d[22]),"+f"(d[23]),"+f"(d[24]),"+f"(d[25]),"+f"(d[26]),"+f"(d[27]),"+f"(d[28]),"+f"(d[29]),"+f"(d[30]),"+f"(d[31]),"+f"(d[32]),"+f"(d[33]),"+f"(d[34]),"+f"(d[35]),"+f"(d[36]),"+f"(d[37]),"+f"(d[38]),"+f"(d[39])
    : "r"(a0), "r"(a1), "r"(a2), "r"(a3), "r"(b.base), "r"(b.off), "r"(b.hi), "r"(sc), "n"(TB));
}
template <int TB> __device__ __forceinline__ void wgmma_rs_n96(float (&d)[48], uint32_t a0, uint32_t a1, uint32_t a2, uint32_t a3, Desc b, int sc) {
  asm volatile("{.reg .pred p; .reg .b32 u; .reg .b64 db; setp.ne.b32 p, %55, 0; add.u32 u, %52, %53; mov.b64 db, {u, %54};"
    "wgmma.mma_async.sync.aligned.m64n96k16.f32.bf16.bf16 {%0,%1,%2,%3,%4,%5,%6,%7,%8,%9,%10,%11,%12,%13,%14,%15,%16,%17,%18,%19,%20,%21,%22,%23,%24,%25,%26,%27,%28,%29,%30,%31,%32,%33,%34,%35,%36,%37,%38,%39,%40,%41,%42,%43,%44,%45,%46,%47}, {%48,%49,%50,%51}, db, p, 1, 1, %56;}"
    : "+f"(d[0]),"+f"(d[1]),"+f"(d[2]),"+f"(d[3]),"+f"(d[4]),"+f"(d[5]),"+f"(d[6]),"+f"(d[7]),"+f"(d[8]),"+f"(d[9]),"+f"(d[10]),"+f"(d[11]),"+f"(d[12]),"+f"(d[13]),"+f"(d[14]),"+f"(d[15]),"+f"(d[16]),"+f"(d[17]),"+f"(d[18]),"+f"(d[19]),"+f"(d[20]),"+f"(d[21]),"+f"(d[22]),"+f"(d[23]),"+f"(d[24]),"+f"(d[25]),"+f"(d[26]),"+f"(d[27]),"+f"(d[28]),"+f"(d[29]),"+f"(d[30]),"+f"(d[31]),"+f"(d[32]),"+f"(d[33]),"+f"(d[34]),"+f"(d[35]),"+f"(d[36]),"+f"(d[37]),"+f"(d[38]),"+f"(d[39]),"+f"(d[40]),"+f"(d[41]),"+f"(d[42]),"+f"(d[43]),"+f"(d[44]),"+f"(d[45]),"+f"(d[46]),"+f"(d[47])
    : "r"(a0), "r"(a1), "r"(a2), "r"(a3), "r"(b.base), "r"(b.off), "r"(b.hi), "r"(sc), "n"(TB));
}
template <int TB> __device__ __forceinline__ void wgmma_rs_n160(float (&d)[80], uint32_t a0, uint32_t a1, uint32_t a2, uint32_t a3, Desc b, int sc) {
  asm volatile("{.reg .pred p; .reg .b32 u; .reg .b64 db; setp.ne.b32 p, %87, 0; add.u32 u, %84, %85; mov.b64 db, {u, %86};"
    "wgmma.mma_async.sync.aligned.m64n160k16.f32.bf16.bf16 {%0,%1,%2,%3,%4,%5,%6,%7,%8,%9,%10,%11,%12,%13,%14,%15,%16,%17,%18,%19,%20,%21,%22,%23,%24,%25,%26,%27,%28,%29,%30,%31,%32,%33,%34,%35,%36,%37,%38,%39,%40,%41,%42,%43,%44,%45,%46,%47,%48,%49,%50,%51,%52,%53,%54,%55,%56,%57,%58,%59,%60,%61,%62,%63,%64,%65,%66,%67,%68,%69,%70,%71,%72,%73,%74,%75,%76,%77,%78,%79}, {%80,%81,%82,%83}, db, p, 1, 1, %88;}"
    : "+f"(d[0]),"+f"(d[1]),"+f"(d[2]),"+f"(d[3]),"+f"(d[4]),"+f"(d[5]),"+f"(d[6]),"+f"(d[7]),"+f"(d[8]),"+f"(d[9]),"+f"(d[10]),"+f"(d[11]),"+f"(d[12]),"+f"(d[13]),"+f"(d[14]),"+f"(d[15]),"+f"(d[16]),"+f"(d[17]),"+f"(d[18]),"+f"(d[19]),"+f"(d[20]),"+f"(d[21]),"+f"(d[22]),"+f"(d[23]),"+f"(d[24]),"+f"(d[25]),"+f"(d[26]),"+f"(d[27]),"+f"(d[28]),"+f"(d[29]),"+f"(d[30]),"+f"(d[31]),"+f"(d[32]),"+f"(d[33]),"+f"(d[34]),"+f"(d[35]),"+f"(d[36]),"+f"(d[37]),"+f"(d[38]),"+f"(d[39]),"+f"(d[40]),"+f"(d[41]),"+f"(d[42]),"+f"(d[43]),"+f"(d[44]),"+f"(d[45]),"+f"(d[46]),"+f"(d[47]),"+f"(d[48]),"+f"(d[49]),"+f"(d[50]),"+f"(d[51]),"+f"(d[52]),"+f"(d[53]),"+f"(d[54]),"+f"(d[55]),"+f"(d[56]),"+f"(d[57]),"+f"(d[58]),"+f"(d[59]),"+f"(d[60]),"+f"(d[61]),"+f"(d[62]),"+f"(d[63]),"+f"(d[64]),"+f"(d[65]),"+f"(d[66]),"+f"(d[67]),"+f"(d[68]),"+f"(d[69]),"+f"(d[70]),"+f"(d[71]),"+f"(d[72]),"+f"(d[73]),"+f"(d[74]),"+f"(d[75]),"+f"(d[76]),"+f"(d[77]),"+f"(d[78]),"+f"(d[79])
    : "r"(a0), "r"(a1), "r"(a2), "r"(a3), "r"(b.base), "r"(b.off), "r"(b.hi), "r"(sc), "n"(TB));
}
template <int TB> __device__ __forceinline__ void wgmma_rs_n192(float (&d)[96], uint32_t a0, uint32_t a1, uint32_t a2, uint32_t a3, Desc b, int sc) {
  asm volatile("{.reg .pred p; .reg .b32 u; .reg .b64 db; setp.ne.b32 p, %103, 0; add.u32 u, %100, %101; mov.b64 db, {u, %102};"
    "wgmma.mma_async.sync.aligned.m64n192k16.f32.bf16.bf16 {%0,%1,%2,%3,%4,%5,%6,%7,%8,%9,%10,%11,%12,%13,%14,%15,%16,%17,%18,%19,%20,%21,%22,%23,%24,%25,%26,%27,%28,%29,%30,%31,%32,%33,%34,%35,%36,%37,%38,%39,%40,%41,%42,%43,%44,%45,%46,%47,%48,%49,%50,%51,%52,%53,%54,%55,%56,%57,%58,%59,%60,%61,%62,%63,%64,%65,%66,%67,%68,%69,%70,%71,%72,%73,%74,%75,%76,%77,%78,%79,%80,%81,%82,%83,%84,%85,%86,%87,%88,%89,%90,%91,%92,%93,%94,%95}, {%96,%97,%98,%99}, db, p, 1, 1, %104;}"
    : "+f"(d[0]),"+f"(d[1]),"+f"(d[2]),"+f"(d[3]),"+f"(d[4]),"+f"(d[5]),"+f"(d[6]),"+f"(d[7]),"+f"(d[8]),"+f"(d[9]),"+f"(d[10]),"+f"(d[11]),"+f"(d[12]),"+f"(d[13]),"+f"(d[14]),"+f"(d[15]),"+f"(d[16]),"+f"(d[17]),"+f"(d[18]),"+f"(d[19]),"+f"(d[20]),"+f"(d[21]),"+f"(d[22]),"+f"(d[23]),"+f"(d[24]),"+f"(d[25]),"+f"(d[26]),"+f"(d[27]),"+f"(d[28]),"+f"(d[29]),"+f"(d[30]),"+f"(d[31]),"+f"(d[32]),"+f"(d[33]),"+f"(d[34]),"+f"(d[35]),"+f"(d[36]),"+f"(d[37]),"+f"(d[38]),"+f"(d[39]),"+f"(d[40]),"+f"(d[41]),"+f"(d[42]),"+f"(d[43]),"+f"(d[44]),"+f"(d[45]),"+f"(d[46]),"+f"(d[47]),"+f"(d[48]),"+f"(d[49]),"+f"(d[50]),"+f"(d[51]),"+f"(d[52]),"+f"(d[53]),"+f"(d[54]),"+f"(d[55]),"+f"(d[56]),"+f"(d[57]),"+f"(d[58]),"+f"(d[59]),"+f"(d[60]),"+f"(d[61]),"+f"(d[62]),"+f"(d[63]),"+f"(d[64]),"+f"(d[65]),"+f"(d[66]),"+f"(d[67]),"+f"(d[68]),"+f"(d[69]),"+f"(d[70]),"+f"(d[71]),"+f"(d[72]),"+f"(d[73]),"+f"(d[74]),"+f"(d[75]),"+f"(d[76]),"+f"(d[77]),"+f"(d[78]),"+f"(d[79]),"+f"(d[80]),"+f"(d[81]),"+f"(d[82]),"+f"(d[83]),"+f"(d[84]),"+f"(d[85]),"+f"(d[86]),"+f"(d[87]),"+f"(d[88]),"+f"(d[89]),"+f"(d[90]),"+f"(d[91]),"+f"(d[92]),"+f"(d[93]),"+f"(d[94]),"+f"(d[95])
    : "r"(a0), "r"(a1), "r"(a2), "r"(a3), "r"(b.base), "r"(b.off), "r"(b.hi), "r"(sc), "n"(TB));
}
template <int N, int TA, int TB> __device__ __forceinline__ void wgmma_ss(float (&d)[N / 2], Desc a, Desc b, int sc) {
  if constexpr (N == 48) wgmma_ss_n48<TA, TB>(d, a, b, sc);
  else if constexpr (N == 80) wgmma_ss_n80<TA, TB>(d, a, b, sc);
  else if constexpr (N == 160) wgmma_ss_n160<TA, TB>(d, a, b, sc);
  else if constexpr (N == 192) wgmma_ss_n192<TA, TB>(d, a, b, sc);
}
template <int N, int TB> __device__ __forceinline__ void wgmma_rs(float (&d)[N / 2], uint32_t a0, uint32_t a1, uint32_t a2, uint32_t a3, Desc b, int sc) {
  if constexpr (N == 80) wgmma_rs_n80<TB>(d, a0, a1, a2, a3, b, sc);
  else if constexpr (N == 96) wgmma_rs_n96<TB>(d, a0, a1, a2, a3, b, sc);
  else if constexpr (N == 160) wgmma_rs_n160<TB>(d, a0, a1, a2, a3, b, sc);
  else if constexpr (N == 192) wgmma_rs_n192<TB>(d, a0, a1, a2, a3, b, sc);
}

constexpr uint32_t SMEM_BASE = 1024;
constexpr uint32_t PAGE = 10240;
constexpr uint32_t OFF_RING = 16 * PAGE;
constexpr uint32_t OFF_KVB = 49152;
constexpr uint32_t OFF_R1 = 35840;
constexpr uint32_t OFF_MISC = 22 * PAGE;
constexpr uint32_t OFF_W2 = OFF_MISC - 6 * 24576;
constexpr uint32_t OFF_BAR = OFF_MISC;
constexpr uint32_t OFF_EPOCH = OFF_MISC + 1856;
constexpr uint32_t OFF_LN1 = OFF_MISC + 1920;
constexpr uint32_t OFF_RK1 = OFF_MISC + 2944;
constexpr uint32_t OFF_B2 = OFF_RK1 + 3072;
constexpr uint32_t OFF_SCR = OFF_MISC + 6784;
constexpr uint32_t SMEM_BYTES = OFF_MISC + 7040;

enum : int {
  G2 = 0, PX = 1, PF = 2, RX = 3, RXK = 5,
  FX = 6, FKV = 19, FQ = 39, FWO = 49, FW1 = 57, FW2 = 65,
  AO = 77, AH = 93, AF = 109,
  DKV = 133, DQ = 153, DW = 163, DF = 179, DG = 195,
  SO = 219, SFB = 221,
  SIDE = 223, SIDE2 = 224, KVB = 225, END = 226, RKV = 227, OM = 228
};

__device__ uint32_t g_epoch;
__device__ uint4 g_ln1[2048];
__device__ uint4 g_cs[4 * 1728];
__device__ uint4 g_hstat[32 * 8 * 64];
__device__ __align__(128) float2 g_kv1[8 * 16 * 16 * 64];
__device__ __align__(128) uint2 g_kv2[8 * 960];
__device__ __align__(128) uint32_t g_flag[3 * 32 * 32];
__device__ __align__(128) uint8_t g_act[3 * 32 * 8 * 24576];

struct Maps { CUtensorMap m[11]; };
enum : int { M_X, M_KVF, M_KVH, M_Q2, M_QR, M_WO2, M_WOR, M_W1, M_W1R, M_W2F, M_W2H };

#define TL(id)
#define TLW(id)
#define TL0(id)

constexpr int SPIN_LIMIT = 1 << 19;

__device__ __forceinline__ bool elect_one() {
  uint32_t p;
  asm volatile("{.reg .pred P; elect.sync _|P, 0xffffffff; selp.u32 %0,1,0,P;}" : "=r"(p));
  return p;
}
__device__ __forceinline__ void mbar_wait(uint32_t bar) {
  asm volatile("{.reg .pred p;\nW: mbarrier.try_wait.parity.shared::cta.b64 p, [%0], 0;\n@!p bra W;}" ::"r"(bar) : "memory");
}
__device__ __forceinline__ void mbar_wait_cluster(uint32_t bar) {
  asm volatile("{.reg .pred p;\nW: mbarrier.try_wait.parity.acquire.cluster.shared::cta.b64 p, [%0], 0;\n@!p bra W;}" ::"r"(bar) : "memory");
}
__device__ __forceinline__ void mbar_wait_wd(uint32_t bar) {
  asm volatile("{.reg .pred p; .reg .u32 n; mov.u32 n, 0;\n"
               "W: mbarrier.try_wait.parity.shared::cta.b64 p, [%0], 0;\n"
               "@p bra D; add.u32 n, n, 1; setp.gt.u32 p, n, %1; @p trap; bra W;\n"
               "D: }" ::"r"(bar), "n"(SPIN_LIMIT) : "memory");
}
__device__ __forceinline__ void mbar_arrive(uint32_t bar, uint32_t n) {
  asm volatile("mbarrier.arrive.shared::cta.b64 _, [%0], %1;" ::"r"(bar), "r"(n) : "memory");
}
__device__ __forceinline__ void mbar_arrive_if0(int z, uint32_t bar, uint32_t n) {
  asm volatile("{.reg .pred p; setp.eq.s32 p, %2, 0; @p mbarrier.arrive.shared::cta.b64 _, [%0], %1;}" ::"r"(bar), "r"(n), "r"(z) : "memory");
}
__device__ __forceinline__ void mbar_arrive_remote_if0(int z, uint32_t bar) {
  asm volatile("{.reg .pred p; setp.eq.s32 p, %1, 0; @p mbarrier.arrive.shared::cluster.b64 _, [%0];}" ::"r"(bar), "r"(z) : "memory");
}
__device__ __forceinline__ void mbar_expect(uint32_t bar, uint32_t bytes) {
  asm volatile("mbarrier.arrive.expect_tx.shared::cta.b64 _, [%0], %1;" ::"r"(bar), "r"(bytes) : "memory");
  asm volatile("mbarrier.arrive.shared::cta.b64 _, [%0], 7;" ::"r"(bar) : "memory");
}
__device__ __forceinline__ void tma2d(uint32_t dst, const CUtensorMap* tm, uint32_t bar, int c0, int c1) {
  asm volatile("cp.async.bulk.tensor.2d.shared::cluster.global.mbarrier::complete_tx::bytes [%0],[%1,{%3,%4}],[%2];"
               ::"r"(dst), "l"(tm), "r"(bar), "r"(c0), "r"(c1) : "memory");
}
__device__ __forceinline__ void tma3d(uint32_t dst, const CUtensorMap* tm, uint32_t bar, int c0, int c1, int c2) {
  asm volatile("cp.async.bulk.tensor.3d.shared::cluster.global.mbarrier::complete_tx::bytes [%0],[%1,{%3,%4,%5}],[%2];"
               ::"r"(dst), "l"(tm), "r"(bar), "r"(c0), "r"(c1), "r"(c2) : "memory");
}
__device__ __forceinline__ void tma2d_pair(uint32_t dst, const CUtensorMap* tm, uint32_t bar, int c0, int c1) {
  asm volatile("cp.async.bulk.tensor.2d.shared::cluster.global.mbarrier::complete_tx::bytes.multicast::cluster [%0],[%1,{%3,%4}],[%2],%5;"
               ::"r"(dst), "l"(tm), "r"(bar), "r"(c0), "r"(c1), "h"((uint16_t)3) : "memory");
}
__device__ __forceinline__ void bulk_load(uint32_t dst, const void* src, uint32_t bytes, uint32_t bar) {
  asm volatile("cp.async.bulk.shared::cluster.global.mbarrier::complete_tx::bytes [%0],[%1],%2,[%3];"
               ::"r"(dst), "l"(src), "r"(bytes), "r"(bar) : "memory");
}
__device__ __forceinline__ void bulk_store(void* dst, uint32_t src, uint32_t bytes) {
  asm volatile("cp.async.bulk.global.shared::cta.bulk_group [%0],[%1],%2;" ::"l"(dst), "r"(src), "r"(bytes) : "memory");
}
__device__ __forceinline__ void bulk_commit_wait() {
  asm volatile("cp.async.bulk.commit_group;" ::: "memory");
  asm volatile("cp.async.bulk.wait_group 0;" ::: "memory");
}
__device__ __forceinline__ void l2_prefetch(const void* src, uint32_t bytes) {
  asm volatile("cp.async.bulk.prefetch.L2.global [%0], %1;" ::"l"(src), "r"(bytes) : "memory");
}
__device__ __forceinline__ void fence_gpu() { asm volatile("fence.acq_rel.gpu;" ::: "memory"); }
__device__ __forceinline__ void fence_async_smem() { asm volatile("fence.proxy.async.shared::cta;" ::: "memory"); }
__device__ __forceinline__ void fence_async_global() { asm volatile("fence.proxy.async.global;" ::: "memory"); }
__device__ __forceinline__ void st_flag(uint32_t* p, uint32_t v) {
  asm volatile("st.relaxed.gpu.global.u32 [%0], %1;" ::"l"(p), "r"(v) : "memory");
}
__device__ __forceinline__ uint32_t ld_acq(const uint32_t* p) {
  uint32_t v;
  asm volatile("ld.acquire.gpu.global.u32 %0, [%1];" : "=r"(v) : "l"(p) : "memory");
  return v;
}
__device__ __forceinline__ void wg_fence() { asm volatile("wgmma.fence.sync.aligned;" ::: "memory"); }
__device__ __forceinline__ void wg_commit() { asm volatile("wgmma.commit_group.sync.aligned;" ::: "memory"); }
template <int N> __device__ __forceinline__ void wg_wait() { asm volatile("wgmma.wait_group.sync.aligned %0;" ::"n"(N) : "memory"); }
template <int N> __device__ __forceinline__ void reg_fence(float (&a)[N]) {
#pragma unroll
  for (int i = 0; i < N; i++) asm volatile("" : "+f"(a[i])::"memory");
}
template <int ID, int N> __device__ __forceinline__ void named_bar() { asm volatile("bar.sync %0, %1;" ::"n"(ID), "n"(N) : "memory"); }
template <int N> __device__ __forceinline__ void reg_fence(uint32_t (&a)[N]) {
#pragma unroll
  for (int i = 0; i < N; i++) asm volatile("" : "+r"(a[i])::"memory");
}
__device__ __forceinline__ Desc mkdesc(uint32_t dyn, uint32_t off, uint32_t lbo, uint32_t sbo, uint32_t swz) {
  return Desc{dyn, ((off + SMEM_BASE) >> 4) + ((lbo >> 4) << 16), (sbo >> 4) | (swz << 30)};
}
__device__ __forceinline__ uint32_t pack2(float lo, float hi) {
  uint32_t r;
  asm("cvt.rn.bf16x2.f32 %0, %1, %2;" : "=r"(r) : "f"(hi), "f"(lo));
  return r;
}
__device__ __forceinline__ float bf_lo(uint32_t v) { return __uint_as_float(v << 16); }
__device__ __forceinline__ float bf_hi(uint32_t v) { return __uint_as_float(v & 0xffff0000u); }
__device__ __forceinline__ void stsm4(uint32_t addr, uint32_t a, uint32_t b, uint32_t c, uint32_t d) {
  asm volatile("stmatrix.sync.aligned.m8n8.x4.shared.b16 [%0], {%1,%2,%3,%4};" ::"r"(addr), "r"(a), "r"(b), "r"(c), "r"(d) : "memory");
}
__device__ __forceinline__ void ldsm4(uint32_t addr, uint32_t* r) {
  asm volatile("ldmatrix.sync.aligned.m8n8.x4.shared.b16 {%0,%1,%2,%3}, [%4];" : "=r"(r[0]), "=r"(r[1]), "=r"(r[2]), "=r"(r[3]) : "r"(addr) : "memory");
}
__device__ __forceinline__ float2 lds64(uint32_t a) {
  float2 v;
  asm volatile("ld.shared.v2.f32 {%0,%1}, [%2];" : "=f"(v.x), "=f"(v.y) : "r"(a) : "memory");
  return v;
}
__device__ __forceinline__ float4 lds128(uint32_t a) {
  float4 v;
  asm volatile("ld.shared.v4.f32 {%0,%1,%2,%3}, [%4];" : "=f"(v.x), "=f"(v.y), "=f"(v.z), "=f"(v.w) : "r"(a) : "memory");
  return v;
}
__device__ __forceinline__ uint32_t lds32(uint32_t a) {
  uint32_t v;
  asm volatile("ld.shared.u32 %0, [%1];" : "=r"(v) : "r"(a) : "memory");
  return v;
}
__device__ __forceinline__ void sts32(uint32_t a, uint32_t v) { asm volatile("st.shared.u32 [%0], %1;" ::"r"(a), "r"(v) : "memory"); }
__device__ __forceinline__ void sts64(uint32_t a, uint32_t x, uint32_t y) {
  asm volatile("st.shared.v2.u32 [%0], {%1,%2};" ::"r"(a), "r"(x), "r"(y) : "memory");
}
__device__ __forceinline__ void sts128(uint32_t a, uint32_t x, uint32_t y, uint32_t z, uint32_t w) {
  asm volatile("st.shared.v4.u32 [%0], {%1,%2,%3,%4};" ::"r"(a), "r"(x), "r"(y), "r"(z), "r"(w) : "memory");
}
__device__ __forceinline__ float ex2(float x) {
  float r;
  asm("ex2.approx.ftz.f32 %0, %1;" : "=f"(r) : "f"(x));
  return r;
}
__device__ __forceinline__ float rcp(float x) {
  float r;
  asm("rcp.approx.ftz.f32 %0, %1;" : "=f"(r) : "f"(x));
  return r;
}
constexpr float LOG2E = 1.4426950408889634f;
__device__ __forceinline__ float phi(float z, float a, float a2) {
  float r = ex2(z * a2) + 1e-6f;
  asm("{.reg .pred p; setp.gt.f32 p, %1, 0f00000000; @p fma.rn.f32 %0, %1, %2, 0f3F800008;}" : "+f"(r) : "f"(z), "f"(a));
  return r;
}
__device__ __forceinline__ float gelu(float z, const float3& k) {
  float th;
  asm("tanh.approx.f32 %0, %1;" : "=f"(th) : "f"(z * fmaf(z * z, k.y, k.x)));
  const float hy = z * k.z;
  return fmaf(hy, th, hy);
}
__device__ __forceinline__ uint32_t rk1_frag(float m, float d, int c) {
  const uint32_t hi = pack2(m, d), lo = pack2(m - bf_lo(hi), d - bf_hi(hi));
  return c == 0 ? __byte_perm(hi, 0, 0x1010) : c == 1 ? __byte_perm(lo, hi, 0x7610) : c == 2 ? lo >> 16 : 0u;
}
__device__ __forceinline__ void rk1_store(uint32_t addr, float2 cs, uint32_t bb) {
  const uint32_t hi = pack2(cs.x, cs.y), lo = pack2(cs.x - bf_lo(hi), cs.y - bf_hi(hi));
  sts128(addr, __byte_perm(hi, lo, 0x5410), __byte_perm(hi, bb, 0x5410), bb & 0xffffu, 0);
  sts128(addr + 16, __byte_perm(hi, lo, 0x7632), __byte_perm(hi, bb, 0x7632), bb >> 16, 0);
}
constexpr uint32_t ONES = 0x3F803F80u;
__device__ __forceinline__ void ll_store(uint4* p, float a, float b, uint32_t tag) {
  asm volatile("st.relaxed.gpu.global.v4.u32 [%0], {%1,%2,%3,%2};" ::"l"(p), "r"(__float_as_uint(a)), "r"(tag), "r"(__float_as_uint(b)) : "memory");
}
__device__ __forceinline__ uint4 ll_load(const void* p) {
  uint4 v;
  asm volatile("ld.relaxed.gpu.global.v4.u32 {%0,%1,%2,%3}, [%4];" : "=r"(v.x), "=r"(v.y), "=r"(v.z), "=r"(v.w) : "l"(p) : "memory");
  return v;
}
template <int N>
__device__ __forceinline__ void ll_wait(uint4 (&v)[N], const uint4* p, int stride, uint32_t tag) {
  uint32_t bad;
  int it = 0;
  do {
    bad = 0;
#pragma unroll
    for (int m = 0; m < N; m++) v[m] = ll_load(p + m * stride);
#pragma unroll
    for (int m = 0; m < N; m++) bad |= (v[m].y ^ tag) | (v[m].w ^ tag);
  } while (bad && ++it < SPIN_LIMIT);
}
__device__ __forceinline__ float2 ll_sum4(const uint4* p, uint32_t tag) {
  uint4 v[4];
  ll_wait(v, p, 1728, tag);
  return make_float2((__uint_as_float(v[0].x) + __uint_as_float(v[1].x)) + (__uint_as_float(v[2].x) + __uint_as_float(v[3].x)),
                     (__uint_as_float(v[0].z) + __uint_as_float(v[1].z)) + (__uint_as_float(v[2].z) + __uint_as_float(v[3].z)));
}
__device__ __forceinline__ void poll_flag(const uint32_t* f, int bit, uint32_t& mask, uint32_t epoch) {
  while (!(mask >> bit & 1)) {
    mask = __ballot_sync(0xffffffffu, ld_acq(f) == epoch);
    fence_async_global();
  }
}
template <bool PHI>
__device__ __forceinline__ void ln_pair(const float* z, const float (&a)[2], const float (&a2)[2], uint32_t* o) {
#pragma unroll
  for (int e = 0; e < 4; e++) {
    const int hh = e & 1;
    o[e] = PHI ? pack2(phi(z[2 * e], a[hh], a2[hh]), phi(z[2 * e + 1], a[hh], a2[hh])) : pack2(z[2 * e] * a[hh], z[2 * e + 1] * a[hh]);
  }
}

__global__ void __cluster_dims__(2, 1, 1) __launch_bounds__(384, 1)
fused_block_kernel(const __grid_constant__ Maps maps, const __nv_bfloat16* __restrict__ x, const __nv_bfloat16* __restrict__ wqkv,
                   const __nv_bfloat16* __restrict__ wo, const __nv_bfloat16* __restrict__ w1,
                   const __nv_bfloat16* __restrict__ b1, const __nv_bfloat16* __restrict__ w2,
                   const __nv_bfloat16* __restrict__ b2, __nv_bfloat16* __restrict__ out) {
  extern __shared__ __align__(1024) uint8_t smem_raw[];
  const uint32_t sb = (uint32_t)__cvta_generic_to_shared(smem_raw);
  const uint32_t bars = sb + OFF_BAR;
  const int warp = __shfl_sync(0xffffffffu, threadIdx.x >> 5, 0);
  const int lane = threadIdx.x & 31;

  const int cl = blockIdx.x >> 1, q = blockIdx.x & 1;
  const int u7 = ((cl - 36) * 37) >> 8;
  const int oct = cl < 4 ? 0 : cl < 36 ? 1 + 2 * ((cl - 4) & 7) : 2 + 2 * (cl - 36 - 7 * u7);
  const int u4 = cl < 4 ? cl : cl < 36 ? (cl - 4) >> 3 : u7;
  const int i = 2 * (oct & 7) + (u4 >> 1), p = 2 * (oct >> 3) + (u4 & 1);
  const int j = 2 * p + q;
  auto col_f = [](int jj) { return 160 * (jj >> 1) + 16 * (jj & 2) + 64 * (jj & 1); };
  auto col_r = [](int jj) { return 160 * (jj >> 1) + 128 - 64 * (jj & 2) + 16 * (jj & 1); };
  const int cF = col_f(j), cR = col_r(j), role = q ^ (p & 1);

  auto load_kv = [&](int s, int slot) {
    const uint32_t dst = sb + OFF_RING + slot * 12288, bar = bars + 8 * (FKV + s);
    mbar_expect(bar, 10240);
    tma3d(dst, &maps.m[M_KVF], bar, cF, 32 * s, 1);
    tma2d(dst + 8192, &maps.m[M_KVH], bar, 640 + 640 * role + cR - 16 * q, 32 * s);
  };
  auto load_x = [&](int c, int b, int slot) {
    mbar_expect(bars + 8 * (FX + b), 16384);
    tma2d(sb + slot * 16384, &maps.m[M_X], bars + 8 * (FX + b), 64 * c, 128 * i);
    tma2d(sb + slot * 16384 + 8192, &maps.m[M_X], bars + 8 * (FX + b), 64 * c, 128 * i + 64);
  };
  auto load_x_pair = [&](int c) {
    mbar_expect(bars + 8 * (FX + c), 16384);
    tma2d_pair(sb + c * 16384 + q * 8192, &maps.m[M_X], bars + 8 * (FX + c), 64 * c, 128 * i + 64 * q);
  };

  auto bar_init = [&](int n) { asm volatile("mbarrier.init.shared::cta.b64 [%0], 8;" ::"r"(bars + 8 * n) : "memory"); };
  if (elect_one()) {
    if (warp == 8) {
      bar_init(FX);
      bar_init(FKV);
      bar_init(FKV + 1);
      load_x(0, 0, 0);
      load_kv(0, 0);
      load_kv(1, 1);
    } else {
      asm volatile("prefetch.tensormap [%0];" ::"l"(&maps.m[warp < 8 ? warp : warp - 1]) : "memory");
      if (warp > 8) {
        const int n0 = warp == 9 ? 0 : 6 * warp - 53;
#pragma unroll
        for (int n = 0; n < 6; n++) bar_init(n0 + n);
        bar_init(FKV + warp - 7);
      }
    }
    asm volatile("fence.mbarrier_init.release.cluster;" ::: "memory");
  }
  __syncwarp();
  asm volatile("barrier.cluster.arrive.relaxed.aligned;" ::: "memory");

  if (warp >= 8) {
    asm volatile("setmaxnreg.dec.sync.aligned.u32 88;");
    if (warp == 8) {
      asm volatile("barrier.cluster.wait.aligned;" ::: "memory");
      if (elect_one()) {
        load_x_pair(1);
        load_kv(2, 2);
        load_kv(3, 3);
        load_x_pair(2);
        load_kv(4, 4);
        load_x_pair(3);
        load_x_pair(4);
      }
      TL(40);
      mbar_wait(bars + 8 * G2);
#pragma unroll 1
      for (int s = 5, slot = 0; s < 20; s++) {
        mbar_wait(bars + 8 * (DKV + s - 5));
        if (elect_one()) {
          load_kv(s, slot);
          if (s < 10) load_x_pair(s);
        }
        slot = slot == 4 ? 0 : slot + 1;
      }
#pragma unroll 1
      for (int t = 0, slot = 0; t < 10; t++) {
        mbar_wait(bars + 8 * (DKV + 15 + t));
        if (elect_one()) {
          const uint32_t dst = sb + OFF_RING + slot * 12288, bar = bars + 8 * (FQ + t);
          const int k0 = 64 * (t < 7 ? t + 3 : t - 7);
          mbar_expect(bar, 10240);
          tma3d(dst, &maps.m[M_Q2], bar, 0, k0, 5 * p + 3 * q);
          tma2d(dst + 8192, &maps.m[M_QR], bar, 80 * j + 64 - 64 * q, k0);
          if (t >= 6 && t < 9) load_x(t - 6, t + 4, t - 2);
        }
        slot = slot == 4 ? 0 : slot + 1;
      }
#pragma unroll 1
      for (int n = 0; n < 32; n += 4) {
        mbar_wait(bars + 8 * (DQ + ((0x99876665u >> n) & 15)));
        if (n >= 8) mbar_wait(bars + 8 * (FWO + ((0x71654320u >> (n - 8)) & 7)));
        const int t = (0x71654320u >> n) & 7, k0 = 80 * (t == 0 ? j : t - (t <= j));
        if (elect_one()) {
          const uint32_t dst = sb + 10 * PAGE + (t < 2 ? t ^ 1 : t) * 15360, bar = bars + 8 * (FWO + t);
          mbar_expect(bar, 12800);
          tma3d(dst, &maps.m[M_WO2], bar, 0, k0, cF >> 5);
          tma2d(dst + 10240, &maps.m[M_WOR], bar, cR, k0);
        }
      }
#pragma unroll 1
      for (int t = 0; t < 8; t++) {
        const uint32_t wb = bars + 8 * (t == 0 ? FWO - 7 : t < 5 ? DW + 2 * t - 1 : DF + t - 5);
        const int jj = t == 0 ? j : t - (t <= j);
        mbar_wait(wb);
        mbar_wait(wb + 64);
        if (elect_one()) {
          const uint32_t dst = sb + (7 + 3 * (t < 5 ? t : t - 5)) * PAGE, bar = bars + 8 * (FW1 + t);
          mbar_expect(bar, 30720);
          tma3d(dst, &maps.m[M_W1], bar, 0, col_f(jj), 3 * j);
          tma3d(dst + 24576, &maps.m[M_W1R], bar, 0, col_r(jj), 3 * j);
        }
      }
#pragma unroll 1
      for (int t = 0; t < 12; t++) {
        const int t6 = t < 6 ? t : t - 6;
        const uint32_t wb = bars + 8 * (t < 6 ? DF + ((0x776544 >> (4 * t)) & 7) : DG + t6);
        const int uu = (0xA95024 >> (2 * t)) & 3, n = (0x924900 >> (2 * t)) & 3;
        const int k0 = 192 * (t < 3 ? j : 2 * (n + (n >= p)) + q) + 64 * uu;
        const uint32_t dst = sb + OFF_W2 + ((0x321045 >> (4 * t6)) & 7) * 24576, bar = bars + 8 * (FW2 + t);
        mbar_wait(wb);
        mbar_wait(wb + (t < 6 ? 64 : 96));
        if (elect_one()) {
          mbar_expect(bar, 20480);
          tma2d(dst, &maps.m[M_W2F], bar, cF, k0);
          tma2d(dst + 8192, &maps.m[M_W2F], bar, cF + 64 - 128 * q, k0);
          tma2d(dst + 16384, &maps.m[M_W2H], bar, cR - 16 * q, k0);
        }
      }
    } else {
      uint32_t epoch;
      asm volatile("ld.relaxed.gpu.global.u32 %0, [%1];" : "=r"(epoch) : "l"(&g_epoch) : "memory");
      epoch += 1;
      const int unit = i * 8 + j, hw = warp - 9, ht = hw * 32 + lane;
      asm volatile("barrier.cluster.wait.aligned;" ::: "memory");
      if (lane == 0) {
        mbar_expect(bars + 8 * (RX + hw), hw == 2 ? 8192 : 10240);
        sts32(sb + OFF_EPOCH, epoch);
      }
      const int part = unit & 3, cg = unit >> 2;
      auto colsum = [&](const __nv_bfloat16* wm, int ld, uint4* dst) {
        const int r4 = lane >> 3, v8 = lane & 7;
        const __nv_bfloat16* wp = wm + (part * 160 + 4 * hw + r4) * ld + 64 * cg + 8 * v8;
        uint4 v[14];
#pragma unroll
        for (int m = 0; m < 14; m++) {
          v[m] = make_uint4(0, 0, 0, 0);
          if (m < 13 || hw == 0)
            asm volatile("ld.global.nc.v4.u32 {%0,%1,%2,%3}, [%4];" : "=r"(v[m].x), "=r"(v[m].y), "=r"(v[m].z), "=r"(v[m].w) : "l"(wp));
          wp += 12 * ld;
        }
        float d[8];
#pragma unroll
        for (int e = 0; e < 8; e++) d[e] = 0.f;
#pragma unroll
        for (int m = 0; m < 14; m++) {
          d[0] += bf_lo(v[m].x); d[1] += bf_hi(v[m].x); d[2] += bf_lo(v[m].y); d[3] += bf_hi(v[m].y);
          d[4] += bf_lo(v[m].z); d[5] += bf_hi(v[m].z); d[6] += bf_lo(v[m].w); d[7] += bf_hi(v[m].w);
        }
#pragma unroll 1
        for (int o = 8; o < 32; o <<= 1) {
#pragma unroll
          for (int e = 0; e < 8; e++) d[e] += __shfl_xor_sync(0xffffffffu, d[e], o);
        }
        if (r4 & 2) { d[0] = d[4]; d[1] = d[5]; d[2] = d[6]; d[3] = d[7]; }
        if (r4 & 1) { d[0] = d[2]; d[1] = d[3]; }
        const uint32_t red = sb + OFF_SCR + lane * 8;
#pragma unroll 1
        for (int h = 0; h < 2; h++) {
          if (hw == h) sts64(red, __float_as_uint(d[0]), __float_as_uint(d[1]));
          named_bar<2, 96>();
          if (hw == h + 1) {
            const float2 a = lds64(red);
            d[0] += a.x;
            d[1] += a.y;
          }
        }
        if (hw == 2) ll_store(dst + part * 1728 + 32 * cg + 4 * v8 + r4, d[0], d[1], epoch);
      };
      mbar_wait(bars + 8 * (part < 2 ? G2 : part == 2 ? FKV : FKV + 4));
      mbar_wait(bars + 8 * G2);
#pragma unroll 1
      for (int pass = 0; pass < 2; pass++) {
        if (cg < (pass ? 24 : 30)) colsum(pass ? w1 : wqkv, pass ? 1536 : 1920, g_cs + 960 * pass);
        if (pass) break;
        if (hw == 2) {
          TL(8);
          mbar_wait(bars + 8 * (FX + 9));
          if (lane < 2) {
            const uint32_t nb = lane ? 15360 : 6400;
            l2_prefetch(reinterpret_cast<const uint8_t*>(lane ? w2 : wo) + blockIdx.x * nb, nb);
          }
        } else {
          const int r = 16 * j + 8 * hw + (lane >> 2);
          const uint32_t xa = sb + r * 128 + ((lane & 3) + (lane & 4)) * 16;
          float sm = 0.f, sq = 0.f;
#pragma unroll 1
          for (int ch = 0; ch < 10; ch++) {
            mbar_wait(bars + 8 * (FX + ch));
            const float4 u0 = lds128(xa + ch * 16384), u1 = lds128((xa ^ 64) + ch * 16384);
            const float uu[8] = {u0.x, u0.y, u0.z, u0.w, u1.x, u1.y, u1.z, u1.w};
            float s2 = 0.f, q2 = 0.f;
#pragma unroll
            for (int e = 0; e < 8; e++) {
              const float a = bf_lo(__float_as_uint(uu[e])), b = bf_hi(__float_as_uint(uu[e]));
              sm += a;
              s2 += b;
              sq = fmaf(a, a, sq);
              q2 = fmaf(b, b, q2);
            }
            sm += s2;
            sq += q2;
          }
#pragma unroll
          for (int o = 1; o < 4; o <<= 1) {
            sm += __shfl_xor_sync(0xffffffffu, sm, o);
            sq += __shfl_xor_sync(0xffffffffu, sq, o);
          }
          const float mean = sm * (1.f / 640.f);
          const float rstd = rsqrtf(fmaxf(fmaf(-mean, mean, sq * (1.f / 640.f)), 0.f) + 1e-5f);
          if ((lane & 3) == 0) ll_store(g_ln1 + 128 * i + r, rstd, -mean, epoch);
          if (hw == 0) TL(10);
        }
#pragma unroll 1
        for (int n = 2 * (95 - ht); n < 240; n += 192) {
          int col;
          if (n < 160) col = n + (n < 64 ? 640 + cF : n < 128 ? 1216 + cF : 512 + 640 * role + cR - 16 * q);
          else col = 80 * j + n - 160 + (q ? (n < 224 ? 16 : -64) : 0);
          rk1_store(sb + OFF_RK1 + n * 16, ll_sum4(g_cs + (col >> 1), epoch), 0);
        }
        if (hw < 2) {
          uint4 v[2];
          ll_wait(v, g_ln1 + 128 * i + ht, 64, epoch);
          sts64(sb + OFF_LN1 + ht * 8, v[0].x, v[0].z);
          sts64(sb + OFF_LN1 + ht * 8 + 512, v[1].x, v[1].z);
        }
        fence_async_smem();
        __syncwarp();
        mbar_arrive_if0(lane, bars + 8 * SIDE, hw == 2 ? 2 : 3);
        if (hw == 0) TL(11);
        mbar_wait_wd(bars + 8 * SIDE);
      }
      {
        mbar_wait_wd(bars + 8 * (hw == 2 ? DQ : RKV));
        if (hw == 2) {
#pragma unroll 1
          for (int m = 0; m < 30; m++) sts128(sb + OFF_KVB + (m * 32 + lane) * 16, 0, 0, 0, 0);
        } else if (ht < 60) {
          const float2* src = g_kv1 + (j * 16 + i) * 1024 + ht;
          const uint32_t tag = epoch & 15;
          float sa, sc;
          uint32_t bad;
          int it = 0;
          do {
            uint32_t a[16], b[16];
#pragma unroll
            for (int m = 0; m < 16; m++)
              asm volatile("ld.relaxed.gpu.global.v2.u32 {%0,%1}, [%2];" : "=r"(a[m]), "=r"(b[m]) : "l"(src + m * 64) : "memory");
            sa = sc = 0.f;
            bad = 0;
#pragma unroll
            for (int m = 0; m < 16; m++) {
              bad |= (a[m] ^ tag) | (b[m] ^ tag);
              sa += __uint_as_float(a[m]);
              sc += __uint_as_float(b[m]);
            }
          } while ((bad & 15) && ++it < SPIN_LIMIT);
          asm volatile("st.relaxed.gpu.global.v2.u32 [%0], {%1,%2};" ::"l"(g_kv2 + j * 960 + i * 60 + ht), "r"(pack2(sa, sc)), "r"(epoch) : "memory");
        }
        if (hw == 0) TL(5);
        named_bar<2, 96>();
        {
          uint4 v[5];
          ll_wait(v, reinterpret_cast<const uint4*>(g_kv2 + j * 960) + ht, 96, epoch);
          if (hw == 0) TL(6);
          const int d0 = ht / 6, part = ht - 6 * d0;
#pragma unroll
          for (int m = 0; m < 5; m++) {
            const int d = d0 + 16 * m, head = (d * 205) >> 12, n = 20 * head + 4 * part;
            const uint32_t a = sb + OFF_KVB + d * 16;
            const uint32_t z = head & 1 ? v[m].x << 16 : v[m].x & 0xffffu;
            if (part < 5) sts64(a + (n >> 3) * 1280 + (n & 7) * 2, v[m].x, v[m].z);
            else sts128(a + (10 + (head >> 1)) * 1280, z, z, z, z);
          }
        }
        fence_async_smem();
        __syncwarp();
        mbar_arrive_if0(lane, bars + 8 * KVB, hw == 2 ? 2 : 3);
        if (hw == 0) TL(7);
      }

      if (hw == 2) {
        mbar_wait_wd(bars + 8 * (DQ + 9));
#pragma unroll 1
        for (int n = lane; n < 96; n += 32) {
          const uint32_t bb = *reinterpret_cast<const uint32_t*>(b1 + 192 * j + 2 * n);
          if (n < 40) {
            const uint32_t b = *reinterpret_cast<const uint32_t*>(b2 + (n < 32 ? cF + 2 * n : cR + 2 * n - 64));
            sts64(sb + OFF_B2 + n * 8, b << 16, b & 0xffff0000u);
          }
          rk1_store(sb + OFF_RK1 + n * 32, ll_sum4(g_cs + 960 + 96 * j + n, epoch), bb);
        }
        fence_async_smem();
        __syncwarp();
        mbar_arrive_if0(lane, bars + 8 * SIDE2, 8);
        TL(18);
#pragma unroll 1
        for (int s = 0; s < 2; s++) {
          uint8_t* dst = g_act + ((64 + 2 * i + s) * 8 + j) * 24576;
          mbar_wait_wd(bars + 8 * (AF + 12 * s + 1));
          if (lane == 0) bulk_store(dst + 8192, sb + s * OFF_R1 + 8192, 8192);
          __syncwarp();
          mbar_wait_wd(bars + 8 * (AF + 12 * s + 2));
          if (lane == 0) {
            bulk_store(dst + 16384, sb + s * OFF_R1 + 16384, 8192);
            bulk_commit_wait();
            mbar_arrive(bars + 8 * (SFB + s), 8);
            fence_gpu();
            st_flag(g_flag + (64 + 2 * i + s) * 32 + 8 + j, epoch);
          }
          __syncwarp();
          TL(50 + s);
        }
        mbar_wait_wd(bars + 8 * END);
        if (blockIdx.x == 0 && lane == 0) g_epoch = epoch;
      } else {
        const int s = hw;
#pragma unroll 1
        for (int ph = 0; ph < 3; ph++) {
          uint32_t ab = bars + 8 * (ph < 2 ? AO + 16 * ph + 8 * s : AF + 12 * s);
          const uint32_t bytes = ph < 2 ? 10240 : 8192, base = sb + (ph ? s * OFF_R1 : 0);
          uint8_t* gb = g_act + (ph * 32 + 2 * i + s) * 8 * 24576;
          uint32_t* fl = g_flag + (ph * 32 + 2 * i + s) * 32;
          mbar_wait(ab);
          if (ph == 0 && s == 1) mbar_wait(bars + 8 * SO);
          if (elect_one()) {
            bulk_store(gb + j * 24576, sb + s * (ph ? OFF_R1 : PAGE), bytes);
            bulk_commit_wait();
            if (ph == 0) mbar_arrive(bars + 8 * (SO + s), 8);
            fence_gpu();
            st_flag(fl + j, epoch);
          }
          __syncwarp();
          TL(44 + 2 * ph + s);
          uint32_t slots;
          uint64_t waits;
          if (ph == 0) {
            slots = s ? 02165432u : 00165432u;
            waits = s ? 011060504030201ull : 000101010101010ull;
            if (s == 0) mbar_wait(bars + 8 * (SO + 1));
          } else if (ph == 1) {
            slots = 01021021u;
            waits = 024232221201717ull + (s ? 010101010100000ull : 0);
          } else {
            slots = 0321032103u;
            waits = 0474645444342414027ull + (s ? 0141414141414141410ull : 0);
            ab += 16;
          }
          uint32_t mask = 0;
#pragma unroll 1
          for (int r = 0; r < (ph < 2 ? 7 : 9); r++) {
            int cc = r + (r >= j), bit = cc;
            uint32_t off = 0;
            if (ph == 2) {
              const int uu = (r * 11) >> 5, n = r - 3 * uu;
              cc = 2 * (n + (n >= p)) + q;
              bit = cc + (uu ? 8 : 0);
              off = uu * 8192;
              if (r == 2) mbar_wait(bars + 8 * (SFB + s));
            }
            ab += 8;
            mbar_wait(bars + 8 * (DW + ((uint32_t)waits & 63)));
            poll_flag(fl + lane, bit, mask, epoch);
            if (r == 0) TL(52 + 2 * ph + s);
            if (elect_one()) {
              mbar_expect(ab, bytes);
              bulk_load(base + (slots & 7) * bytes, gb + cc * 24576 + off, bytes, ab);
            }
            slots >>= 3;
            waits >>= 6;
          }
        }
      }
    }
  } else {
    asm volatile("setmaxnreg.inc.sync.aligned.u32 208;");
    asm volatile("barrier.cluster.wait.aligned;" ::: "memory");
    if (elect_one()) {
#pragma unroll
      for (int n = 0; n < 26; n++) bar_init(24 + 26 * warp + n);
      mbar_arrive(bars + 8 * G2, 1);
    }
    __syncwarp();
    mbar_wait(bars + 8 * G2);
    const int s = warp >> 2, w = warp & 3, tid = threadIdx.x & 127, c = lane & 3, g = lane >> 2;
    uint32_t sb_peer;
    asm volatile("mapa.shared::cluster.u32 %0, %1, %2;" : "=r"(sb_peer) : "r"(sb), "r"(q ^ 1));
    const int row0 = 128 * i + 64 * s + 16 * w;
    const uint32_t bs8 = bars + 64 * s, bs12 = bars + 96 * s;
    uint32_t pq[20], hp[20];
    uint32_t epoch;
    {
      float acc[80];
      const Desc dx = mkdesc(s * 512, 0, 16, 1024, 1);
#pragma unroll
      for (int st = 0; st < 20; st++) {
        if ((st & 1) == 0) mbar_wait(bars + 8 * (FX + (st >> 1)));
        mbar_wait(bars + 8 * (FKV + st));
        const Desc da = dx + (st >> 1) * 1024 + (st & 1) * 4, db = mkdesc(0, OFF_RING + (st % 5) * 12288, 4096, 1024, 1);
        wg_fence();
        wgmma_ss<160, 0, 1>(acc, da, db, st != 0);
        wgmma_ss<160, 0, 1>(acc, da + 2, db + 128, 1);
        wg_commit();
        if (st == 0) TL0(0);
        if (st == 18) {
          const uint32_t xa = sb + (64 * s + 16 * w + (lane & 15)) * 128;
#pragma unroll
          for (int ks = 0; ks < 5; ks++) {
            const int col = ks < 4 ? cF + 16 * ks : cR;
            ldsm4(xa + (col >> 6) * 16384 + (((((col & 63) >> 3) + (lane >> 4)) ^ (lane & 7)) << 4), hp + 4 * ks);
          }
          reg_fence(hp);
          mbar_arrive_remote_if0(lane, sb_peer + OFF_BAR + 8 * PX);
        }
        if (st > 0) {
          wg_wait<1>();
          mbar_arrive_if0(lane, bars + 8 * (DKV + st - 1), 1);
        }
      }
      TL0(12);
      float accq[40];
      auto q_step = [&](int t) {
        if (t >= 7) mbar_wait(bars + 8 * (FX + 3 + t));
        mbar_wait(bars + 8 * (FQ + t));
        const Desc da = dx + (t < 7 ? t + 3 : t - 3) * 1024, db = mkdesc(0, OFF_RING + (t % 5) * 12288, 4096, 512, 2);
        wg_fence();
#pragma unroll
        for (int ks = 0; ks < 4; ks++) wgmma_ss<80, 0, 1>(accq, da + 2 * ks, db + 64 * ks, 1);
        wg_commit();
      };
      mbar_wait(bars + 8 * SIDE);
      epoch = lds32(sb + OFF_EPOCH);
      float a1[2], a2[2];
      uint32_t rk[2];
#pragma unroll
      for (int r = 0; r < 2; r++) {
        const float2 st = lds64(sb + OFF_LN1 + (64 * s + 16 * w + g + 8 * r) * 8);
        a1[r] = st.x;
        a2[r] = st.x * LOG2E;
        rk[r] = rk1_frag(st.y, 0.f, c);
      }
      wg_fence();
      wgmma_rs<160, 0>(acc, rk[0], rk[1], 0, 0, mkdesc(0, OFF_RK1, 0, 128, 0), 1);
      wg_commit();
      wgmma_rs<80, 0>(accq, rk[0], rk[1], 0, 0, mkdesc(0, OFF_RK1 + 2560, 0, 128, 0), 0);
      q_step(0);
      const int hi = lane >> 4;
      const uint32_t rowoff = sb + (64 * s + 16 * w + (lane & 15)) * 16;
      const uint32_t remoff = sb_peer + (64 * s + 16 * w) * 16 + lane * 4;
      auto put_remote = [&](const uint32_t* r, uint32_t a) {
#pragma unroll
        for (int e = 0; e < 4; e++)
          asm volatile("st.async.shared::cluster.mbarrier::complete_tx::bytes.b32 [%0], %1, [%2];"
                       ::"r"(a + (e >> 1) * 2048 + (e & 1) * 128), "r"(r[e]), "r"(sb_peer + OFF_BAR + 8 * RXK) : "memory");
      };
      const int mF = 2 * (p & 1) - q, g0 = 2 * mF + hi;
      const uint32_t ka = rowoff + g0 * 2048;
      mbar_wait(bars + 8 * (DKV + 17));
      mbar_wait_cluster(bars + 8 * PX);
      wg_wait<1>();
      reg_fence(acc);
      mbar_arrive_if0(lane, bars + 8 * (DKV + 19), 1);
      TL0(1);
      uint32_t r[4], r2[4];
      if (role == 0) {
        ln_pair<true>(acc + 64, a1, a2, r);
        ln_pair<true>(acc + 72, a1, a2, r2);
        put_remote(r, remoff + (q ? 0 : 6 * 2048));
        put_remote(r2, remoff + (q ? 2 * 2048 : 8 * 2048));
      } else {
        ln_pair<false>(acc + 64, a1, a2, r);
        ln_pair<false>(acc + 72, a1, a2, r2);
        const uint32_t a = rowoff + (hi + (q ? 17 : 10)) * 2048;
        stsm4(a, r[0], r[1], r[2], r[3]);
        stsm4(a + 4096, r2[0], r2[1], r2[2], r2[3]);
      }
      q_step(1);
#pragma unroll
      for (int n = 0; n < 4; n++) {
        const int P = n == 0 ? 0 : n == 1 ? 3 : n - 1;
        ln_pair<true>(acc + 8 * P, a1, a2, r);
        ln_pair<false>(acc + 32 + 8 * P, a1, a2, r2);
        if (n < 2 && mF == (n ? 2 : -1)) {
          put_remote(r, remoff + (n ? 0 : 8 * 2048));
          put_remote(r2, remoff + (n ? 10 * 2048 : 19 * 2048));
        } else {
          stsm4(ka + P * 4096, r[0], r[1], r[2], r[3]);
          stsm4(ka + P * 4096 + (g0 + 2 * P > 4 ? 11 * 2048 : 10 * 2048), r2[0], r2[1], r2[2], r2[3]);
        }
        if (n == 0) {
          wg_wait<1>();
          mbar_arrive_if0(lane, bars + 8 * DQ, 1);
        }
        if (n == 1) q_step(2);
        if (n == 2) {
          wg_wait<1>();
          mbar_arrive_if0(lane, bars + 8 * (DQ + 1), 1);
        }
      }
      sts128(rowoff + 15 * 2048, ONES, ONES, ONES, ONES);
      TL0(2);
      mbar_wait_cluster(bars + 8 * RXK);
      fence_async_smem();
      named_bar<1, 256>();
      TL0(3);
      float kv[24];
      {
        const Desc da = mkdesc(s * 640, 0, 128, 2048, 0), db = da + 1280;
        wg_fence();
#pragma unroll
        for (int kk = 0; kk < 8; kk++) wgmma_ss<48, 1, 1>(kv, da + 16 * kk, db + 16 * kk, kk != 0);
        wg_commit();
      }
      wg_wait<1>();
      mbar_arrive_if0(lane, bars + 8 * (DQ + 2), 1);
      q_step(3);
      {
        const uint32_t tag = epoch & 15;
        const uint8_t* gp[2];
        int eb[2], zo[2];
#pragma unroll
        for (int hh = 0; hh < 2; hh++) {
          const int r = 16 * w + g + 8 * hh, d = 40 * s + r, own = (d * 205) >> 10;
          eb[hh] = c - 4 * s - (r < 20 ? 0 : r < 40 ? 10 : 99);
          zo[hh] = c < 2 && r < 40 ? 10 + c - eb[hh] : -1;
          gp[hh] = reinterpret_cast<const uint8_t*>(g_kv1) + (((j * 16 + own) * 16 + i) * 64 + (d - 5 * own) * 12 + eb[hh]) * 8;
        }
        wg_wait<1>();
        reg_fence(kv);
        TL0(4);
#pragma unroll
        for (int hh = 0; hh < 2; hh++) {
#pragma unroll
          for (int tt = 0; tt < 7; tt++) {
            const float v0 = tt < 6 ? kv[4 * tt + 2 * hh] : s ? kv[2 * hh] : kv[20 + 2 * hh];
            const float v1 = tt < 6 ? kv[4 * tt + 2 * hh + 1] : v0;
            asm volatile("{.reg .pred p; .reg .b32 a, b; setp.lt.u32 p, %3, %4; lop3.b32 a, %1, %5, 15, 0xD8; lop3.b32 b, %2, %5, 15, 0xD8;"
                         "@p st.relaxed.gpu.global.v2.u32 [%0], {a, b};}"
                         ::"l"(tt < 6 ? gp[hh] + 32 * tt : gp[hh] + 8 * zo[hh]), "r"(__float_as_uint(v0)), "r"(__float_as_uint(v1)),
                         "r"(tt < 6 ? eb[hh] + 4 * tt : zo[hh]), "r"(tt < 6 ? 10 : 64), "r"(tag) : "memory");
          }
        }
      }
      mbar_arrive_if0(lane, bars + 8 * RKV, 1);
      TL0(9);
#pragma unroll
      for (int t = 4; t < 10; t++) {
        q_step(t);
        wg_wait<1>();
        mbar_arrive_if0(lane, bars + 8 * (DQ + t - 1), 1);
      }
      wg_wait<0>();
      reg_fence(accq);
      mbar_arrive_if0(lane, bars + 8 * (DQ + 9), 1);
      TL0(13);
#pragma unroll
      for (int P = 0; P < 5; P++) ln_pair<true>(accq + 8 * P, a1, a2, pq + 4 * P);
      reg_fence(pq);
      TL0(14);
    }
    const uint32_t rs = sb + s * OFF_R1;
    const uint32_t stoff = (lane >> 4) * 1024 + (16 * w + (lane & 15)) * 16;
    const Desc drs = mkdesc(s * (OFF_R1 / 16), 0, 1024, 128, 0);
    float accg[80];
    {
      {
        float o[48];
        wg_fence();
        mbar_wait(bars + 8 * (s ? OM : KVB));
        TL0(15);
#pragma unroll
        for (int ks = 0; ks < 5; ks++)
          wgmma_rs<96, 1>(o, pq[4 * ks], pq[4 * ks + 1], pq[4 * ks + 2], pq[4 * ks + 3], mkdesc(ks < 4 ? 16 * q : -64 * q, OFF_KVB + 256 * ks, 128, 1280, 0), ks != 0);
        wg_commit();
        mbar_arrive_if0(lane | s, bars + 8 * OM, 2);
        wg_wait<0>();
        reg_fence(o);
        float inv[2][4];
#pragma unroll
        for (int hh = 0; hh < 2; hh++)
#pragma unroll
          for (int h = 0; h < 4; h++) inv[hh][h] = rcp(o[40 + 4 * (h >> 1) + 2 * hh + (h & 1)] + 1e-6f);
        uint32_t r[4];
#pragma unroll
        for (int t = 0; t < 10; t++) {
#pragma unroll
          for (int hh = 0; hh < 2; hh++) {
            const float f = t == 2 ? (c < 2 ? inv[hh][0] : inv[hh][1]) : t == 7 ? (c < 2 ? inv[hh][2] : inv[hh][3]) : inv[hh][(8 * t) / 20];
            r[2 * (t & 1) + hh] = pack2(o[4 * t + 2 * hh] * f, o[4 * t + 2 * hh + 1] * f);
          }
          if (t & 1) stsm4(sb + s * PAGE + stoff + (t >> 1) * 2048, r[0], r[1], r[2], r[3]);
        }
        fence_async_smem();
        __syncwarp();
        mbar_arrive_if0(lane, bs8 + 8 * AO, 2);
        TLW(16 + s);
      }
      float acc[40];
#pragma unroll
      for (int r = 0; r < 20; r++) { acc[2 * r] = bf_lo(hp[r]); acc[2 * r + 1] = bf_hi(hp[r]); }
      reg_fence(acc);
#pragma unroll
      for (int t = 0; t < 8; t++) {
        mbar_wait(bars + 8 * (FWO + t));
        mbar_wait(bs8 + 8 * (AO + t));
        if (t == 1) TLW(20 + s);
        const Desc da = mkdesc(t == 0 ? s * 640 : t == 7 ? s * 1280 : 0, (t == 0 || t == 7 ? 0 : t < 6 ? t + 1 : 1) * PAGE, 1024, 128, 0);
        const Desc db = mkdesc(0, 10 * PAGE + (t < 2 ? t ^ 1 : t) * 15360, 5120, 512, 2);
        wg_fence();
#pragma unroll
        for (int ks = 0; ks < 5; ks++) wgmma_ss<80, 0, 1>(acc, da + 128 * ks, db + 64 * ks, 1);
        wg_commit();
        if (t == 0) wg_wait<0>();
        else if (t > 1) wg_wait<1>();
        if (t != 1) mbar_arrive_if0(lane, bs8 + 8 * (DW + (t ? t - 1 : 0)), 2);
      }
      wg_wait<0>();
      reg_fence(acc);
      mbar_arrive_if0(lane, bs8 + 8 * (DW + 7), 2);
      TLW(22 + s);
#pragma unroll
      for (int r = 0; r < 20; r++) hp[r] = pack2(acc[2 * r], acc[2 * r + 1]);
      mbar_wait(bs8 + 8 * (DW + 7));
#pragma unroll
      for (int ks = 0; ks < 5; ks++)
        stsm4(rs + stoff + ks * 2048, hp[4 * ks], hp[4 * ks + 1], hp[4 * ks + 2], hp[4 * ks + 3]);
      fence_async_smem();
      __syncwarp();
      mbar_arrive_if0(lane, bs8 + 8 * AH, 2);
      reg_fence(hp);
      TLW(24 + s);
    }
    float accf[96];
    uint4 hs[4];
    const uint4* hsp = g_hstat + ((2 * i + s) * 8 + 2 * c) * 64 + 16 * w + g;
    uint32_t rk[2];
    float3 gk[2];
#pragma unroll
    for (int t = 0; t < 8; t++) {
      mbar_wait(bars + 8 * (FW1 + t));
      mbar_wait(bs8 + 8 * (AH + t));
      if (t == 1) TLW(26 + s);
      const Desc da = drs + (t % 3) * (PAGE / 16), db = mkdesc(0, (7 + 3 * (t % 5)) * PAGE, 8192, 1024, 1);
      wg_fence();
#pragma unroll
      for (int ks = 0; ks < 4; ks++) wgmma_ss<192, 0, 1>(accf, da + 128 * ks, db + 128 * ks, (t | ks) != 0);
      wgmma_ss<192, 0, 1>(accf, da + 512, mkdesc(0, (7 + 3 * (t % 5)) * PAGE + 24576, 2048, 1024, 1), 1);
      if (t == 7) wgmma_rs<192, 0>(accf, rk[0], rk[1], 0, 0, mkdesc(0, OFF_RK1, 0, 128, 0), 1);
      wg_commit();
      if (t == 0) {
        float sm[2] = {0.f, 0.f}, sq[2] = {0.f, 0.f};
        mbar_wait(bars + 8 * SIDE2);
#pragma unroll
        for (int m = 0; m < 10; m++) {
          const float2 b = lds64(sb + OFF_B2 + (8 * m + 2 * c) * 4);
#pragma unroll
          for (int hh = 0; hh < 2; hh++) {
            const float h0 = bf_lo(hp[2 * m + hh]), h1 = bf_hi(hp[2 * m + hh]);
            sm[hh] += h0 + h1;
            sq[hh] = fmaf(h0, h0, fmaf(h1, h1, sq[hh]));
            const float v0 = b.x + h0, v1 = b.y + h1;
            const int e = 4 * m + 2 * hh;
            if (m < 8) { accg[e] = v0; accg[e + 1] = v1; accg[32 + e] = 0.f; accg[33 + e] = 0.f; }
            else { accg[e + 32] = q ? 0.f : v0; accg[e + 33] = q ? 0.f : v1; accg[e + 40] = q ? v0 : 0.f; accg[e + 41] = q ? v1 : 0.f; }
          }
        }
        reg_fence(accg);
#pragma unroll
        for (int o = 1; o < 4; o <<= 1) {
#pragma unroll
          for (int hh = 0; hh < 2; hh++) {
            sm[hh] += __shfl_xor_sync(0xffffffffu, sm[hh], o);
            sq[hh] += __shfl_xor_sync(0xffffffffu, sq[hh], o);
          }
        }
        if (c < 2) ll_store(g_hstat + ((2 * i + s) * 8 + j) * 64 + 16 * w + g + 8 * c, c ? sm[1] : sm[0], c ? sq[1] : sq[0], epoch);
        wg_wait<0>();
      } else if (t > 1) wg_wait<1>();
      if (t != 1) mbar_arrive_if0(lane, bs8 + 8 * (DF + (t ? t - 1 : 0)), 2);
      if (t == 4) {
#pragma unroll
        for (int m = 0; m < 4; m++) hs[m] = ll_load(hsp + (m >> 1) * 64 + 8 * (m & 1));
      }
      if (t == 6) {
        while (((hs[0].y ^ epoch) | (hs[0].w ^ epoch) | (hs[1].y ^ epoch) | (hs[1].w ^ epoch) | (hs[2].y ^ epoch) | (hs[2].w ^ epoch) |
                (hs[3].y ^ epoch) | (hs[3].w ^ epoch)) != 0) {
#pragma unroll
          for (int m = 0; m < 4; m++) hs[m] = ll_load(hsp + (m >> 1) * 64 + 8 * (m & 1));
        }
        __syncwarp();
#pragma unroll
        for (int hh = 0; hh < 2; hh++) {
          float sm = __uint_as_float(hs[hh].x) + __uint_as_float(hs[2 + hh].x), sq = __uint_as_float(hs[hh].z) + __uint_as_float(hs[2 + hh].z);
#pragma unroll
          for (int o = 1; o < 4; o <<= 1) {
            sm += __shfl_xor_sync(0xffffffffu, sm, o);
            sq += __shfl_xor_sync(0xffffffffu, sq, o);
          }
          const float mean = sm * (1.f / 640.f), var = fmaxf(fmaf(-mean, mean, sq * (1.f / 640.f)), 0.f) + 1e-5f;
          const float a = rsqrtf(var);
          rk[hh] = rk1_frag(-mean, var * a, c);
          gk[hh] = make_float3(0.7978845608028654f * a, 0.7978845608028654f * 0.044715f * a * a * a, 0.5f * a);
        }
      }
    }
    wg_wait<0>();
    reg_fence(accf);
    mbar_arrive_if0(lane, bs8 + 8 * (DF + 7), 2);
    TLW(28 + s);
    auto g_step = [&](int t, int slot) {
      mbar_wait(bars + 8 * (FW2 + t));
      mbar_wait(bs12 + 8 * (AF + t));
      if (t == 3) TLW(32 + s);
      const Desc da = mkdesc(drs.base + (t & 3) * 512, 0, 1024, 128, 0), db = mkdesc(slot * 1536, OFF_W2, 8192, 1024, 1);
      wg_fence();
#pragma unroll
      for (int ks = 0; ks < 4; ks++) wgmma_ss<160, 0, 1>(accg, da + 128 * ks, db + 128 * ks, 1);
      wg_commit();
    };
#pragma unroll 1
    for (int t = 0; t < 3; t++) {
      uint32_t r[16];
#pragma unroll
      for (int e = 0; e < 16; e++) r[e] = pack2(gelu(accf[2 * e], gk[e & 1]), gelu(accf[2 * e + 1], gk[e & 1]));
      mbar_wait(bs8 + 8 * (DF + 7));
#pragma unroll
      for (int n = 0; n < 4; n++) stsm4(rs + stoff + t * 8192 + n * 2048, r[4 * n], r[4 * n + 1], r[4 * n + 2], r[4 * n + 3]);
      fence_async_smem();
      __syncwarp();
      mbar_arrive_if0(lane, bs12 + 8 * (AF + t), 2);
#pragma unroll
      for (int e = 0; e < 64; e++) accf[e] = accf[e + 32];
      g_step(t, (0x045 >> (4 * t)) & 7);
      wg_wait<1>();
      mbar_arrive_if0(lane | (t == 0), bs12 + 8 * (DG + t - 1), 2);
    }
    TLW(30 + s);
    wg_wait<0>();
    mbar_arrive_if0(lane, bs12 + 8 * (DG + 2), 2);
#pragma unroll
    for (int t = 3; t < 12; t++) {
      g_step(t, (0x321045 >> (4 * (t % 6))) & 7);
      if (t > 3) {
        wg_wait<1>();
        mbar_arrive_if0(lane, bs12 + 8 * (DG + t - 1), 2);
        if (t == 7) mbar_arrive_remote_if0(lane, sb_peer + OFF_BAR + 8 * PF);
      }
    }
    mbar_wait_cluster(bars + 8 * PF);
    wg_wait<0>();
    reg_fence(accg);
    mbar_arrive_if0(lane, bs12 + 8 * (DG + 11), 2);
    TLW(34 + s);
    {
      const uint32_t buf = OFF_W2 + 5 * 24576 + s * PAGE + tid * 16;
#pragma unroll
      for (int e = 0; e < 8; e++) {
        const float a = accg[64 + e], b = accg[72 + e];
        accg[64 + e] = q ? a : b;
        accg[72 + e] = q ? b : a;
      }
#pragma unroll
      for (int m = 0; m < 5; m++) {
        const float* a = accg + 32 + 8 * m;
        asm volatile("st.async.shared::cluster.mbarrier::complete_tx::bytes.v4.b32 [%0], {%1,%2,%3,%4}, [%5];"
                     ::"r"(sb_peer + buf + m * 2048), "r"(pack2(a[0], a[1])), "r"(pack2(a[2], a[3])), "r"(pack2(a[4], a[5])),
                     "r"(pack2(a[6], a[7])), "r"(sb_peer + OFF_BAR + 8 * (RX + s)) : "memory");
      }
      TLW(58 + s);
      mbar_wait(bs12 + 8 * (DG + 11));
      mbar_wait_cluster(bars + 8 * (RX + s));
      TLW(60 + s);
      float4 rx[5];
#pragma unroll
      for (int m = 0; m < 5; m++) rx[m] = lds128(sb + buf + m * 2048);
      const uint32_t stg = rs + w * 2816;
      const uint32_t sa = stg + (lane & 15) * 176 + (lane >> 4) * 16;
#pragma unroll
      for (int ks = 0; ks < 5; ks++) {
        const uint32_t u[4] = {__float_as_uint(rx[ks].x), __float_as_uint(rx[ks].y), __float_as_uint(rx[ks].z), __float_as_uint(rx[ks].w)};
        const float* a = accg + (ks < 4 ? 8 * ks : 72);
        stsm4(sa + ks * 32, pack2(a[0] + bf_lo(u[0]), a[1] + bf_hi(u[0])), pack2(a[2] + bf_lo(u[1]), a[3] + bf_hi(u[1])),
              pack2(a[4] + bf_lo(u[2]), a[5] + bf_hi(u[2])), pack2(a[6] + bf_lo(u[3]), a[7] + bf_hi(u[3])));
      }
      __syncwarp();
#pragma unroll
      for (int m = 0; m < 4; m++) rx[m] = lds128(stg + (4 * m + (lane >> 3)) * 176 + (lane & 7) * 16);
      rx[4] = lds128(stg + (lane >> 1) * 176 + 128 + (lane & 1) * 16);
      __nv_bfloat16* outp = out + (row0 + (lane >> 3)) * 640 + cF + (lane & 7) * 8;
#pragma unroll
      for (int m = 0; m < 4; m++) *reinterpret_cast<float4*>(outp + m * 4 * 640) = rx[m];
      *reinterpret_cast<float4*>(out + (row0 + (lane >> 1)) * 640 + cR + (lane & 1) * 8) = rx[4];
    }
    mbar_arrive_if0(lane, bars + 8 * END, 1);
    TLW(36 + s);
  }
}

typedef CUresult (*EncodeFn)(CUtensorMap*, CUtensorMapDataType, cuuint32_t, void*, const cuuint64_t*, const cuuint64_t*,
                             const cuuint32_t*, const cuuint32_t*, CUtensorMapInterleave, CUtensorMapSwizzle,
                             CUtensorMapL2promotion, CUtensorMapFloatOOBfill);

void make_map(EncodeFn enc, CUtensorMap* tm, const void* base, int rows, int cols, int box_rows, int box_cols, int group, int natom,
              CUtensorMapSwizzle sw) {
  const cuuint64_t dims[3] = {(cuuint64_t)(natom ? group : cols), (cuuint64_t)rows, (cuuint64_t)(cols / group)};
  const cuuint64_t strides[2] = {(cuuint64_t)cols * 2, (cuuint64_t)group * 2};
  const cuuint32_t box[3] = {(cuuint32_t)box_cols, (cuuint32_t)box_rows, (cuuint32_t)natom}, es[3] = {1, 1, 1};
  enc(tm, CU_TENSOR_MAP_DATA_TYPE_BFLOAT16, natom ? 3 : 2, const_cast<void*>(base), dims, strides, box, es,
      CU_TENSOR_MAP_INTERLEAVE_NONE, sw, CU_TENSOR_MAP_L2_PROMOTION_L2_128B, CU_TENSOR_MAP_FLOAT_OOB_FILL_NONE);
}

}

extern "C" void kernel_launch(void* const* d_in, const int* in_sizes, int n_in, void* d_out, int out_size) {
  const __nv_bfloat16* x = (const __nv_bfloat16*)d_in[0];
  const __nv_bfloat16* wqkv = (const __nv_bfloat16*)d_in[1];
  const __nv_bfloat16* wo = (const __nv_bfloat16*)d_in[2];
  const __nv_bfloat16* w1 = (const __nv_bfloat16*)d_in[4];
  const __nv_bfloat16* b1 = (const __nv_bfloat16*)d_in[5];
  const __nv_bfloat16* w2 = (const __nv_bfloat16*)d_in[6];
  const __nv_bfloat16* b2 = (const __nv_bfloat16*)d_in[7];

  void* fn = nullptr;
  cudaDriverEntryPointQueryResult qr;
  cudaGetDriverEntryPoint("cuTensorMapEncodeTiled", &fn, cudaEnableDefault, &qr);
  EncodeFn enc = (EncodeFn)fn;
  const CUtensorMapSwizzle S128 = CU_TENSOR_MAP_SWIZZLE_128B, S64 = CU_TENSOR_MAP_SWIZZLE_64B;
  Maps maps;
  make_map(enc, &maps.m[M_X], x, 2048, 640, 64, 64, 64, 0, S128);
  make_map(enc, &maps.m[M_KVF], wqkv, 640, 1920, 32, 64, 640, 2, S128);
  make_map(enc, &maps.m[M_KVH], wqkv, 640, 1920, 32, 32, 64, 0, S128);
  make_map(enc, &maps.m[M_Q2], wqkv, 640, 1920, 64, 32, 32, 2, S64);
  make_map(enc, &maps.m[M_QR], wqkv, 640, 1920, 64, 16, 64, 0, S64);
  make_map(enc, &maps.m[M_WO2], wo, 640, 640, 80, 32, 32, 2, S64);
  make_map(enc, &maps.m[M_WOR], wo, 640, 640, 80, 16, 64, 0, S64);
  make_map(enc, &maps.m[M_W1], w1, 640, 1536, 64, 64, 64, 3, S128);
  make_map(enc, &maps.m[M_W1R], w1, 640, 1536, 16, 64, 64, 3, S128);
  make_map(enc, &maps.m[M_W2F], w2, 1536, 640, 64, 64, 64, 0, S128);
  make_map(enc, &maps.m[M_W2H], w2, 1536, 640, 64, 32, 64, 0, S128);
  cudaFuncSetAttribute(fused_block_kernel, cudaFuncAttributeMaxDynamicSharedMemorySize, SMEM_BYTES);
  fused_block_kernel<<<128, 384, SMEM_BYTES>>>(maps, x, wqkv, wo, w1, b1, w2, b2, (__nv_bfloat16*)d_out);
}
```

```cpp
#include <cuda_runtime.h>
#include <cuda_bf16.h>
#include <cuda.h>
#include <stdint.h>

namespace {

struct Desc { uint32_t base, off, hi; };
__device__ __forceinline__ Desc operator+(Desc d, uint32_t o) { return Desc{d.base, d.off + o, d.hi}; }
template <int TA, int TB> __device__ __forceinline__ void wgmma_ss_n48(float (&d)[24], Desc a, Desc b, int sc) {
  asm volatile("{.reg .pred p; .reg .b32 t, u; .reg .b64 da, db; setp.ne.b32 p, %30, 0; add.u32 t, %24, %25; mov.b64 da, {t, %26}; add.u32 u, %27, %28; mov.b64 db, {u, %29};"
    "wgmma.mma_async.sync.aligned.m64n48k16.f32.bf16.bf16 {%0,%1,%2,%3,%4,%5,%6,%7,%8,%9,%10,%11,%12,%13,%14,%15,%16,%17,%18,%19,%20,%21,%22,%23}, da, db, p, 1, 1, %31, %32;}"
    : "+f"(d[0]),"+f"(d[1]),"+f"(d[2]),"+f"(d[3]),"+f"(d[4]),"+f"(d[5]),"+f"(d[6]),"+f"(d[7]),"+f"(d[8]),"+f"(d[9]),"+f"(d[10]),"+f"(d[11]),"+f"(d[12]),"+f"(d[13]),"+f"(d[14]),"+f"(d[15]),"+f"(d[16]),"+f"(d[17]),"+f"(d[18]),"+f"(d[19]),"+f"(d[20]),"+f"(d[21]),"+f"(d[22]),"+f"(d[23])
    : "r"(a.base), "r"(a.off), "r"(a.hi), "r"(b.base), "r"(b.off), "r"(b.hi), "r"(sc), "n"(TA), "n"(TB));
}
template <int TA, int TB> __device__ __forceinline__ void wgmma_ss_n80(float (&d)[40], Desc a, Desc b, int sc) {
  asm volatile("{.reg .pred p; .reg .b32 t, u; .reg .b64 da, db; setp.ne.b32 p, %46, 0; add.u32 t, %40, %41; mov.b64 da, {t, %42}; add.u32 u, %43, %44; mov.b64 db, {u, %45};"
    "wgmma.mma_async.sync.aligned.m64n80k16.f32.bf16.bf16 {%0,%1,%2,%3,%4,%5,%6,%7,%8,%9,%10,%11,%12,%13,%14,%15,%16,%17,%18,%19,%20,%21,%22,%23,%24,%25,%26,%27,%28,%29,%30,%31,%32,%33,%34,%35,%36,%37,%38,%39}, da, db, p, 1, 1, %47, %48;}"
    : "+f"(d[0]),"+f"(d[1]),"+f"(d[2]),"+f"(d[3]),"+f"(d[4]),"+f"(d[5]),"+f"(d[6]),"+f"(d[7]),"+f"(d[8]),"+f"(d[9]),"+f"(d[10]),"+f"(d[11]),"+f"(d[12]),"+f"(d[13]),"+f"(d[14]),"+f"(d[15]),"+f"(d[16]),"+f"(d[17]),"+f"(d[18]),"+f"(d[19]),"+f"(d[20]),"+f"(d[21]),"+f"(d[22]),"+f"(d[23]),"+f"(d[24]),"+f"(d[25]),"+f"(d[26]),"+f"(d[27]),"+f"(d[28]),"+f"(d[29]),"+f"(d[30]),"+f"(d[31]),"+f"(d[32]),"+f"(d[33]),"+f"(d[34]),"+f"(d[35]),"+f"(d[36]),"+f"(d[37]),"+f"(d[38]),"+f"(d[39])
    : "r"(a.base), "r"(a.off), "r"(a.hi), "r"(b.base), "r"(b.off), "r"(b.hi), "r"(sc), "n"(TA), "n"(TB));
}
template <int TA, int TB> __device__ __forceinline__ void wgmma_ss_n160(float (&d)[80], Desc a, Desc b, int sc) {
  asm volatile("{.reg .pred p; .reg .b32 t, u; .reg .b64 da, db; setp.ne.b32 p, %86, 0; add.u32 t, %80, %81; mov.b64 da, {t, %82}; add.u32 u, %83, %84; mov.b64 db, {u, %85};"
    "wgmma.mma_async.sync.aligned.m64n160k16.f32.bf16.bf16 {%0,%1,%2,%3,%4,%5,%6,%7,%8,%9,%10,%11,%12,%13,%14,%15,%16,%17,%18,%19,%20,%21,%22,%23,%24,%25,%26,%27,%28,%29,%30,%31,%32,%33,%34,%35,%36,%37,%38,%39,%40,%41,%42,%43,%44,%45,%46,%47,%48,%49,%50,%51,%52,%53,%54,%55,%56,%57,%58,%59,%60,%61,%62,%63,%64,%65,%66,%67,%68,%69,%70,%71,%72,%73,%74,%75,%76,%77,%78,%79}, da, db, p, 1, 1, %87, %88;}"
    : "+f"(d[0]),"+f"(d[1]),"+f"(d[2]),"+f"(d[3]),"+f"(d[4]),"+f"(d[5]),"+f"(d[6]),"+f"(d[7]),"+f"(d[8]),"+f"(d[9]),"+f"(d[10]),"+f"(d[11]),"+f"(d[12]),"+f"(d[13]),"+f"(d[14]),"+f"(d[15]),"+f"(d[16]),"+f"(d[17]),"+f"(d[18]),"+f"(d[19]),"+f"(d[20]),"+f"(d[21]),"+f"(d[22]),"+f"(d[23]),"+f"(d[24]),"+f"(d[25]),"+f"(d[26]),"+f"(d[27]),"+f"(d[28]),"+f"(d[29]),"+f"(d[30]),"+f"(d[31]),"+f"(d[32]),"+f"(d[33]),"+f"(d[34]),"+f"(d[35]),"+f"(d[36]),"+f"(d[37]),"+f"(d[38]),"+f"(d[39]),"+f"(d[40]),"+f"(d[41]),"+f"(d[42]),"+f"(d[43]),"+f"(d[44]),"+f"(d[45]),"+f"(d[46]),"+f"(d[47]),"+f"(d[48]),"+f"(d[49]),"+f"(d[50]),"+f"(d[51]),"+f"(d[52]),"+f"(d[53]),"+f"(d[54]),"+f"(d[55]),"+f"(d[56]),"+f"(d[57]),"+f"(d[58]),"+f"(d[59]),"+f"(d[60]),"+f"(d[61]),"+f"(d[62]),"+f"(d[63]),"+f"(d[64]),"+f"(d[65]),"+f"(d[66]),"+f"(d[67]),"+f"(d[68]),"+f"(d[69]),"+f"(d[70]),"+f"(d[71]),"+f"(d[72]),"+f"(d[73]),"+f"(d[74]),"+f"(d[75]),"+f"(d[76]),"+f"(d[77]),"+f"(d[78]),"+f"(d[79])
    : "r"(a.base), "r"(a.off), "r"(a.hi), "r"(b.base), "r"(b.off), "r"(b.hi), "r"(sc), "n"(TA), "n"(TB));
}
template <int TA, int TB> __device__ __forceinline__ void wgmma_ss_n192(float (&d)[96], Desc a, Desc b, int sc) {
  asm volatile("{.reg .pred p; .reg .b32 t, u; .reg .b64 da, db; setp.ne.b32 p, %102, 0; add.u32 t, %96, %97; mov.b64 da, {t, %98}; add.u32 u, %99, %100; mov.b64 db, {u, %101};"
    "wgmma.mma_async.sync.aligned.m64n192k16.f32.bf16.bf16 {%0,%1,%2,%3,%4,%5,%6,%7,%8,%9,%10,%11,%12,%13,%14,%15,%16,%17,%18,%19,%20,%21,%22,%23,%24,%25,%26,%27,%28,%29,%30,%31,%32,%33,%34,%35,%36,%37,%38,%39,%40,%41,%42,%43,%44,%45,%46,%47,%48,%49,%50,%51,%52,%53,%54,%55,%56,%57,%58,%59,%60,%61,%62,%63,%64,%65,%66,%67,%68,%69,%70,%71,%72,%73,%74,%75,%76,%77,%78,%79,%80,%81,%82,%83,%84,%85,%86,%87,%88,%89,%90,%91,%92,%93,%94,%95}, da, db, p, 1, 1, %103, %104;}"
    : "+f"(d[0]),"+f"(d[1]),"+f"(d[2]),"+f"(d[3]),"+f"(d[4]),"+f"(d[5]),"+f"(d[6]),"+f"(d[7]),"+f"(d[8]),"+f"(d[9]),"+f"(d[10]),"+f"(d[11]),"+f"(d[12]),"+f"(d[13]),"+f"(d[14]),"+f"(d[15]),"+f"(d[16]),"+f"(d[17]),"+f"(d[18]),"+f"(d[19]),"+f"(d[20]),"+f"(d[21]),"+f"(d[22]),"+f"(d[23]),"+f"(d[24]),"+f"(d[25]),"+f"(d[26]),"+f"(d[27]),"+f"(d[28]),"+f"(d[29]),"+f"(d[30]),"+f"(d[31]),"+f"(d[32]),"+f"(d[33]),"+f"(d[34]),"+f"(d[35]),"+f"(d[36]),"+f"(d[37]),"+f"(d[38]),"+f"(d[39]),"+f"(d[40]),"+f"(d[41]),"+f"(d[42]),"+f"(d[43]),"+f"(d[44]),"+f"(d[45]),"+f"(d[46]),"+f"(d[47]),"+f"(d[48]),"+f"(d[49]),"+f"(d[50]),"+f"(d[51]),"+f"(d[52]),"+f"(d[53]),"+f"(d[54]),"+f"(d[55]),"+f"(d[56]),"+f"(d[57]),"+f"(d[58]),"+f"(d[59]),"+f"(d[60]),"+f"(d[61]),"+f"(d[62]),"+f"(d[63]),"+f"(d[64]),"+f"(d[65]),"+f"(d[66]),"+f"(d[67]),"+f"(d[68]),"+f"(d[69]),"+f"(d[70]),"+f"(d[71]),"+f"(d[72]),"+f"(d[73]),"+f"(d[74]),"+f"(d[75]),"+f"(d[76]),"+f"(d[77]),"+f"(d[78]),"+f"(d[79]),"+f"(d[80]),"+f"(d[81]),"+f"(d[82]),"+f"(d[83]),"+f"(d[84]),"+f"(d[85]),"+f"(d[86]),"+f"(d[87]),"+f"(d[88]),"+f"(d[89]),"+f"(d[90]),"+f"(d[91]),"+f"(d[92]),"+f"(d[93]),"+f"(d[94]),"+f"(d[95])
    : "r"(a.base), "r"(a.off), "r"(a.hi), "r"(b.base), "r"(b.off), "r"(b.hi), "r"(sc), "n"(TA), "n"(TB));
}
template <int TB> __device__ __forceinline__ void wgmma_rs_n80(float (&d)[40], uint32_t a0, uint32_t a1, uint32_t a2, uint32_t a3, Desc b, int sc) {
  asm volatile("{.reg .pred p; .reg .b32 u; .reg .b64 db; setp.ne.b32 p, %47, 0; add.u32 u, %44, %45; mov.b64 db, {u, %46};"
    "wgmma.mma_async.sync.aligned.m64n80k16.f32.bf16.bf16 {%0,%1,%2,%3,%4,%5,%6,%7,%8,%9,%10,%11,%12,%13,%14,%15,%16,%17,%18,%19,%20,%21,%22,%23,%24,%25,%26,%27,%28,%29,%30,%31,%32,%33,%34,%35,%36,%37,%38,%39}, {%40,%41,%42,%43}, db, p, 1, 1, %48;}"
    : "+f"(d[0]),"+f"(d[1]),"+f"(d[2]),"+f"(d[3]),"+f"(d[4]),"+f"(d[5]),"+f"(d[6]),"+f"(d[7]),"+f"(d[8]),"+f"(d[9]),"+f"(d[10]),"+f"(d[11]),"+f"(d[12]),"+f"(d[13]),"+f"(d[14]),"+f"(d[15]),"+f"(d[16]),"+f"(d[17]),"+f"(d[18]),"+f"(d[19]),"+f"(d[20]),"+f"(d[21]),"+f"(d[22]),"+f"(d[23]),"+f"(d[24]),"+f"(d[25]),"+f"(d[26]),"+f"(d[27]),"+f"(d[28]),"+f"(d[29]),"+f"(d[30]),"+f"(d[31]),"+f"(d[32]),"+f"(d[33]),"+f"(d[34]),"+f"(d[35]),"+f"(d[36]),"+f"(d[37]),"+f"(d[38]),"+f"(d[39])
    : "r"(a0), "r"(a1), "r"(a2), "r"(a3), "r"(b.base), "r"(b.off), "r"(b.hi), "r"(sc), "n"(TB));
}
template <int TB> __device__ __forceinline__ void wgmma_rs_n96(float (&d)[48], uint32_t a0, uint32_t a1, uint32_t a2, uint32_t a3, Desc b, int sc) {
  asm volatile("{.reg .pred p; .reg .b32 u; .reg .b64 db; setp.ne.b32 p, %55, 0; add.u32 u, %52, %53; mov.b64 db, {u, %54};"
    "wgmma.mma_async.sync.aligned.m64n96k16.f32.bf16.bf16 {%0,%1,%2,%3,%4,%5,%6,%7,%8,%9,%10,%11,%12,%13,%14,%15,%16,%17,%18,%19,%20,%21,%22,%23,%24,%25,%26,%27,%28,%29,%30,%31,%32,%33,%34,%35,%36,%37,%38,%39,%40,%41,%42,%43,%44,%45,%46,%47}, {%48,%49,%50,%51}, db, p, 1, 1, %56;}"
    : "+f"(d[0]),"+f"(d[1]),"+f"(d[2]),"+f"(d[3]),"+f"(d[4]),"+f"(d[5]),"+f"(d[6]),"+f"(d[7]),"+f"(d[8]),"+f"(d[9]),"+f"(d[10]),"+f"(d[11]),"+f"(d[12]),"+f"(d[13]),"+f"(d[14]),"+f"(d[15]),"+f"(d[16]),"+f"(d[17]),"+f"(d[18]),"+f"(d[19]),"+f"(d[20]),"+f"(d[21]),"+f"(d[22]),"+f"(d[23]),"+f"(d[24]),"+f"(d[25]),"+f"(d[26]),"+f"(d[27]),"+f"(d[28]),"+f"(d[29]),"+f"(d[30]),"+f"(d[31]),"+f"(d[32]),"+f"(d[33]),"+f"(d[34]),"+f"(d[35]),"+f"(d[36]),"+f"(d[37]),"+f"(d[38]),"+f"(d[39]),"+f"(d[40]),"+f"(d[41]),"+f"(d[42]),"+f"(d[43]),"+f"(d[44]),"+f"(d[45]),"+f"(d[46]),"+f"(d[47])
    : "r"(a0), "r"(a1), "r"(a2), "r"(a3), "r"(b.base), "r"(b.off), "r"(b.hi), "r"(sc), "n"(TB));
}
template <int TB> __device__ __forceinline__ void wgmma_rs_n160(float (&d)[80], uint32_t a0, uint32_t a1, uint32_t a2, uint32_t a3, Desc b, int sc) {
  asm volatile("{.reg .pred p; .reg .b32 u; .reg .b64 db; setp.ne.b32 p, %87, 0; add.u32 u, %84, %85; mov.b64 db, {u, %86};"
    "wgmma.mma_async.sync.aligned.m64n160k16.f32.bf16.bf16 {%0,%1,%2,%3,%4,%5,%6,%7,%8,%9,%10,%11,%12,%13,%14,%15,%16,%17,%18,%19,%20,%21,%22,%23,%24,%25,%26,%27,%28,%29,%30,%31,%32,%33,%34,%35,%36,%37,%38,%39,%40,%41,%42,%43,%44,%45,%46,%47,%48,%49,%50,%51,%52,%53,%54,%55,%56,%57,%58,%59,%60,%61,%62,%63,%64,%65,%66,%67,%68,%69,%70,%71,%72,%73,%74,%75,%76,%77,%78,%79}, {%80,%81,%82,%83}, db, p, 1, 1, %88;}"
    : "+f"(d[0]),"+f"(d[1]),"+f"(d[2]),"+f"(d[3]),"+f"(d[4]),"+f"(d[5]),"+f"(d[6]),"+f"(d[7]),"+f"(d[8]),"+f"(d[9]),"+f"(d[10]),"+f"(d[11]),"+f"(d[12]),"+f"(d[13]),"+f"(d[14]),"+f"(d[15]),"+f"(d[16]),"+f"(d[17]),"+f"(d[18]),"+f"(d[19]),"+f"(d[20]),"+f"(d[21]),"+f"(d[22]),"+f"(d[23]),"+f"(d[24]),"+f"(d[25]),"+f"(d[26]),"+f"(d[27]),"+f"(d[28]),"+f"(d[29]),"+f"(d[30]),"+f"(d[31]),"+f"(d[32]),"+f"(d[33]),"+f"(d[34]),"+f"(d[35]),"+f"(d[36]),"+f"(d[37]),"+f"(d[38]),"+f"(d[39]),"+f"(d[40]),"+f"(d[41]),"+f"(d[42]),"+f"(d[43]),"+f"(d[44]),"+f"(d[45]),"+f"(d[46]),"+f"(d[47]),"+f"(d[48]),"+f"(d[49]),"+f"(d[50]),"+f"(d[51]),"+f"(d[52]),"+f"(d[53]),"+f"(d[54]),"+f"(d[55]),"+f"(d[56]),"+f"(d[57]),"+f"(d[58]),"+f"(d[59]),"+f"(d[60]),"+f"(d[61]),"+f"(d[62]),"+f"(d[63]),"+f"(d[64]),"+f"(d[65]),"+f"(d[66]),"+f"(d[67]),"+f"(d[68]),"+f"(d[69]),"+f"(d[70]),"+f"(d[71]),"+f"(d[72]),"+f"(d[73]),"+f"(d[74]),"+f"(d[75]),"+f"(d[76]),"+f"(d[77]),"+f"(d[78]),"+f"(d[79])
    : "r"(a0), "r"(a1), "r"(a2), "r"(a3), "r"(b.base), "r"(b.off), "r"(b.hi), "r"(sc), "n"(TB));
}
template <int TB> __device__ __forceinline__ void wgmma_rs_n192(float (&d)[96], uint32_t a0, uint32_t a1, uint32_t a2, uint32_t a3, Desc b, int sc) {
  asm volatile("{.reg .pred p; .reg .b32 u; .reg .b64 db; setp.ne.b32 p, %103, 0; add.u32 u, %100, %101; mov.b64 db, {u, %102};"
    "wgmma.mma_async.sync.aligned.m64n192k16.f32.bf16.bf16 {%0,%1,%2,%3,%4,%5,%6,%7,%8,%9,%10,%11,%12,%13,%14,%15,%16,%17,%18,%19,%20,%21,%22,%23,%24,%25,%26,%27,%28,%29,%30,%31,%32,%33,%34,%35,%36,%37,%38,%39,%40,%41,%42,%43,%44,%45,%46,%47,%48,%49,%50,%51,%52,%53,%54,%55,%56,%57,%58,%59,%60,%61,%62,%63,%64,%65,%66,%67,%68,%69,%70,%71,%72,%73,%74,%75,%76,%77,%78,%79,%80,%81,%82,%83,%84,%85,%86,%87,%88,%89,%90,%91,%92,%93,%94,%95}, {%96,%97,%98,%99}, db, p, 1, 1, %104;}"
    : "+f"(d[0]),"+f"(d[1]),"+f"(d[2]),"+f"(d[3]),"+f"(d[4]),"+f"(d[5]),"+f"(d[6]),"+f"(d[7]),"+f"(d[8]),"+f"(d[9]),"+f"(d[10]),"+f"(d[11]),"+f"(d[12]),"+f"(d[13]),"+f"(d[14]),"+f"(d[15]),"+f"(d[16]),"+f"(d[17]),"+f"(d[18]),"+f"(d[19]),"+f"(d[20]),"+f"(d[21]),"+f"(d[22]),"+f"(d[23]),"+f"(d[24]),"+f"(d[25]),"+f"(d[26]),"+f"(d[27]),"+f"(d[28]),"+f"(d[29]),"+f"(d[30]),"+f"(d[31]),"+f"(d[32]),"+f"(d[33]),"+f"(d[34]),"+f"(d[35]),"+f"(d[36]),"+f"(d[37]),"+f"(d[38]),"+f"(d[39]),"+f"(d[40]),"+f"(d[41]),"+f"(d[42]),"+f"(d[43]),"+f"(d[44]),"+f"(d[45]),"+f"(d[46]),"+f"(d[47]),"+f"(d[48]),"+f"(d[49]),"+f"(d[50]),"+f"(d[51]),"+f"(d[52]),"+f"(d[53]),"+f"(d[54]),"+f"(d[55]),"+f"(d[56]),"+f"(d[57]),"+f"(d[58]),"+f"(d[59]),"+f"(d[60]),"+f"(d[61]),"+f"(d[62]),"+f"(d[63]),"+f"(d[64]),"+f"(d[65]),"+f"(d[66]),"+f"(d[67]),"+f"(d[68]),"+f"(d[69]),"+f"(d[70]),"+f"(d[71]),"+f"(d[72]),"+f"(d[73]),"+f"(d[74]),"+f"(d[75]),"+f"(d[76]),"+f"(d[77]),"+f"(d[78]),"+f"(d[79]),"+f"(d[80]),"+f"(d[81]),"+f"(d[82]),"+f"(d[83]),"+f"(d[84]),"+f"(d[85]),"+f"(d[86]),"+f"(d[87]),"+f"(d[88]),"+f"(d[89]),"+f"(d[90]),"+f"(d[91]),"+f"(d[92]),"+f"(d[93]),"+f"(d[94]),"+f"(d[95])
    : "r"(a0), "r"(a1), "r"(a2), "r"(a3), "r"(b.base), "r"(b.off), "r"(b.hi), "r"(sc), "n"(TB));
}
template <int N, int TA, int TB> __device__ __forceinline__ void wgmma_ss(float (&d)[N / 2], Desc a, Desc b, int sc) {
  if constexpr (N == 48) wgmma_ss_n48<TA, TB>(d, a, b, sc);
  else if constexpr (N == 80) wgmma_ss_n80<TA, TB>(d, a, b, sc);
  else if constexpr (N == 160) wgmma_ss_n160<TA, TB>(d, a, b, sc);
  else if constexpr (N == 192) wgmma_ss_n192<TA, TB>(d, a, b, sc);
}
template <int N, int TB> __device__ __forceinline__ void wgmma_rs(float (&d)[N / 2], uint32_t a0, uint32_t a1, uint32_t a2, uint32_t a3, Desc b, int sc) {
  if constexpr (N == 80) wgmma_rs_n80<TB>(d, a0, a1, a2, a3, b, sc);
  else if constexpr (N == 96) wgmma_rs_n96<TB>(d, a0, a1, a2, a3, b, sc);
  else if constexpr (N == 160) wgmma_rs_n160<TB>(d, a0, a1, a2, a3, b, sc);
  else if constexpr (N == 192) wgmma_rs_n192<TB>(d, a0, a1, a2, a3, b, sc);
}

constexpr uint32_t SMEM_BASE = 1024;
constexpr uint32_t PAGE = 10240;
constexpr uint32_t OFF_RING = 16 * PAGE;
constexpr uint32_t OFF_KVB = 49152;
constexpr uint32_t OFF_R1 = 35840;
constexpr uint32_t OFF_MISC = 22 * PAGE;
constexpr uint32_t OFF_W2 = OFF_MISC - 6 * 24576;
constexpr uint32_t OFF_BAR = OFF_MISC;
constexpr uint32_t OFF_LN1 = OFF_MISC + 1920;
constexpr uint32_t OFF_RK1 = OFF_MISC + 2944;
constexpr uint32_t OFF_B2 = OFF_RK1 + 3072;
constexpr uint32_t OFF_SCR = OFF_MISC + 6784;
constexpr uint32_t SMEM_BYTES = OFF_MISC + 7040;

enum : int {
  FX = 0, PX = 13, PF = 14, RX = 15, RXK = 17, SIDE = 18, ZK = 19, RKV = 20,
  RE = 21, RF = 26, ST1 = 31,
  FWO = 32, FW1 = 40, FW2 = 48,
  AO = 60, AH = 76, AF = 92,
  DW = 116, DF = 132, DG = 148,
  SO = 172, SFB = 174,
  SIDE2 = 176, KVB = 177, END = 178, OM = 179
};

__device__ uint32_t g_epoch;
__device__ uint4 g_ln1[2048];
__device__ uint4 g_cs[4 * 1728];
__device__ uint4 g_hstat[32 * 8 * 64];
__device__ __align__(128) float2 g_kv1[8 * 16 * 16 * 64];
__device__ __align__(128) uint2 g_kv2[8 * 960];
__device__ __align__(128) uint32_t g_flag[3 * 32 * 32];
__device__ __align__(128) uint8_t g_act[3 * 32 * 8 * 24576];

struct Maps { CUtensorMap m[11]; };
enum : int { M_X, M_KVF, M_KVH, M_Q2, M_QR, M_WO2, M_WOR, M_W1, M_W1R, M_W2F, M_W2H };

#define TL(id)
#define TLW(id)
#define TL0(id)
#define TC(v)
#define TS(id, v)

constexpr int SPIN_LIMIT = 1 << 19;

__device__ __forceinline__ bool elect_one() {
  uint32_t p;
  asm volatile("{.reg .pred P; elect.sync _|P, 0xffffffff; selp.u32 %0,1,0,P;}" : "=r"(p));
  return p;
}
__device__ __forceinline__ void mbar_wait(uint32_t bar, uint32_t parity = 0) {
  asm volatile("{.reg .pred p;\nW: mbarrier.try_wait.parity.shared::cta.b64 p, [%0], %1;\n@!p bra W;}" ::"r"(bar), "r"(parity) : "memory");
}
__device__ __forceinline__ void mbar_wait_cluster(uint32_t bar) {
  asm volatile("{.reg .pred p;\nW: mbarrier.try_wait.parity.acquire.cluster.shared::cta.b64 p, [%0], 0;\n@!p bra W;}" ::"r"(bar) : "memory");
}
__device__ __forceinline__ void mbar_wait_wd(uint32_t bar) {
  asm volatile("{.reg .pred p; .reg .u32 n; mov.u32 n, 0;\n"
               "W: mbarrier.try_wait.parity.shared::cta.b64 p, [%0], 0;\n"
               "@p bra D; add.u32 n, n, 1; setp.gt.u32 p, n, %1; @p trap; bra W;\n"
               "D: }" ::"r"(bar), "n"(SPIN_LIMIT) : "memory");
}
__device__ __forceinline__ void mbar_arrive(uint32_t bar, uint32_t n) {
  asm volatile("mbarrier.arrive.shared::cta.b64 _, [%0], %1;" ::"r"(bar), "r"(n) : "memory");
}
__device__ __forceinline__ void mbar_arrive_if0(int z, uint32_t bar, uint32_t n) {
  asm volatile("{.reg .pred p; setp.eq.s32 p, %2, 0; @p mbarrier.arrive.shared::cta.b64 _, [%0], %1;}" ::"r"(bar), "r"(n), "r"(z) : "memory");
}
__device__ __forceinline__ void mbar_arrive_remote_if0(int z, uint32_t bar) {
  asm volatile("{.reg .pred p; setp.eq.s32 p, %1, 0; @p mbarrier.arrive.shared::cluster.b64 _, [%0];}" ::"r"(bar), "r"(z) : "memory");
}
__device__ __forceinline__ void mbar_expect(uint32_t bar, uint32_t bytes) {
  asm volatile("mbarrier.arrive.expect_tx.shared::cta.b64 _, [%0], %1;" ::"r"(bar), "r"(bytes) : "memory");
  asm volatile("mbarrier.arrive.shared::cta.b64 _, [%0], 7;" ::"r"(bar) : "memory");
}
__device__ __forceinline__ void tma2d(uint32_t dst, const CUtensorMap* tm, uint32_t bar, int c0, int c1) {
  asm volatile("cp.async.bulk.tensor.2d.shared::cluster.global.mbarrier::complete_tx::bytes [%0],[%1,{%3,%4}],[%2];"
               ::"r"(dst), "l"(tm), "r"(bar), "r"(c0), "r"(c1) : "memory");
}
__device__ __forceinline__ void tma3d(uint32_t dst, const CUtensorMap* tm, uint32_t bar, int c0, int c1, int c2) {
  asm volatile("cp.async.bulk.tensor.3d.shared::cluster.global.mbarrier::complete_tx::bytes [%0],[%1,{%3,%4,%5}],[%2];"
               ::"r"(dst), "l"(tm), "r"(bar), "r"(c0), "r"(c1), "r"(c2) : "memory");
}
__device__ __forceinline__ void tma2d_pair(uint32_t dst, const CUtensorMap* tm, uint32_t bar, int c0, int c1) {
  asm volatile("cp.async.bulk.tensor.2d.shared::cluster.global.mbarrier::complete_tx::bytes.multicast::cluster [%0],[%1,{%3,%4}],[%2],%5;"
               ::"r"(dst), "l"(tm), "r"(bar), "r"(c0), "r"(c1), "h"((uint16_t)3) : "memory");
}
__device__ __forceinline__ void bulk_load(uint32_t dst, const void* src, uint32_t bytes, uint32_t bar) {
  asm volatile("cp.async.bulk.shared::cluster.global.mbarrier::complete_tx::bytes [%0],[%1],%2,[%3];"
               ::"r"(dst), "l"(src), "r"(bytes), "r"(bar) : "memory");
}
__device__ __forceinline__ void bulk_store(void* dst, uint32_t src, uint32_t bytes) {
  asm volatile("cp.async.bulk.global.shared::cta.bulk_group [%0],[%1],%2;" ::"l"(dst), "r"(src), "r"(bytes) : "memory");
}
__device__ __forceinline__ void bulk_commit_wait() {
  asm volatile("cp.async.bulk.commit_group;" ::: "memory");
  asm volatile("cp.async.bulk.wait_group 0;" ::: "memory");
}
__device__ __forceinline__ void l2_prefetch(const void* src, uint32_t bytes) {
  asm volatile("cp.async.bulk.prefetch.L2.global [%0], %1;" ::"l"(src), "r"(bytes) : "memory");
}
__device__ __forceinline__ void fence_gpu() { asm volatile("fence.acq_rel.gpu;" ::: "memory"); }
__device__ __forceinline__ void fence_async_smem() { asm volatile("fence.proxy.async.shared::cta;" ::: "memory"); }
__device__ __forceinline__ void fence_async_global() { asm volatile("fence.proxy.async.global;" ::: "memory"); }
__device__ __forceinline__ void st_flag(uint32_t* p, uint32_t v) {
  asm volatile("st.relaxed.gpu.global.u32 [%0], %1;" ::"l"(p), "r"(v) : "memory");
}
__device__ __forceinline__ uint32_t ld_acq(const uint32_t* p) {
  uint32_t v;
  asm volatile("ld.acquire.gpu.global.u32 %0, [%1];" : "=r"(v) : "l"(p) : "memory");
  return v;
}
__device__ __forceinline__ void wg_fence() { asm volatile("wgmma.fence.sync.aligned;" ::: "memory"); }
__device__ __forceinline__ void wg_commit() { asm volatile("wgmma.commit_group.sync.aligned;" ::: "memory"); }
template <int N> __device__ __forceinline__ void wg_wait() { asm volatile("wgmma.wait_group.sync.aligned %0;" ::"n"(N) : "memory"); }
template <int N> __device__ __forceinline__ void reg_fence(float (&a)[N]) {
#pragma unroll
  for (int i = 0; i < N; i++) asm volatile("" : "+f"(a[i])::"memory");
}
template <int ID, int N> __device__ __forceinline__ void named_bar() { asm volatile("bar.sync %0, %1;" ::"n"(ID), "n"(N) : "memory"); }
template <int N> __device__ __forceinline__ void reg_fence(uint32_t (&a)[N]) {
#pragma unroll
  for (int i = 0; i < N; i++) asm volatile("" : "+r"(a[i])::"memory");
}
__device__ __forceinline__ Desc mkdesc(uint32_t dyn, uint32_t off, uint32_t lbo, uint32_t sbo, uint32_t swz) {
  return Desc{dyn, ((off + SMEM_BASE) >> 4) + ((lbo >> 4) << 16), (sbo >> 4) | (swz << 30)};
}
__device__ __forceinline__ uint32_t pack2(float lo, float hi) {
  uint32_t r;
  asm("cvt.rn.bf16x2.f32 %0, %1, %2;" : "=r"(r) : "f"(hi), "f"(lo));
  return r;
}
__device__ __forceinline__ float bf_lo(uint32_t v) { return __uint_as_float(v << 16); }
__device__ __forceinline__ float bf_hi(uint32_t v) { return __uint_as_float(v & 0xffff0000u); }
__device__ __forceinline__ void stsm4(uint32_t addr, uint32_t a, uint32_t b, uint32_t c, uint32_t d) {
  asm volatile("stmatrix.sync.aligned.m8n8.x4.shared.b16 [%0], {%1,%2,%3,%4};" ::"r"(addr), "r"(a), "r"(b), "r"(c), "r"(d) : "memory");
}
__device__ __forceinline__ void ldsm4(uint32_t addr, uint32_t* r) {
  asm volatile("ldmatrix.sync.aligned.m8n8.x4.shared.b16 {%0,%1,%2,%3}, [%4];" : "=r"(r[0]), "=r"(r[1]), "=r"(r[2]), "=r"(r[3]) : "r"(addr) : "memory");
}
__device__ __forceinline__ float2 lds64(uint32_t a) {
  float2 v;
  asm volatile("ld.shared.v2.f32 {%0,%1}, [%2];" : "=f"(v.x), "=f"(v.y) : "r"(a) : "memory");
  return v;
}
__device__ __forceinline__ float4 lds128(uint32_t a) {
  float4 v;
  asm volatile("ld.shared.v4.f32 {%0,%1,%2,%3}, [%4];" : "=f"(v.x), "=f"(v.y), "=f"(v.z), "=f"(v.w) : "r"(a) : "memory");
  return v;
}
__device__ __forceinline__ void sts64(uint32_t a, uint32_t x, uint32_t y) {
  asm volatile("st.shared.v2.u32 [%0], {%1,%2};" ::"r"(a), "r"(x), "r"(y) : "memory");
}
__device__ __forceinline__ void sts128(uint32_t a, uint32_t x, uint32_t y, uint32_t z, uint32_t w) {
  asm volatile("st.shared.v4.u32 [%0], {%1,%2,%3,%4};" ::"r"(a), "r"(x), "r"(y), "r"(z), "r"(w) : "memory");
}
__device__ __forceinline__ float ex2(float x) {
  float r;
  asm("ex2.approx.ftz.f32 %0, %1;" : "=f"(r) : "f"(x));
  return r;
}
__device__ __forceinline__ float rcp(float x) {
  float r;
  asm("rcp.approx.ftz.f32 %0, %1;" : "=f"(r) : "f"(x));
  return r;
}
constexpr float LOG2E = 1.4426950408889634f;
__device__ __forceinline__ float phi(float z, float a, float a2) {
  float r = ex2(z * a2) + 1e-6f;
  asm("{.reg .pred p; setp.gt.f32 p, %1, 0f00000000; @p fma.rn.f32 %0, %1, %2, 0f3F800008;}" : "+f"(r) : "f"(z), "f"(a));
  return r;
}
__device__ __forceinline__ float gelu(float z, const float3& k) {
  float th;
  asm("tanh.approx.f32 %0, %1;" : "=f"(th) : "f"(z * fmaf(z * z, k.y, k.x)));
  const float hy = z * k.z;
  return fmaf(hy, th, hy);
}
__device__ __forceinline__ uint32_t rk1_frag(float m, float d, int c) {
  const uint32_t hi = pack2(m, d), lo = pack2(m - bf_lo(hi), d - bf_hi(hi));
  return c == 0 ? __byte_perm(hi, 0, 0x1010) : c == 1 ? __byte_perm(lo, hi, 0x7610) : c == 2 ? lo >> 16 : 0u;
}
__device__ __forceinline__ void rk1_store(uint32_t addr, float2 cs, uint32_t bb) {
  const uint32_t hi = pack2(cs.x, cs.y), lo = pack2(cs.x - bf_lo(hi), cs.y - bf_hi(hi));
  sts128(addr, __byte_perm(hi, lo, 0x5410), __byte_perm(hi, bb, 0x5410), bb & 0xffffu, 0);
  sts128(addr + 16, __byte_perm(hi, lo, 0x7632), __byte_perm(hi, bb, 0x7632), bb >> 16, 0);
}
constexpr uint32_t ONES = 0x3F803F80u;
__device__ __forceinline__ void ll_store(uint4* p, float a, float b, uint32_t tag) {
  asm volatile("st.relaxed.gpu.global.v4.u32 [%0], {%1,%2,%3,%2};" ::"l"(p), "r"(__float_as_uint(a)), "r"(tag), "r"(__float_as_uint(b)) : "memory");
}
__device__ __forceinline__ uint4 ll_load(const void* p) {
  uint4 v;
  asm volatile("ld.relaxed.gpu.global.v4.u32 {%0,%1,%2,%3}, [%4];" : "=r"(v.x), "=r"(v.y), "=r"(v.z), "=r"(v.w) : "l"(p) : "memory");
  return v;
}
template <int N>
__device__ __forceinline__ void ll_wait(uint4 (&v)[N], const uint4* p, int stride, uint32_t tag) {
  uint32_t bad;
  int it = 0;
  do {
    bad = 0;
#pragma unroll
    for (int m = 0; m < N; m++) v[m] = ll_load(p + m * stride);
#pragma unroll
    for (int m = 0; m < N; m++) bad |= (v[m].y ^ tag) | (v[m].w ^ tag);
  } while (bad && ++it < SPIN_LIMIT);
}
__device__ __forceinline__ void ll_wait2(uint4 (&v)[8], const uint4* p, uint32_t tag) {
  uint32_t bad;
  int it = 0;
  do {
    bad = 0;
#pragma unroll
    for (int m = 0; m < 8; m++) v[m] = ll_load(p + (m >> 1) * 1728 + (m & 1));
#pragma unroll
    for (int m = 0; m < 8; m++) bad |= (v[m].y ^ tag) | (v[m].w ^ tag);
  } while (bad && ++it < SPIN_LIMIT);
}
__device__ __forceinline__ float2 ll_sum4(const uint4* p, uint32_t tag) {
  uint4 v[4];
  ll_wait(v, p, 1728, tag);
  return make_float2((__uint_as_float(v[0].x) + __uint_as_float(v[1].x)) + (__uint_as_float(v[2].x) + __uint_as_float(v[3].x)),
                     (__uint_as_float(v[0].z) + __uint_as_float(v[1].z)) + (__uint_as_float(v[2].z) + __uint_as_float(v[3].z)));
}
__device__ __forceinline__ void poll_flag(const uint32_t* f, int bit, uint32_t& mask, uint32_t epoch) {
  while (!(mask >> bit & 1)) {
    mask = __ballot_sync(0xffffffffu, ld_acq(f) == epoch);
    fence_async_global();
  }
}
template <bool PHI>
__device__ __forceinline__ void ln_pair(const float* z, const float (&a)[2], const float (&a2)[2], uint32_t* o) {
#pragma unroll
  for (int e = 0; e < 4; e++) {
    const int hh = e & 1;
    o[e] = PHI ? pack2(phi(z[2 * e], a[hh], a2[hh]), phi(z[2 * e + 1], a[hh], a2[hh])) : pack2(z[2 * e] * a[hh], z[2 * e + 1] * a[hh]);
  }
}

__global__ void __cluster_dims__(2, 1, 1) __launch_bounds__(384, 1)
fused_block_kernel(const __grid_constant__ Maps maps, const __nv_bfloat16* __restrict__ x, const __nv_bfloat16* __restrict__ wqkv,
                   const __nv_bfloat16* __restrict__ wo, const __nv_bfloat16* __restrict__ w1,
                   const __nv_bfloat16* __restrict__ b1, const __nv_bfloat16* __restrict__ w2,
                   const __nv_bfloat16* __restrict__ b2, __nv_bfloat16* __restrict__ out) {
  extern __shared__ __align__(1024) uint8_t smem_raw[];
  const uint32_t sb = (uint32_t)__cvta_generic_to_shared(smem_raw);
  const uint32_t bars = sb + OFF_BAR;
  const int warp = __shfl_sync(0xffffffffu, threadIdx.x >> 5, 0);
  const int lane = threadIdx.x & 31;
  if (warp < 3 && elect_one()) asm volatile("prefetch.tensormap [%0];" ::"l"(&maps.m[warp]) : "memory");

  const int cl = blockIdx.x >> 1, q = blockIdx.x & 1;
  const int u7 = ((cl - 36) * 37) >> 8;
  const int oct = cl < 4 ? 0 : cl < 36 ? 1 + 2 * ((cl - 4) & 7) : 2 + 2 * (cl - 36 - 7 * u7);
  const int u4 = cl < 4 ? cl : cl < 36 ? (cl - 4) >> 3 : u7;
  const int i = 2 * (oct & 7) + (u4 >> 1), p = 2 * (oct >> 3) + (u4 & 1);
  const int j = 2 * p + q;
  auto col_f = [](int jj) { return 160 * (jj >> 1) + 16 * (jj & 2) + 64 * (jj & 1); };
  auto col_r = [](int jj) { return 160 * (jj >> 1) + 128 - 64 * (jj & 2) + 16 * (jj & 1); };
  const int cF = col_f(j), cR = col_r(j), role = q ^ (p & 1);

  auto load_kv = [&](int s, int slot) {
    const uint32_t dst = sb + OFF_RING + slot * 12288, bar = bars + 8 * (RF + slot);
    mbar_expect(bar, 10240);
    tma3d(dst, &maps.m[M_KVF], bar, cF, 32 * s, 1);
    tma2d(dst + 8192, &maps.m[M_KVH], bar, 640 + 640 * role + cR - 16 * q, 32 * s);
  };
  auto load_x = [&](int c, int b, int slot) {
    mbar_expect(bars + 8 * (FX + b), 16384);
    tma2d(sb + slot * 16384, &maps.m[M_X], bars + 8 * (FX + b), 64 * c, 128 * i);
    tma2d(sb + slot * 16384 + 8192, &maps.m[M_X], bars + 8 * (FX + b), 64 * c, 128 * i + 64);
  };
  auto load_x_pair = [&](int c) {
    mbar_expect(bars + 8 * (FX + c), 16384);
    tma2d_pair(sb + c * 16384 + q * 8192, &maps.m[M_X], bars + 8 * (FX + c), 64 * c, 128 * i + 64 * q);
  };

  auto bar_init = [&](int n) { asm volatile("mbarrier.init.shared::cta.b64 [%0], 8;" ::"r"(bars + 8 * n) : "memory"); };
  TC(tc0);
  if (elect_one()) {
    if (warp == 8 || warp < 5) {
      const int n0 = warp == 8 ? RF : 1 + 5 * warp;
#pragma unroll
      for (int n = 0; n < 5; n++) bar_init(n0 + n);
      asm volatile("fence.mbarrier_init.release.cluster;" ::: "memory");
    }
    if (warp == 8) {
      bar_init(FX);
      load_x(0, 0, 0);
      load_kv(0, 0);
      load_kv(1, 1);
      bar_init(ST1);
    }
  }
  __syncwarp();
  TC(tc1);
  asm volatile("barrier.cluster.arrive.relaxed.aligned;" ::: "memory");

  if (warp >= 8) {
    TC(tc2);
    asm volatile("barrier.cluster.wait.aligned;" ::: "memory");
    TC(tc3);
    if (warp == 8 && elect_one()) {
      load_x_pair(1);
      load_kv(2, 2);
      load_kv(3, 3);
      load_x_pair(2);
      load_kv(4, 4);
      load_x_pair(3);
      load_x_pair(4);
    }
    __syncwarp();
    if (warp == 8) { TL(40); }
    asm volatile("setmaxnreg.dec.sync.aligned.u32 88;");
    if (warp == 8) {
      TS(41, tc0); TS(42, tc1); TS(43, tc2); TS(19, tc3);
      uint32_t ph = 0;
#pragma unroll 1
      for (int s = 5, slot = 0; s < 20; s++) {
        mbar_wait(bars + 8 * (RE + slot), ph);
        if (elect_one()) {
          load_kv(s, slot);
          if (s < 10) load_x_pair(s);
          else if (s < 18) asm volatile("prefetch.tensormap [%0];" ::"l"(&maps.m[s - 7]) : "memory");
        }
        if (++slot == 5) { slot = 0; ph ^= 1; }
      }
#pragma unroll 1
      for (int t = 0, slot = 0; t < 10; t++) {
        mbar_wait(bars + 8 * (RE + slot), ph);
        if (elect_one()) {
          const uint32_t dst = sb + OFF_RING + slot * 12288, bar = bars + 8 * (RF + slot);
          const int k0 = 64 * (t < 7 ? t + 3 : t - 7);
          mbar_expect(bar, 10240);
          tma3d(dst, &maps.m[M_Q2], bar, 0, k0, 5 * p + 3 * q);
          tma2d(dst + 8192, &maps.m[M_QR], bar, 80 * j + 64 - 64 * q, k0);
          if (t >= 6 && t < 9) load_x(t - 6, t + 4, t - 2);
        }
        if (++slot == 5) { slot = 0; ph ^= 1; }
      }
#pragma unroll 1
      for (int n = 0; n < 32; n += 4) {
        mbar_wait(bars + 8 * (RE + ((0x44321110u >> n) & 15)), 1);
        if (n >= 8) mbar_wait(bars + 8 * (FWO + ((0x71654320u >> (n - 8)) & 7)));
        const int t = (0x71654320u >> n) & 7, k0 = 80 * (t == 0 ? j : t - (t <= j));
        if (elect_one()) {
          const uint32_t dst = sb + 10 * PAGE + (t < 2 ? t ^ 1 : t) * 15360, bar = bars + 8 * (FWO + t);
          mbar_expect(bar, 12800);
          tma3d(dst, &maps.m[M_WO2], bar, 0, k0, cF >> 5);
          tma2d(dst + 10240, &maps.m[M_WOR], bar, cR, k0);
        }
      }
#pragma unroll 1
      for (int t = 0; t < 8; t++) {
        const uint32_t wb = bars + 8 * (t == 0 ? FWO + 1 : t < 5 ? DW + 2 * t - 1 : DF + t - 5);
        const int jj = t == 0 ? j : t - (t <= j);
        mbar_wait(wb);
        if (t) mbar_wait(wb + 64);
        if (elect_one()) {
          const uint32_t dst = sb + (7 + 3 * (t < 5 ? t : t - 5)) * PAGE, bar = bars + 8 * (FW1 + t);
          mbar_expect(bar, 30720);
          tma3d(dst, &maps.m[M_W1], bar, 0, col_f(jj), 3 * j);
          tma3d(dst + 24576, &maps.m[M_W1R], bar, 0, col_r(jj), 3 * j);
        }
      }
#pragma unroll 1
      for (int t = 0; t < 12; t++) {
        const int t6 = t < 6 ? t : t - 6;
        const uint32_t wb = bars + 8 * (t < 6 ? DF + ((0x776544 >> (4 * t)) & 7) : DG + t6);
        const int uu = (0xA95024 >> (2 * t)) & 3, n = (0x924900 >> (2 * t)) & 3;
        const int k0 = 192 * (t < 3 ? j : 2 * (n + (n >= p)) + q) + 64 * uu;
        const uint32_t dst = sb + OFF_W2 + ((0x321045 >> (4 * t6)) & 7) * 24576, bar = bars + 8 * (FW2 + t);
        mbar_wait(wb);
        mbar_wait(wb + (t < 6 ? 64 : 96));
        if (elect_one()) {
          mbar_expect(bar, 20480);
          tma2d(dst, &maps.m[M_W2F], bar, cF, k0);
          tma2d(dst + 8192, &maps.m[M_W2F], bar, cF + 64 - 128 * q, k0);
          tma2d(dst + 16384, &maps.m[M_W2H], bar, cR - 16 * q, k0);
        }
      }
    } else {
      uint32_t epoch;
      asm volatile("ld.relaxed.gpu.global.u32 %0, [%1];" : "=r"(epoch) : "l"(&g_epoch) : "memory");
      epoch += 1;
      const int unit = i * 8 + j, hw = warp - 9, ht = hw * 32 + lane;
      const int part = unit & 3, cg = unit >> 2;
      auto colsum = [&](const __nv_bfloat16* wm, int ld, uint4* dst, bool active, bool first) {
        const int r4 = lane >> 3, v8 = lane & 7;
        const __nv_bfloat16* wp = wm + (part * 160 + 4 * hw + r4) * ld + 64 * cg + 8 * v8;
        uint4 v[14];
#pragma unroll
        for (int m = 0; m < 14; m++) {
          v[m] = make_uint4(0, 0, 0, 0);
          if (active && (m < 13 || hw == 0))
            asm volatile("ld.global.nc.v4.u32 {%0,%1,%2,%3}, [%4];" : "=r"(v[m].x), "=r"(v[m].y), "=r"(v[m].z), "=r"(v[m].w) : "l"(wp));
          wp += 12 * ld;
        }
        if (first && elect_one()) {
#pragma unroll 1
          for (int n = 0; n < 50; n += 10) {
#pragma unroll
            for (int e = 0; e < 10; e++) bar_init(32 + 50 * hw + n + e);
          }
          mbar_expect(bars + 8 * (RX + hw), hw == 2 ? 8192 : 10240);
        }
        __syncwarp();
        float d[8];
#pragma unroll
        for (int e = 0; e < 8; e++) d[e] = 0.f;
#pragma unroll
        for (int m = 0; m < 14; m++) {
          d[0] += bf_lo(v[m].x); d[1] += bf_hi(v[m].x); d[2] += bf_lo(v[m].y); d[3] += bf_hi(v[m].y);
          d[4] += bf_lo(v[m].z); d[5] += bf_hi(v[m].z); d[6] += bf_lo(v[m].w); d[7] += bf_hi(v[m].w);
        }
#pragma unroll 1
        for (int o = 8; o < 32; o <<= 1) {
#pragma unroll
          for (int e = 0; e < 8; e++) d[e] += __shfl_xor_sync(0xffffffffu, d[e], o);
        }
        if (r4 & 2) { d[0] = d[4]; d[1] = d[5]; d[2] = d[6]; d[3] = d[7]; }
        if (r4 & 1) { d[0] = d[2]; d[1] = d[3]; }
        const uint32_t red = sb + OFF_SCR + lane * 8;
#pragma unroll 1
        for (int h = 0; h < 2; h++) {
          if (hw == h) sts64(red, __float_as_uint(d[0]), __float_as_uint(d[1]));
          named_bar<2, 96>();
          if (hw == h + 1) {
            const float2 a = lds64(red);
            d[0] += a.x;
            d[1] += a.y;
          }
        }
        if (hw == 2 && active) ll_store(dst + part * 1728 + 32 * cg + 4 * v8 + r4, d[0], d[1], epoch);
      };
      if (part >= 2) mbar_wait_wd(bars + 8 * (FX + 2 * part - 4));
#pragma unroll 1
      for (int pass = 0; pass < 2; pass++) {
        colsum(pass ? w1 : wqkv, pass ? 1536 : 1920, g_cs + 960 * pass, cg < (pass ? 24 : 30), !pass);
        if (pass) break;
        if (hw == 2) {
          TL(8);
          mbar_wait_wd(bars + 8 * ST1);
          if (lane < 2) {
            const uint32_t nb = lane ? 15360 : 6400;
            l2_prefetch(reinterpret_cast<const uint8_t*>(lane ? w2 : wo) + blockIdx.x * nb, nb);
          }
          uint4 v[4];
          ll_wait(v, g_ln1 + 128 * i + lane, 32, epoch);
#pragma unroll
          for (int m = 0; m < 4; m++) sts64(sb + OFF_LN1 + (lane + 32 * m) * 8, v[m].x, v[m].z);
          TL(10);
        } else if (ht < 60) {
          const int n = 4 * ht;
          int col;
          if (n < 160) col = n + (n < 64 ? 640 + cF : n < 128 ? 1216 + cF : 512 + 640 * role + cR - 16 * q);
          else col = 80 * j + n - 160 + (q ? (n < 224 ? 16 : -64) : 0);
          mbar_wait(bars + 8 * (FX + 7));
          uint4 v[8];
          ll_wait2(v, g_cs + (col >> 1), epoch);
#pragma unroll
          for (int e = 0; e < 2; e++)
            rk1_store(sb + OFF_RK1 + n * 16 + 32 * e,
                      make_float2((__uint_as_float(v[e].x) + __uint_as_float(v[2 + e].x)) + (__uint_as_float(v[4 + e].x) + __uint_as_float(v[6 + e].x)),
                                  (__uint_as_float(v[e].z) + __uint_as_float(v[2 + e].z)) + (__uint_as_float(v[4 + e].z) + __uint_as_float(v[6 + e].z))), 0);
        }
        fence_async_smem();
        __syncwarp();
        mbar_arrive_if0(lane, bars + 8 * SIDE, hw == 2 ? 2 : 3);
        if (hw == 0) TL(11);
        mbar_wait_wd(bars + 8 * SIDE);
      }
      {
        mbar_wait_wd(bars + 8 * (hw == 2 ? ZK : RKV));
        if (hw == 2) {
#pragma unroll 1
          for (int m = 0; m < 30; m++) sts128(sb + OFF_KVB + (m * 32 + lane) * 16, 0, 0, 0, 0);
        } else if (ht < 60) {
          const float2* src = g_kv1 + (j * 16 + i) * 1024 + ht;
          const uint32_t tag = epoch & 15;
          float sa, sc;
          uint32_t bad;
          int it = 0;
          do {
            uint32_t a[16], b[16];
#pragma unroll
            for (int m = 0; m < 16; m++)
              asm volatile("ld.relaxed.gpu.global.v2.u32 {%0,%1}, [%2];" : "=r"(a[m]), "=r"(b[m]) : "l"(src + m * 64) : "memory");
            sa = sc = 0.f;
            bad = 0;
#pragma unroll
            for (int m = 0; m < 16; m++) {
              bad |= (a[m] ^ tag) | (b[m] ^ tag);
              sa += __uint_as_float(a[m]);
              sc += __uint_as_float(b[m]);
            }
          } while ((bad & 15) && ++it < SPIN_LIMIT);
          asm volatile("st.relaxed.gpu.global.v2.u32 [%0], {%1,%2};" ::"l"(g_kv2 + j * 960 + i * 60 + ht), "r"(pack2(sa, sc)), "r"(epoch) : "memory");
        }
        if (hw == 0) TL(5);
        named_bar<2, 96>();
        {
          uint4 v[5];
          ll_wait(v, reinterpret_cast<const uint4*>(g_kv2 + j * 960) + ht, 96, epoch);
          if (hw == 0) TL(6);
          const int d0 = ht / 6, part = ht - 6 * d0;
#pragma unroll
          for (int m = 0; m < 5; m++) {
            const int d = d0 + 16 * m, head = (d * 205) >> 12, n = 20 * head + 4 * part;
            const uint32_t a = sb + OFF_KVB + d * 16;
            const uint32_t z = head & 1 ? v[m].x << 16 : v[m].x & 0xffffu;
            if (part < 5) sts64(a + (n >> 3) * 1280 + (n & 7) * 2, v[m].x, v[m].z);
            else sts128(a + (10 + (head >> 1)) * 1280, z, z, z, z);
          }
        }
        fence_async_smem();
        __syncwarp();
        mbar_arrive_if0(lane, bars + 8 * KVB, hw == 2 ? 2 : 3);
        if (hw == 0) TL(7);
      }

      if (hw == 2) {
#pragma unroll 1
        for (int n = lane; n < 96; n += 32) {
          const uint32_t bb = *reinterpret_cast<const uint32_t*>(b1 + 192 * j + 2 * n);
          if (n < 40) {
            const uint32_t b = *reinterpret_cast<const uint32_t*>(b2 + (n < 32 ? cF + 2 * n : cR + 2 * n - 64));
            sts64(sb + OFF_B2 + n * 8, b << 16, b & 0xffff0000u);
          }
          rk1_store(sb + OFF_RK1 + n * 32, ll_sum4(g_cs + 960 + 96 * j + n, epoch), bb);
        }
        fence_async_smem();
        __syncwarp();
        mbar_arrive_if0(lane, bars + 8 * SIDE2, 8);
        TL(18);
#pragma unroll 1
        for (int s = 0; s < 2; s++) {
          uint8_t* dst = g_act + ((64 + 2 * i + s) * 8 + j) * 24576;
          mbar_wait_wd(bars + 8 * (AF + 12 * s + 1));
          if (lane == 0) bulk_store(dst + 8192, sb + s * OFF_R1 + 8192, 8192);
          __syncwarp();
          mbar_wait_wd(bars + 8 * (AF + 12 * s + 2));
          if (lane == 0) {
            bulk_store(dst + 16384, sb + s * OFF_R1 + 16384, 8192);
            bulk_commit_wait();
            mbar_arrive(bars + 8 * (SFB + s), 8);
            fence_gpu();
            st_flag(g_flag + (64 + 2 * i + s) * 32 + 8 + j, epoch);
          }
          __syncwarp();
          TL(50 + s);
        }
        mbar_wait_wd(bars + 8 * END);
        if (blockIdx.x == 0 && lane == 0) g_epoch = epoch;
      } else {
        const int s = hw;
#pragma unroll 1
        for (int ph = 0; ph < 3; ph++) {
          uint32_t ab = bars + 8 * (ph < 2 ? AO + 16 * ph + 8 * s : AF + 12 * s);
          const uint32_t bytes = ph < 2 ? 10240 : 8192, base = sb + (ph ? s * OFF_R1 : 0);
          uint8_t* gb = g_act + (ph * 32 + 2 * i + s) * 8 * 24576;
          uint32_t* fl = g_flag + (ph * 32 + 2 * i + s) * 32;
          mbar_wait(ab);
          if (ph == 0 && s == 1) mbar_wait(bars + 8 * SO);
          if (elect_one()) {
            bulk_store(gb + j * 24576, sb + s * (ph ? OFF_R1 : PAGE), bytes);
            bulk_commit_wait();
            if (ph == 0) mbar_arrive(bars + 8 * (SO + s), 8);
            fence_gpu();
            st_flag(fl + j, epoch);
          }
          __syncwarp();
          TL(44 + 2 * ph + s);
          uint32_t slots;
          uint64_t waits;
          if (ph == 0) {
            slots = s ? 02165432u : 00165432u;
            waits = s ? 011060504030201ull : 000101010101010ull;
            if (s == 0) mbar_wait(bars + 8 * (SO + 1));
          } else if (ph == 1) {
            slots = 01021021u;
            waits = 024232221201717ull + (s ? 010101010100000ull : 0);
          } else {
            slots = 0321032103u;
            waits = 0474645444342414027ull + (s ? 0141414141414141410ull : 0);
            ab += 16;
          }
          uint32_t mask = 0;
#pragma unroll 1
          for (int r = 0; r < (ph < 2 ? 7 : 9); r++) {
            int cc = r + (r >= j), bit = cc;
            uint32_t off = 0;
            if (ph == 2) {
              const int uu = (r * 11) >> 5, n = r - 3 * uu;
              cc = 2 * (n + (n >= p)) + q;
              bit = cc + (uu ? 8 : 0);
              off = uu * 8192;
              if (r == 2) mbar_wait(bars + 8 * (SFB + s));
            }
            ab += 8;
            mbar_wait(bars + 8 * (DW + ((uint32_t)waits & 63)));
            poll_flag(fl + lane, bit, mask, epoch);
            if (r == 0) TL(52 + 2 * ph + s);
            if (elect_one()) {
              mbar_expect(ab, bytes);
              bulk_load(base + (slots & 7) * bytes, gb + cc * 24576 + off, bytes, ab);
            }
            slots >>= 3;
            waits >>= 6;
          }
        }
      }
    }
  } else {
    uint32_t epoch;
    asm volatile("ld.relaxed.gpu.global.u32 %0, [%1];" : "=r"(epoch) : "l"(&g_epoch) : "memory");
    epoch += 1;
    asm volatile("barrier.cluster.wait.aligned;" ::: "memory");
    TC(tc4);
    const int s = warp >> 2, w = warp & 3, tid = threadIdx.x & 127, c = lane & 3, g = lane >> 2;
    uint32_t sb_peer;
    asm volatile("mapa.shared::cluster.u32 %0, %1, %2;" : "=r"(sb_peer) : "r"(sb), "r"(q ^ 1));
    const int row0 = 128 * i + 64 * s + 16 * w;
    const uint32_t bs8 = bars + 64 * s, bs12 = bars + 96 * s;
    uint32_t pq[20], hp[20];
    {
      float acc[80];
      const Desc dx = mkdesc(s * 512, 0, 16, 1024, 1);
      const int srow = 16 * j + 2 * warp + (lane >> 4);
      float sm = 0.f, sq = 0.f;
#pragma unroll
      for (int st = 0; st < 20; st++) {
        if ((st & 1) == 0 && st <= 4) mbar_wait(bars + 8 * (FX + (st >> 1)));
        mbar_wait(bars + 8 * (RF + st % 5), (st / 5) & 1);
        const Desc da = dx + (st >> 1) * 1024 + (st & 1) * 4, db = mkdesc(0, OFF_RING + (st % 5) * 12288, 4096, 1024, 1);
        wg_fence();
        wgmma_ss<160, 0, 1>(acc, da, db, st != 0);
        wgmma_ss<160, 0, 1>(acc, da + 2, db + 128, 1);
        wg_commit();
        if (st == 0) { TL0(0); TS(38, tc4); TS(62, (uint32_t)tl_gt); }
        if (st == 1) asm volatile("setmaxnreg.inc.sync.aligned.u32 208;");
        if (st >= 2 && st <= 10 && (st & 1) == 0) {
          if (st > 2) {
            mbar_wait(bars + 8 * (FX + st - 2));
            mbar_wait(bars + 8 * (FX + st - 1));
          }
          const float4 u = lds128(sb + (st - 2 + ((lane >> 3) & 1)) * 16384 + srow * 128 + (lane & 7) * 16);
          const float uu[4] = {u.x, u.y, u.z, u.w};
#pragma unroll
          for (int e = 0; e < 4; e++) {
            const float a = bf_lo(__float_as_uint(uu[e])), b = bf_hi(__float_as_uint(uu[e]));
            sm += a + b;
            sq = fmaf(a, a, fmaf(b, b, sq));
          }
        }
        if (st == 11) {
#pragma unroll
          for (int o = 1; o < 16; o <<= 1) {
            sm += __shfl_xor_sync(0xffffffffu, sm, o);
            sq += __shfl_xor_sync(0xffffffffu, sq, o);
          }
          const float mean = sm * (1.f / 640.f);
          const float rstd = rsqrtf(fmaxf(fmaf(-mean, mean, sq * (1.f / 640.f)), 0.f) + 1e-5f);
          if ((lane & 15) == 0) ll_store(g_ln1 + 128 * i + srow, rstd, -mean, epoch);
          mbar_arrive_if0(lane, bars + 8 * ST1, 1);
          TL0(39);
        }
        if (st == 18) {
          const uint32_t xa = sb + (64 * s + 16 * w + (lane & 15)) * 128;
#pragma unroll
          for (int ks = 0; ks < 5; ks++) {
            const int col = ks < 4 ? cF + 16 * ks : cR;
            ldsm4(xa + (col >> 6) * 16384 + (((((col & 63) >> 3) + (lane >> 4)) ^ (lane & 7)) << 4), hp + 4 * ks);
          }
          reg_fence(hp);
          mbar_arrive_remote_if0(lane, sb_peer + OFF_BAR + 8 * PX);
        }
        if (st > 0) {
          wg_wait<1>();
          mbar_arrive_if0(lane, bars + 8 * (RE + (st - 1) % 5), 1);
        }
      }
      TL0(12);
      float accq[40];
      auto q_step = [&](int t) {
        if (t >= 7) mbar_wait(bars + 8 * (FX + 3 + t));
        mbar_wait(bars + 8 * (RF + t % 5), t / 5);
        const Desc da = dx + (t < 7 ? t + 3 : t - 3) * 1024, db = mkdesc(0, OFF_RING + (t % 5) * 12288, 4096, 512, 2);
        wg_fence();
#pragma unroll
        for (int ks = 0; ks < 4; ks++) wgmma_ss<80, 0, 1>(accq, da + 2 * ks, db + 64 * ks, 1);
        wg_commit();
      };
      mbar_wait(bars + 8 * SIDE);
      float a1[2], a2[2];
      uint32_t rk[2];
#pragma unroll
      for (int r = 0; r < 2; r++) {
        const float2 st = lds64(sb + OFF_LN1 + (64 * s + 16 * w + g + 8 * r) * 8);
        a1[r] = st.x;
        a2[r] = st.x * LOG2E;
        rk[r] = rk1_frag(st.y, 0.f, c);
      }
      wg_fence();
      wgmma_rs<160, 0>(acc, rk[0], rk[1], 0, 0, mkdesc(0, OFF_RK1, 0, 128, 0), 1);
      wg_commit();
      wgmma_rs<80, 0>(accq, rk[0], rk[1], 0, 0, mkdesc(0, OFF_RK1 + 2560, 0, 128, 0), 0);
      q_step(0);
      const int hi = lane >> 4;
      const uint32_t rowoff = sb + (64 * s + 16 * w + (lane & 15)) * 16;
      const uint32_t remoff = sb_peer + (64 * s + 16 * w) * 16 + lane * 4;
      auto put_remote = [&](const uint32_t* r, uint32_t a) {
#pragma unroll
        for (int e = 0; e < 4; e++)
          asm volatile("st.async.shared::cluster.mbarrier::complete_tx::bytes.b32 [%0], %1, [%2];"
                       ::"r"(a + (e >> 1) * 2048 + (e & 1) * 128), "r"(r[e]), "r"(sb_peer + OFF_BAR + 8 * RXK) : "memory");
      };
      const int mF = 2 * (p & 1) - q, g0 = 2 * mF + hi;
      const uint32_t ka = rowoff + g0 * 2048;
      mbar_wait(bars + 8 * (RE + 2), 1);
      mbar_wait_cluster(bars + 8 * PX);
      wg_wait<1>();
      reg_fence(acc);
      mbar_arrive_if0(lane, bars + 8 * (RE + 4), 1);
      TL0(1);
      uint32_t r[4], r2[4];
      if (role == 0) {
        ln_pair<true>(acc + 64, a1, a2, r);
        ln_pair<true>(acc + 72, a1, a2, r2);
        put_remote(r, remoff + (q ? 0 : 6 * 2048));
        put_remote(r2, remoff + (q ? 2 * 2048 : 8 * 2048));
      } else {
        ln_pair<false>(acc + 64, a1, a2, r);
        ln_pair<false>(acc + 72, a1, a2, r2);
        const uint32_t a = rowoff + (hi + (q ? 17 : 10)) * 2048;
        stsm4(a, r[0], r[1], r[2], r[3]);
        stsm4(a + 4096, r2[0], r2[1], r2[2], r2[3]);
      }
      q_step(1);
#pragma unroll
      for (int n = 0; n < 4; n++) {
        const int P = n == 0 ? 0 : n == 1 ? 3 : n - 1;
        ln_pair<true>(acc + 8 * P, a1, a2, r);
        ln_pair<false>(acc + 32 + 8 * P, a1, a2, r2);
        if (n < 2 && mF == (n ? 2 : -1)) {
          put_remote(r, remoff + (n ? 0 : 8 * 2048));
          put_remote(r2, remoff + (n ? 10 * 2048 : 19 * 2048));
        } else {
          stsm4(ka + P * 4096, r[0], r[1], r[2], r[3]);
          stsm4(ka + P * 4096 + (g0 + 2 * P > 4 ? 11 * 2048 : 10 * 2048), r2[0], r2[1], r2[2], r2[3]);
        }
        if (n == 0) {
          wg_wait<1>();
          mbar_arrive_if0(lane, bars + 8 * RE, 1);
          mbar_arrive_if0(lane, bars + 8 * ZK, 1);
        }
        if (n == 1) q_step(2);
        if (n == 2) {
          wg_wait<1>();
          mbar_arrive_if0(lane, bars + 8 * (RE + 1), 1);
        }
      }
      sts128(rowoff + 15 * 2048, ONES, ONES, ONES, ONES);
      TL0(2);
      mbar_wait_cluster(bars + 8 * RXK);
      fence_async_smem();
      named_bar<1, 256>();
      TL0(3);
      float kv[24];
      {
        const Desc da = mkdesc(s * 640, 0, 128, 2048, 0), db = da + 1280;
        wg_fence();
#pragma unroll
        for (int kk = 0; kk < 8; kk++) wgmma_ss<48, 1, 1>(kv, da + 16 * kk, db + 16 * kk, kk != 0);
        wg_commit();
      }
      wg_wait<1>();
      mbar_arrive_if0(lane, bars + 8 * (RE + 2), 1);
      q_step(3);
      {
        const uint32_t tag = epoch & 15;
        const uint8_t* gp[2];
        int eb[2], zo[2];
#pragma unroll
        for (int hh = 0; hh < 2; hh++) {
          const int r = 16 * w + g + 8 * hh, d = 40 * s + r, own = (d * 205) >> 10;
          eb[hh] = c - 4 * s - (r < 20 ? 0 : r < 40 ? 10 : 99);
          zo[hh] = c < 2 && r < 40 ? 10 + c - eb[hh] : -1;
          gp[hh] = reinterpret_cast<const uint8_t*>(g_kv1) + (((j * 16 + own) * 16 + i) * 64 + (d - 5 * own) * 12 + eb[hh]) * 8;
        }
        wg_wait<1>();
        reg_fence(kv);
        TL0(4);
#pragma unroll
        for (int hh = 0; hh < 2; hh++) {
#pragma unroll
          for (int tt = 0; tt < 7; tt++) {
            const float v0 = tt < 6 ? kv[4 * tt + 2 * hh] : s ? kv[2 * hh] : kv[20 + 2 * hh];
            const float v1 = tt < 6 ? kv[4 * tt + 2 * hh + 1] : v0;
            asm volatile("{.reg .pred p; .reg .b32 a, b; setp.lt.u32 p, %3, %4; lop3.b32 a, %1, %5, 15, 0xD8; lop3.b32 b, %2, %5, 15, 0xD8;"
                         "@p st.relaxed.gpu.global.v2.u32 [%0], {a, b};}"
                         ::"l"(tt < 6 ? gp[hh] + 32 * tt : gp[hh] + 8 * zo[hh]), "r"(__float_as_uint(v0)), "r"(__float_as_uint(v1)),
                         "r"(tt < 6 ? eb[hh] + 4 * tt : zo[hh]), "r"(tt < 6 ? 10 : 64), "r"(tag) : "memory");
          }
        }
      }
      mbar_arrive_if0(lane, bars + 8 * RKV, 1);
      TL0(9);
#pragma unroll
      for (int t = 4; t < 10; t++) {
        q_step(t);
        wg_wait<1>();
        mbar_arrive_if0(lane, bars + 8 * (RE + (t - 1) % 5), 1);
      }
      wg_wait<0>();
      reg_fence(accq);
      mbar_arrive_if0(lane, bars + 8 * (RE + 4), 1);
      TL0(13);
#pragma unroll
      for (int P = 0; P < 5; P++) ln_pair<true>(accq + 8 * P, a1, a2, pq + 4 * P);
      reg_fence(pq);
      TL0(14);
    }
    const uint32_t rs = sb + s * OFF_R1;
    const uint32_t stoff = (lane >> 4) * 1024 + (16 * w + (lane & 15)) * 16;
    const Desc drs = mkdesc(s * (OFF_R1 / 16), 0, 1024, 128, 0);
    float accg[80];
    {
      {
        float o[48];
        wg_fence();
        mbar_wait(bars + 8 * (s ? OM : KVB));
        TL0(15);
#pragma unroll
        for (int ks = 0; ks < 5; ks++)
          wgmma_rs<96, 1>(o, pq[4 * ks], pq[4 * ks + 1], pq[4 * ks + 2], pq[4 * ks + 3], mkdesc(ks < 4 ? 16 * q : -64 * q, OFF_KVB + 256 * ks, 128, 1280, 0), ks != 0);
        wg_commit();
        mbar_arrive_if0(lane | s, bars + 8 * OM, 2);
        wg_wait<0>();
        reg_fence(o);
        float inv[2][4];
#pragma unroll
        for (int hh = 0; hh < 2; hh++)
#pragma unroll
          for (int h = 0; h < 4; h++) inv[hh][h] = rcp(o[40 + 4 * (h >> 1) + 2 * hh + (h & 1)] + 1e-6f);
        uint32_t r[4];
#pragma unroll
        for (int t = 0; t < 10; t++) {
#pragma unroll
          for (int hh = 0; hh < 2; hh++) {
            const float f = t == 2 ? (c < 2 ? inv[hh][0] : inv[hh][1]) : t == 7 ? (c < 2 ? inv[hh][2] : inv[hh][3]) : inv[hh][(8 * t) / 20];
            r[2 * (t & 1) + hh] = pack2(o[4 * t + 2 * hh] * f, o[4 * t + 2 * hh + 1] * f);
          }
          if (t & 1) stsm4(sb + s * PAGE + stoff + (t >> 1) * 2048, r[0], r[1], r[2], r[3]);
        }
        fence_async_smem();
        __syncwarp();
        mbar_arrive_if0(lane, bs8 + 8 * AO, 2);
        TLW(16 + s);
      }
      float acc[40];
#pragma unroll
      for (int r = 0; r < 20; r++) { acc[2 * r] = bf_lo(hp[r]); acc[2 * r + 1] = bf_hi(hp[r]); }
      reg_fence(acc);
#pragma unroll
      for (int t = 0; t < 8; t++) {
        mbar_wait(bars + 8 * (FWO + t));
        mbar_wait(bs8 + 8 * (AO + t));
        if (t == 1) TLW(20 + s);
        const Desc da = mkdesc(t == 0 ? s * 640 : t == 7 ? s * 1280 : 0, (t == 0 || t == 7 ? 0 : t < 6 ? t + 1 : 1) * PAGE, 1024, 128, 0);
        const Desc db = mkdesc(0, 10 * PAGE + (t < 2 ? t ^ 1 : t) * 15360, 5120, 512, 2);
        wg_fence();
#pragma unroll
        for (int ks = 0; ks < 5; ks++) wgmma_ss<80, 0, 1>(acc, da + 128 * ks, db + 64 * ks, 1);
        wg_commit();
        if (t == 0) wg_wait<0>();
        else if (t > 1) wg_wait<1>();
        if (t != 1) mbar_arrive_if0(lane, bs8 + 8 * (DW + (t ? t - 1 : 0)), 2);
      }
      wg_wait<0>();
      reg_fence(acc);
      mbar_arrive_if0(lane, bs8 + 8 * (DW + 7), 2);
      TLW(22 + s);
#pragma unroll
      for (int r = 0; r < 20; r++) hp[r] = pack2(acc[2 * r], acc[2 * r + 1]);
      mbar_wait(bs8 + 8 * (DW + 7));
#pragma unroll
      for (int ks = 0; ks < 5; ks++)
        stsm4(rs + stoff + ks * 2048, hp[4 * ks], hp[4 * ks + 1], hp[4 * ks + 2], hp[4 * ks + 3]);
      fence_async_smem();
      __syncwarp();
      mbar_arrive_if0(lane, bs8 + 8 * AH, 2);
      reg_fence(hp);
      TLW(24 + s);
    }
    float accf[96];
    uint4 hs[4];
    const uint4* hsp = g_hstat + ((2 * i + s) * 8 + 2 * c) * 64 + 16 * w + g;
    uint32_t rk[2];
    float3 gk[2];
#pragma unroll
    for (int t = 0; t < 8; t++) {
      mbar_wait(bars + 8 * (FW1 + t));
      mbar_wait(bs8 + 8 * (AH + t));
      if (t == 1) TLW(26 + s);
      const Desc da = drs + (t % 3) * (PAGE / 16), db = mkdesc(0, (7 + 3 * (t % 5)) * PAGE, 8192, 1024, 1);
      wg_fence();
#pragma unroll
      for (int ks = 0; ks < 4; ks++) wgmma_ss<192, 0, 1>(accf, da + 128 * ks, db + 128 * ks, (t | ks) != 0);
      wgmma_ss<192, 0, 1>(accf, da + 512, mkdesc(0, (7 + 3 * (t % 5)) * PAGE + 24576, 2048, 1024, 1), 1);
      if (t == 7) wgmma_rs<192, 0>(accf, rk[0], rk[1], 0, 0, mkdesc(0, OFF_RK1, 0, 128, 0), 1);
      wg_commit();
      if (t == 0) {
        float sm[2] = {0.f, 0.f}, sq[2] = {0.f, 0.f};
        mbar_wait(bars + 8 * SIDE2);
#pragma unroll
        for (int m = 0; m < 10; m++) {
          const float2 b = lds64(sb + OFF_B2 + (8 * m + 2 * c) * 4);
#pragma unroll
          for (int hh = 0; hh < 2; hh++) {
            const float h0 = bf_lo(hp[2 * m + hh]), h1 = bf_hi(hp[2 * m + hh]);
            sm[hh] += h0 + h1;
            sq[hh] = fmaf(h0, h0, fmaf(h1, h1, sq[hh]));
            const float v0 = b.x + h0, v1 = b.y + h1;
            const int e = 4 * m + 2 * hh;
            if (m < 8) { accg[e] = v0; accg[e + 1] = v1; accg[32 + e] = 0.f; accg[33 + e] = 0.f; }
            else { accg[e + 32] = q ? 0.f : v0; accg[e + 33] = q ? 0.f : v1; accg[e + 40] = q ? v0 : 0.f; accg[e + 41] = q ? v1 : 0.f; }
          }
        }
        reg_fence(accg);
#pragma unroll
        for (int o = 1; o < 4; o <<= 1) {
#pragma unroll
          for (int hh = 0; hh < 2; hh++) {
            sm[hh] += __shfl_xor_sync(0xffffffffu, sm[hh], o);
            sq[hh] += __shfl_xor_sync(0xffffffffu, sq[hh], o);
          }
        }
        if (c < 2) ll_store(g_hstat + ((2 * i + s) * 8 + j) * 64 + 16 * w + g + 8 * c, c ? sm[1] : sm[0], c ? sq[1] : sq[0], epoch);
        wg_wait<0>();
      } else if (t > 1) wg_wait<1>();
      if (t != 1) mbar_arrive_if0(lane, bs8 + 8 * (DF + (t ? t - 1 : 0)), 2);
      if (t == 4) {
#pragma unroll
        for (int m = 0; m < 4; m++) hs[m] = ll_load(hsp + (m >> 1) * 64 + 8 * (m & 1));
      }
      if (t == 6) {
        while (((hs[0].y ^ epoch) | (hs[0].w ^ epoch) | (hs[1].y ^ epoch) | (hs[1].w ^ epoch) | (hs[2].y ^ epoch) | (hs[2].w ^ epoch) |
                (hs[3].y ^ epoch) | (hs[3].w ^ epoch)) != 0) {
#pragma unroll
          for (int m = 0; m < 4; m++) hs[m] = ll_load(hsp + (m >> 1) * 64 + 8 * (m & 1));
        }
        __syncwarp();
#pragma unroll
        for (int hh = 0; hh < 2; hh++) {
          float sm = __uint_as_float(hs[hh].x) + __uint_as_float(hs[2 + hh].x), sq = __uint_as_float(hs[hh].z) + __uint_as_float(hs[2 + hh].z);
#pragma unroll
          for (int o = 1; o < 4; o <<= 1) {
            sm += __shfl_xor_sync(0xffffffffu, sm, o);
            sq += __shfl_xor_sync(0xffffffffu, sq, o);
          }
          const float mean = sm * (1.f / 640.f), var = fmaxf(fmaf(-mean, mean, sq * (1.f / 640.f)), 0.f) + 1e-5f;
          const float a = rsqrtf(var);
          rk[hh] = rk1_frag(-mean, var * a, c);
          gk[hh] = make_float3(0.7978845608028654f * a, 0.7978845608028654f * 0.044715f * a * a * a, 0.5f * a);
        }
      }
    }
    wg_wait<0>();
    reg_fence(accf);
    mbar_arrive_if0(lane, bs8 + 8 * (DF + 7), 2);
    TLW(28 + s);
    auto g_step = [&](int t, int slot) {
      mbar_wait(bars + 8 * (FW2 + t));
      mbar_wait(bs12 + 8 * (AF + t));
      if (t == 3) TLW(32 + s);
      const Desc da = mkdesc(drs.base + (t & 3) * 512, 0, 1024, 128, 0), db = mkdesc(slot * 1536, OFF_W2, 8192, 1024, 1);
      wg_fence();
#pragma unroll
      for (int ks = 0; ks < 4; ks++) wgmma_ss<160, 0, 1>(accg, da + 128 * ks, db + 128 * ks, 1);
      wg_commit();
    };
#pragma unroll 1
    for (int t = 0; t < 3; t++) {
      uint32_t r[16];
#pragma unroll
      for (int e = 0; e < 16; e++) r[e] = pack2(gelu(accf[2 * e], gk[e & 1]), gelu(accf[2 * e + 1], gk[e & 1]));
      mbar_wait(bs8 + 8 * (DF + 7));
#pragma unroll
      for (int n = 0; n < 4; n++) stsm4(rs + stoff + t * 8192 + n * 2048, r[4 * n], r[4 * n + 1], r[4 * n + 2], r[4 * n + 3]);
      fence_async_smem();
      __syncwarp();
      mbar_arrive_if0(lane, bs12 + 8 * (AF + t), 2);
#pragma unroll
      for (int e = 0; e < 64; e++) accf[e] = accf[e + 32];
      g_step(t, (0x045 >> (4 * t)) & 7);
      wg_wait<1>();
      mbar_arrive_if0(lane | (t == 0), bs12 + 8 * (DG + t - 1), 2);
    }
    TLW(30 + s);
    wg_wait<0>();
    mbar_arrive_if0(lane, bs12 + 8 * (DG + 2), 2);
#pragma unroll
    for (int t = 3; t < 12; t++) {
      g_step(t, (0x321045 >> (4 * (t % 6))) & 7);
      if (t > 3) {
        wg_wait<1>();
        mbar_arrive_if0(lane, bs12 + 8 * (DG + t - 1), 2);
        if (t == 7) mbar_arrive_remote_if0(lane, sb_peer + OFF_BAR + 8 * PF);
      }
    }
    mbar_wait_cluster(bars + 8 * PF);
    wg_wait<0>();
    reg_fence(accg);
    mbar_arrive_if0(lane, bs12 + 8 * (DG + 11), 2);
    TLW(34 + s);
    {
      const uint32_t buf = OFF_W2 + 5 * 24576 + s * PAGE + tid * 16;
#pragma unroll
      for (int e = 0; e < 8; e++) {
        const float a = accg[64 + e], b = accg[72 + e];
        accg[64 + e] = q ? a : b;
        accg[72 + e] = q ? b : a;
      }
#pragma unroll
      for (int m = 0; m < 5; m++) {
        const float* a = accg + 32 + 8 * m;
        asm volatile("st.async.shared::cluster.mbarrier::complete_tx::bytes.v4.b32 [%0], {%1,%2,%3,%4}, [%5];"
                     ::"r"(sb_peer + buf + m * 2048), "r"(pack2(a[0], a[1])), "r"(pack2(a[2], a[3])), "r"(pack2(a[4], a[5])),
                     "r"(pack2(a[6], a[7])), "r"(sb_peer + OFF_BAR + 8 * (RX + s)) : "memory");
      }
      TLW(58 + s);
      mbar_wait(bs12 + 8 * (DG + 11));
      mbar_wait_cluster(bars + 8 * (RX + s));
      TLW(60 + s);
      float4 rx[5];
#pragma unroll
      for (int m = 0; m < 5; m++) rx[m] = lds128(sb + buf + m * 2048);
      const uint32_t stg = rs + w * 2816;
      const uint32_t sa = stg + (lane & 15) * 176 + (lane >> 4) * 16;
#pragma unroll
      for (int ks = 0; ks < 5; ks++) {
        const uint32_t u[4] = {__float_as_uint(rx[ks].x), __float_as_uint(rx[ks].y), __float_as_uint(rx[ks].z), __float_as_uint(rx[ks].w)};
        const float* a = accg + (ks < 4 ? 8 * ks : 72);
        stsm4(sa + ks * 32, pack2(a[0] + bf_lo(u[0]), a[1] + bf_hi(u[0])), pack2(a[2] + bf_lo(u[1]), a[3] + bf_hi(u[1])),
              pack2(a[4] + bf_lo(u[2]), a[5] + bf_hi(u[2])), pack2(a[6] + bf_lo(u[3]), a[7] + bf_hi(u[3])));
      }
      __syncwarp();
#pragma unroll
      for (int m = 0; m < 4; m++) rx[m] = lds128(stg + (4 * m + (lane >> 3)) * 176 + (lane & 7) * 16);
      rx[4] = lds128(stg + (lane >> 1) * 176 + 128 + (lane & 1) * 16);
      __nv_bfloat16* outp = out + (row0 + (lane >> 3)) * 640 + cF + (lane & 7) * 8;
#pragma unroll
      for (int m = 0; m < 4; m++) *reinterpret_cast<float4*>(outp + m * 4 * 640) = rx[m];
      *reinterpret_cast<float4*>(out + (row0 + (lane >> 1)) * 640 + cR + (lane & 1) * 8) = rx[4];
    }
    mbar_arrive_if0(lane, bars + 8 * END, 1);
    TLW(36 + s);
  }
}

typedef CUresult (*EncodeFn)(CUtensorMap*, CUtensorMapDataType, cuuint32_t, void*, const cuuint64_t*, const cuuint64_t*,
                             const cuuint32_t*, const cuuint32_t*, CUtensorMapInterleave, CUtensorMapSwizzle,
                             CUtensorMapL2promotion, CUtensorMapFloatOOBfill);

void make_map(EncodeFn enc, CUtensorMap* tm, const void* base, int rows, int cols, int box_rows, int box_cols, int group, int natom,
              CUtensorMapSwizzle sw) {
  const cuuint64_t dims[3] = {(cuuint64_t)(natom ? group : cols), (cuuint64_t)rows, (cuuint64_t)(cols / group)};
  const cuuint64_t strides[2] = {(cuuint64_t)cols * 2, (cuuint64_t)group * 2};
  const cuuint32_t box[3] = {(cuuint32_t)box_cols, (cuuint32_t)box_rows, (cuuint32_t)natom}, es[3] = {1, 1, 1};
  enc(tm, CU_TENSOR_MAP_DATA_TYPE_BFLOAT16, natom ? 3 : 2, const_cast<void*>(base), dims, strides, box, es,
      CU_TENSOR_MAP_INTERLEAVE_NONE, sw, CU_TENSOR_MAP_L2_PROMOTION_L2_128B, CU_TENSOR_MAP_FLOAT_OOB_FILL_NONE);
}

}

extern "C" void kernel_launch(void* const* d_in, const int* in_sizes, int n_in, void* d_out, int out_size) {
  const __nv_bfloat16* x = (const __nv_bfloat16*)d_in[0];
  const __nv_bfloat16* wqkv = (const __nv_bfloat16*)d_in[1];
  const __nv_bfloat16* wo = (const __nv_bfloat16*)d_in[2];
  const __nv_bfloat16* w1 = (const __nv_bfloat16*)d_in[4];
  const __nv_bfloat16* b1 = (const __nv_bfloat16*)d_in[5];
  const __nv_bfloat16* w2 = (const __nv_bfloat16*)d_in[6];
  const __nv_bfloat16* b2 = (const __nv_bfloat16*)d_in[7];

  void* fn = nullptr;
  cudaDriverEntryPointQueryResult qr;
  cudaGetDriverEntryPoint("cuTensorMapEncodeTiled", &fn, cudaEnableDefault, &qr);
  EncodeFn enc = (EncodeFn)fn;
  const CUtensorMapSwizzle S128 = CU_TENSOR_MAP_SWIZZLE_128B, S64 = CU_TENSOR_MAP_SWIZZLE_64B;
  Maps maps;
  make_map(enc, &maps.m[M_X], x, 2048, 640, 64, 64, 64, 0, S128);
  make_map(enc, &maps.m[M_KVF], wqkv, 640, 1920, 32, 64, 640, 2, S128);
  make_map(enc, &maps.m[M_KVH], wqkv, 640, 1920, 32, 32, 64, 0, S128);
  make_map(enc, &maps.m[M_Q2], wqkv, 640, 1920, 64, 32, 32, 2, S64);
  make_map(enc, &maps.m[M_QR], wqkv, 640, 1920, 64, 16, 64, 0, S64);
  make_map(enc, &maps.m[M_WO2], wo, 640, 640, 80, 32, 32, 2, S64);
  make_map(enc, &maps.m[M_WOR], wo, 640, 640, 80, 16, 64, 0, S64);
  make_map(enc, &maps.m[M_W1], w1, 640, 1536, 64, 64, 64, 3, S128);
  make_map(enc, &maps.m[M_W1R], w1, 640, 1536, 16, 64, 64, 3, S128);
  make_map(enc, &maps.m[M_W2F], w2, 1536, 640, 64, 64, 64, 0, S128);
  make_map(enc, &maps.m[M_W2H], w2, 1536, 640, 64, 32, 64, 0, S128);
  cudaFuncSetAttribute(fused_block_kernel, cudaFuncAttributeMaxDynamicSharedMemorySize, SMEM_BYTES);
  fused_block_kernel<<<128, 384, SMEM_BYTES>>>(maps, x, wqkv, wo, w1, b1, w2, b2, (__nv_bfloat16*)d_out);
}
```

```cpp
#include <cuda_runtime.h>
#include <cuda_bf16.h>
#include <cuda.h>
#include <stdint.h>

namespace {

struct Desc { uint32_t base, off, hi; };
__device__ __forceinline__ Desc operator+(Desc d, uint32_t o) { return Desc{d.base, d.off + o, d.hi}; }
template <int TA, int TB> __device__ __forceinline__ void wgmma_ss_n48(float (&d)[24], Desc a, Desc b, int sc) {
  asm volatile("{.reg .pred p; .reg .b32 t, u; .reg .b64 da, db; setp.ne.b32 p, %30, 0; add.u32 t, %24, %25; mov.b64 da, {t, %26}; add.u32 u, %27, %28; mov.b64 db, {u, %29};"
    "wgmma.mma_async.sync.aligned.m64n48k16.f32.bf16.bf16 {%0,%1,%2,%3,%4,%5,%6,%7,%8,%9,%10,%11,%12,%13,%14,%15,%16,%17,%18,%19,%20,%21,%22,%23}, da, db, p, 1, 1, %31, %32;}"
    : "+f"(d[0]),"+f"(d[1]),"+f"(d[2]),"+f"(d[3]),"+f"(d[4]),"+f"(d[5]),"+f"(d[6]),"+f"(d[7]),"+f"(d[8]),"+f"(d[9]),"+f"(d[10]),"+f"(d[11]),"+f"(d[12]),"+f"(d[13]),"+f"(d[14]),"+f"(d[15]),"+f"(d[16]),"+f"(d[17]),"+f"(d[18]),"+f"(d[19]),"+f"(d[20]),"+f"(d[21]),"+f"(d[22]),"+f"(d[23])
    : "r"(a.base), "r"(a.off), "r"(a.hi), "r"(b.base), "r"(b.off), "r"(b.hi), "r"(sc), "n"(TA), "n"(TB));
}
template <int TA, int TB> __device__ __forceinline__ void wgmma_ss_n80(float (&d)[40], Desc a, Desc b, int sc) {
  asm volatile("{.reg .pred p; .reg .b32 t, u; .reg .b64 da, db; setp.ne.b32 p, %46, 0; add.u32 t, %40, %41; mov.b64 da, {t, %42}; add.u32 u, %43, %44; mov.b64 db, {u, %45};"
    "wgmma.mma_async.sync.aligned.m64n80k16.f32.bf16.bf16 {%0,%1,%2,%3,%4,%5,%6,%7,%8,%9,%10,%11,%12,%13,%14,%15,%16,%17,%18,%19,%20,%21,%22,%23,%24,%25,%26,%27,%28,%29,%30,%31,%32,%33,%34,%35,%36,%37,%38,%39}, da, db, p, 1, 1, %47, %48;}"
    : "+f"(d[0]),"+f"(d[1]),"+f"(d[2]),"+f"(d[3]),"+f"(d[4]),"+f"(d[5]),"+f"(d[6]),"+f"(d[7]),"+f"(d[8]),"+f"(d[9]),"+f"(d[10]),"+f"(d[11]),"+f"(d[12]),"+f"(d[13]),"+f"(d[14]),"+f"(d[15]),"+f"(d[16]),"+f"(d[17]),"+f"(d[18]),"+f"(d[19]),"+f"(d[20]),"+f"(d[21]),"+f"(d[22]),"+f"(d[23]),"+f"(d[24]),"+f"(d[25]),"+f"(d[26]),"+f"(d[27]),"+f"(d[28]),"+f"(d[29]),"+f"(d[30]),"+f"(d[31]),"+f"(d[32]),"+f"(d[33]),"+f"(d[34]),"+f"(d[35]),"+f"(d[36]),"+f"(d[37]),"+f"(d[38]),"+f"(d[39])
    : "r"(a.base), "r"(a.off), "r"(a.hi), "r"(b.base), "r"(b.off), "r"(b.hi), "r"(sc), "n"(TA), "n"(TB));
}
template <int TA, int TB> __device__ __forceinline__ void wgmma_ss_n160(float (&d)[80], Desc a, Desc b, int sc) {
  asm volatile("{.reg .pred p; .reg .b32 t, u; .reg .b64 da, db; setp.ne.b32 p, %86, 0; add.u32 t, %80, %81; mov.b64 da, {t, %82}; add.u32 u, %83, %84; mov.b64 db, {u, %85};"
    "wgmma.mma_async.sync.aligned.m64n160k16.f32.bf16.bf16 {%0,%1,%2,%3,%4,%5,%6,%7,%8,%9,%10,%11,%12,%13,%14,%15,%16,%17,%18,%19,%20,%21,%22,%23,%24,%25,%26,%27,%28,%29,%30,%31,%32,%33,%34,%35,%36,%37,%38,%39,%40,%41,%42,%43,%44,%45,%46,%47,%48,%49,%50,%51,%52,%53,%54,%55,%56,%57,%58,%59,%60,%61,%62,%63,%64,%65,%66,%67,%68,%69,%70,%71,%72,%73,%74,%75,%76,%77,%78,%79}, da, db, p, 1, 1, %87, %88;}"
    : "+f"(d[0]),"+f"(d[1]),"+f"(d[2]),"+f"(d[3]),"+f"(d[4]),"+f"(d[5]),"+f"(d[6]),"+f"(d[7]),"+f"(d[8]),"+f"(d[9]),"+f"(d[10]),"+f"(d[11]),"+f"(d[12]),"+f"(d[13]),"+f"(d[14]),"+f"(d[15]),"+f"(d[16]),"+f"(d[17]),"+f"(d[18]),"+f"(d[19]),"+f"(d[20]),"+f"(d[21]),"+f"(d[22]),"+f"(d[23]),"+f"(d[24]),"+f"(d[25]),"+f"(d[26]),"+f"(d[27]),"+f"(d[28]),"+f"(d[29]),"+f"(d[30]),"+f"(d[31]),"+f"(d[32]),"+f"(d[33]),"+f"(d[34]),"+f"(d[35]),"+f"(d[36]),"+f"(d[37]),"+f"(d[38]),"+f"(d[39]),"+f"(d[40]),"+f"(d[41]),"+f"(d[42]),"+f"(d[43]),"+f"(d[44]),"+f"(d[45]),"+f"(d[46]),"+f"(d[47]),"+f"(d[48]),"+f"(d[49]),"+f"(d[50]),"+f"(d[51]),"+f"(d[52]),"+f"(d[53]),"+f"(d[54]),"+f"(d[55]),"+f"(d[56]),"+f"(d[57]),"+f"(d[58]),"+f"(d[59]),"+f"(d[60]),"+f"(d[61]),"+f"(d[62]),"+f"(d[63]),"+f"(d[64]),"+f"(d[65]),"+f"(d[66]),"+f"(d[67]),"+f"(d[68]),"+f"(d[69]),"+f"(d[70]),"+f"(d[71]),"+f"(d[72]),"+f"(d[73]),"+f"(d[74]),"+f"(d[75]),"+f"(d[76]),"+f"(d[77]),"+f"(d[78]),"+f"(d[79])
    : "r"(a.base), "r"(a.off), "r"(a.hi), "r"(b.base), "r"(b.off), "r"(b.hi), "r"(sc), "n"(TA), "n"(TB));
}
template <int TA, int TB> __device__ __forceinline__ void wgmma_ss_n192(float (&d)[96], Desc a, Desc b, int sc) {
  asm volatile("{.reg .pred p; .reg .b32 t, u; .reg .b64 da, db; setp.ne.b32 p, %102, 0; add.u32 t, %96, %97; mov.b64 da, {t, %98}; add.u32 u, %99, %100; mov.b64 db, {u, %101};"
    "wgmma.mma_async.sync.aligned.m64n192k16.f32.bf16.bf16 {%0,%1,%2,%3,%4,%5,%6,%7,%8,%9,%10,%11,%12,%13,%14,%15,%16,%17,%18,%19,%20,%21,%22,%23,%24,%25,%26,%27,%28,%29,%30,%31,%32,%33,%34,%35,%36,%37,%38,%39,%40,%41,%42,%43,%44,%45,%46,%47,%48,%49,%50,%51,%52,%53,%54,%55,%56,%57,%58,%59,%60,%61,%62,%63,%64,%65,%66,%67,%68,%69,%70,%71,%72,%73,%74,%75,%76,%77,%78,%79,%80,%81,%82,%83,%84,%85,%86,%87,%88,%89,%90,%91,%92,%93,%94,%95}, da, db, p, 1, 1, %103, %104;}"
    : "+f"(d[0]),"+f"(d[1]),"+f"(d[2]),"+f"(d[3]),"+f"(d[4]),"+f"(d[5]),"+f"(d[6]),"+f"(d[7]),"+f"(d[8]),"+f"(d[9]),"+f"(d[10]),"+f"(d[11]),"+f"(d[12]),"+f"(d[13]),"+f"(d[14]),"+f"(d[15]),"+f"(d[16]),"+f"(d[17]),"+f"(d[18]),"+f"(d[19]),"+f"(d[20]),"+f"(d[21]),"+f"(d[22]),"+f"(d[23]),"+f"(d[24]),"+f"(d[25]),"+f"(d[26]),"+f"(d[27]),"+f"(d[28]),"+f"(d[29]),"+f"(d[30]),"+f"(d[31]),"+f"(d[32]),"+f"(d[33]),"+f"(d[34]),"+f"(d[35]),"+f"(d[36]),"+f"(d[37]),"+f"(d[38]),"+f"(d[39]),"+f"(d[40]),"+f"(d[41]),"+f"(d[42]),"+f"(d[43]),"+f"(d[44]),"+f"(d[45]),"+f"(d[46]),"+f"(d[47]),"+f"(d[48]),"+f"(d[49]),"+f"(d[50]),"+f"(d[51]),"+f"(d[52]),"+f"(d[53]),"+f"(d[54]),"+f"(d[55]),"+f"(d[56]),"+f"(d[57]),"+f"(d[58]),"+f"(d[59]),"+f"(d[60]),"+f"(d[61]),"+f"(d[62]),"+f"(d[63]),"+f"(d[64]),"+f"(d[65]),"+f"(d[66]),"+f"(d[67]),"+f"(d[68]),"+f"(d[69]),"+f"(d[70]),"+f"(d[71]),"+f"(d[72]),"+f"(d[73]),"+f"(d[74]),"+f"(d[75]),"+f"(d[76]),"+f"(d[77]),"+f"(d[78]),"+f"(d[79]),"+f"(d[80]),"+f"(d[81]),"+f"(d[82]),"+f"(d[83]),"+f"(d[84]),"+f"(d[85]),"+f"(d[86]),"+f"(d[87]),"+f"(d[88]),"+f"(d[89]),"+f"(d[90]),"+f"(d[91]),"+f"(d[92]),"+f"(d[93]),"+f"(d[94]),"+f"(d[95])
    : "r"(a.base), "r"(a.off), "r"(a.hi), "r"(b.base), "r"(b.off), "r"(b.hi), "r"(sc), "n"(TA), "n"(TB));
}
template <int TB> __device__ __forceinline__ void wgmma_rs_n80(float (&d)[40], uint32_t a0, uint32_t a1, uint32_t a2, uint32_t a3, Desc b, int sc) {
  asm volatile("{.reg .pred p; .reg .b32 u; .reg .b64 db; setp.ne.b32 p, %47, 0; add.u32 u, %44, %45; mov.b64 db, {u, %46};"
    "wgmma.mma_async.sync.aligned.m64n80k16.f32.bf16.bf16 {%0,%1,%2,%3,%4,%5,%6,%7,%8,%9,%10,%11,%12,%13,%14,%15,%16,%17,%18,%19,%20,%21,%22,%23,%24,%25,%26,%27,%28,%29,%30,%31,%32,%33,%34,%35,%36,%37,%38,%39}, {%40,%41,%42,%43}, db, p, 1, 1, %48;}"
    : "+f"(d[0]),"+f"(d[1]),"+f"(d[2]),"+f"(d[3]),"+f"(d[4]),"+f"(d[5]),"+f"(d[6]),"+f"(d[7]),"+f"(d[8]),"+f"(d[9]),"+f"(d[10]),"+f"(d[11]),"+f"(d[12]),"+f"(d[13]),"+f"(d[14]),"+f"(d[15]),"+f"(d[16]),"+f"(d[17]),"+f"(d[18]),"+f"(d[19]),"+f"(d[20]),"+f"(d[21]),"+f"(d[22]),"+f"(d[23]),"+f"(d[24]),"+f"(d[25]),"+f"(d[26]),"+f"(d[27]),"+f"(d[28]),"+f"(d[29]),"+f"(d[30]),"+f"(d[31]),"+f"(d[32]),"+f"(d[33]),"+f"(d[34]),"+f"(d[35]),"+f"(d[36]),"+f"(d[37]),"+f"(d[38]),"+f"(d[39])
    : "r"(a0), "r"(a1), "r"(a2), "r"(a3), "r"(b.base), "r"(b.off), "r"(b.hi), "r"(sc), "n"(TB));
}
template <int TB> __device__ __forceinline__ void wgmma_rs_n96(float (&d)[48], uint32_t a0, uint32_t a1, uint32_t a2, uint32_t a3, Desc b, int sc) {
  asm volatile("{.reg .pred p; .reg .b32 u; .reg .b64 db; setp.ne.b32 p, %55, 0; add.u32 u, %52, %53; mov.b64 db, {u, %54};"
    "wgmma.mma_async.sync.aligned.m64n96k16.f32.bf16.bf16 {%0,%1,%2,%3,%4,%5,%6,%7,%8,%9,%10,%11,%12,%13,%14,%15,%16,%17,%18,%19,%20,%21,%22,%23,%24,%25,%26,%27,%28,%29,%30,%31,%32,%33,%34,%35,%36,%37,%38,%39,%40,%41,%42,%43,%44,%45,%46,%47}, {%48,%49,%50,%51}, db, p, 1, 1, %56;}"
    : "+f"(d[0]),"+f"(d[1]),"+f"(d[2]),"+f"(d[3]),"+f"(d[4]),"+f"(d[5]),"+f"(d[6]),"+f"(d[7]),"+f"(d[8]),"+f"(d[9]),"+f"(d[10]),"+f"(d[11]),"+f"(d[12]),"+f"(d[13]),"+f"(d[14]),"+f"(d[15]),"+f"(d[16]),"+f"(d[17]),"+f"(d[18]),"+f"(d[19]),"+f"(d[20]),"+f"(d[21]),"+f"(d[22]),"+f"(d[23]),"+f"(d[24]),"+f"(d[25]),"+f"(d[26]),"+f"(d[27]),"+f"(d[28]),"+f"(d[29]),"+f"(d[30]),"+f"(d[31]),"+f"(d[32]),"+f"(d[33]),"+f"(d[34]),"+f"(d[35]),"+f"(d[36]),"+f"(d[37]),"+f"(d[38]),"+f"(d[39]),"+f"(d[40]),"+f"(d[41]),"+f"(d[42]),"+f"(d[43]),"+f"(d[44]),"+f"(d[45]),"+f"(d[46]),"+f"(d[47])
    : "r"(a0), "r"(a1), "r"(a2), "r"(a3), "r"(b.base), "r"(b.off), "r"(b.hi), "r"(sc), "n"(TB));
}
template <int TB> __device__ __forceinline__ void wgmma_rs_n160(float (&d)[80], uint32_t a0, uint32_t a1, uint32_t a2, uint32_t a3, Desc b, int sc) {
  asm volatile("{.reg .pred p; .reg .b32 u; .reg .b64 db; setp.ne.b32 p, %87, 0; add.u32 u, %84, %85; mov.b64 db, {u, %86};"
    "wgmma.mma_async.sync.aligned.m64n160k16.f32.bf16.bf16 {%0,%1,%2,%3,%4,%5,%6,%7,%8,%9,%10,%11,%12,%13,%14,%15,%16,%17,%18,%19,%20,%21,%22,%23,%24,%25,%26,%27,%28,%29,%30,%31,%32,%33,%34,%35,%36,%37,%38,%39,%40,%41,%42,%43,%44,%45,%46,%47,%48,%49,%50,%51,%52,%53,%54,%55,%56,%57,%58,%59,%60,%61,%62,%63,%64,%65,%66,%67,%68,%69,%70,%71,%72,%73,%74,%75,%76,%77,%78,%79}, {%80,%81,%82,%83}, db, p, 1, 1, %88;}"
    : "+f"(d[0]),"+f"(d[1]),"+f"(d[2]),"+f"(d[3]),"+f"(d[4]),"+f"(d[5]),"+f"(d[6]),"+f"(d[7]),"+f"(d[8]),"+f"(d[9]),"+f"(d[10]),"+f"(d[11]),"+f"(d[12]),"+f"(d[13]),"+f"(d[14]),"+f"(d[15]),"+f"(d[16]),"+f"(d[17]),"+f"(d[18]),"+f"(d[19]),"+f"(d[20]),"+f"(d[21]),"+f"(d[22]),"+f"(d[23]),"+f"(d[24]),"+f"(d[25]),"+f"(d[26]),"+f"(d[27]),"+f"(d[28]),"+f"(d[29]),"+f"(d[30]),"+f"(d[31]),"+f"(d[32]),"+f"(d[33]),"+f"(d[34]),"+f"(d[35]),"+f"(d[36]),"+f"(d[37]),"+f"(d[38]),"+f"(d[39]),"+f"(d[40]),"+f"(d[41]),"+f"(d[42]),"+f"(d[43]),"+f"(d[44]),"+f"(d[45]),"+f"(d[46]),"+f"(d[47]),"+f"(d[48]),"+f"(d[49]),"+f"(d[50]),"+f"(d[51]),"+f"(d[52]),"+f"(d[53]),"+f"(d[54]),"+f"(d[55]),"+f"(d[56]),"+f"(d[57]),"+f"(d[58]),"+f"(d[59]),"+f"(d[60]),"+f"(d[61]),"+f"(d[62]),"+f"(d[63]),"+f"(d[64]),"+f"(d[65]),"+f"(d[66]),"+f"(d[67]),"+f"(d[68]),"+f"(d[69]),"+f"(d[70]),"+f"(d[71]),"+f"(d[72]),"+f"(d[73]),"+f"(d[74]),"+f"(d[75]),"+f"(d[76]),"+f"(d[77]),"+f"(d[78]),"+f"(d[79])
    : "r"(a0), "r"(a1), "r"(a2), "r"(a3), "r"(b.base), "r"(b.off), "r"(b.hi), "r"(sc), "n"(TB));
}
template <int TB> __device__ __forceinline__ void wgmma_rs_n192(float (&d)[96], uint32_t a0, uint32_t a1, uint32_t a2, uint32_t a3, Desc b, int sc) {
  asm volatile("{.reg .pred p; .reg .b32 u; .reg .b64 db; setp.ne.b32 p, %103, 0; add.u32 u, %100, %101; mov.b64 db, {u, %102};"
    "wgmma.mma_async.sync.aligned.m64n192k16.f32.bf16.bf16 {%0,%1,%2,%3,%4,%5,%6,%7,%8,%9,%10,%11,%12,%13,%14,%15,%16,%17,%18,%19,%20,%21,%22,%23,%24,%25,%26,%27,%28,%29,%30,%31,%32,%33,%34,%35,%36,%37,%38,%39,%40,%41,%42,%43,%44,%45,%46,%47,%48,%49,%50,%51,%52,%53,%54,%55,%56,%57,%58,%59,%60,%61,%62,%63,%64,%65,%66,%67,%68,%69,%70,%71,%72,%73,%74,%75,%76,%77,%78,%79,%80,%81,%82,%83,%84,%85,%86,%87,%88,%89,%90,%91,%92,%93,%94,%95}, {%96,%97,%98,%99}, db, p, 1, 1, %104;}"
    : "+f"(d[0]),"+f"(d[1]),"+f"(d[2]),"+f"(d[3]),"+f"(d[4]),"+f"(d[5]),"+f"(d[6]),"+f"(d[7]),"+f"(d[8]),"+f"(d[9]),"+f"(d[10]),"+f"(d[11]),"+f"(d[12]),"+f"(d[13]),"+f"(d[14]),"+f"(d[15]),"+f"(d[16]),"+f"(d[17]),"+f"(d[18]),"+f"(d[19]),"+f"(d[20]),"+f"(d[21]),"+f"(d[22]),"+f"(d[23]),"+f"(d[24]),"+f"(d[25]),"+f"(d[26]),"+f"(d[27]),"+f"(d[28]),"+f"(d[29]),"+f"(d[30]),"+f"(d[31]),"+f"(d[32]),"+f"(d[33]),"+f"(d[34]),"+f"(d[35]),"+f"(d[36]),"+f"(d[37]),"+f"(d[38]),"+f"(d[39]),"+f"(d[40]),"+f"(d[41]),"+f"(d[42]),"+f"(d[43]),"+f"(d[44]),"+f"(d[45]),"+f"(d[46]),"+f"(d[47]),"+f"(d[48]),"+f"(d[49]),"+f"(d[50]),"+f"(d[51]),"+f"(d[52]),"+f"(d[53]),"+f"(d[54]),"+f"(d[55]),"+f"(d[56]),"+f"(d[57]),"+f"(d[58]),"+f"(d[59]),"+f"(d[60]),"+f"(d[61]),"+f"(d[62]),"+f"(d[63]),"+f"(d[64]),"+f"(d[65]),"+f"(d[66]),"+f"(d[67]),"+f"(d[68]),"+f"(d[69]),"+f"(d[70]),"+f"(d[71]),"+f"(d[72]),"+f"(d[73]),"+f"(d[74]),"+f"(d[75]),"+f"(d[76]),"+f"(d[77]),"+f"(d[78]),"+f"(d[79]),"+f"(d[80]),"+f"(d[81]),"+f"(d[82]),"+f"(d[83]),"+f"(d[84]),"+f"(d[85]),"+f"(d[86]),"+f"(d[87]),"+f"(d[88]),"+f"(d[89]),"+f"(d[90]),"+f"(d[91]),"+f"(d[92]),"+f"(d[93]),"+f"(d[94]),"+f"(d[95])
    : "r"(a0), "r"(a1), "r"(a2), "r"(a3), "r"(b.base), "r"(b.off), "r"(b.hi), "r"(sc), "n"(TB));
}
template <int N, int TA, int TB> __device__ __forceinline__ void wgmma_ss(float (&d)[N / 2], Desc a, Desc b, int sc) {
  if constexpr (N == 48) wgmma_ss_n48<TA, TB>(d, a, b, sc);
  else if constexpr (N == 80) wgmma_ss_n80<TA, TB>(d, a, b, sc);
  else if constexpr (N == 160) wgmma_ss_n160<TA, TB>(d, a, b, sc);
  else if constexpr (N == 192) wgmma_ss_n192<TA, TB>(d, a, b, sc);
}
template <int N, int TB> __device__ __forceinline__ void wgmma_rs(float (&d)[N / 2], uint32_t a0, uint32_t a1, uint32_t a2, uint32_t a3, Desc b, int sc) {
  if constexpr (N == 80) wgmma_rs_n80<TB>(d, a0, a1, a2, a3, b, sc);
  else if constexpr (N == 96) wgmma_rs_n96<TB>(d, a0, a1, a2, a3, b, sc);
  else if constexpr (N == 160) wgmma_rs_n160<TB>(d, a0, a1, a2, a3, b, sc);
  else if constexpr (N == 192) wgmma_rs_n192<TB>(d, a0, a1, a2, a3, b, sc);
}

constexpr uint32_t SMEM_BASE = 1024;
constexpr uint32_t PAGE = 10240;
constexpr uint32_t OFF_RING = 16 * PAGE;
constexpr uint32_t OFF_KVB = 50176;
constexpr uint32_t OFF_KVP = 43008;
constexpr uint32_t OFF_R1 = 35840;
constexpr uint32_t OFF_MISC = 22 * PAGE;
constexpr uint32_t OFF_W2 = OFF_MISC - 6 * 24576;
constexpr uint32_t OFF_BAR = OFF_MISC;
constexpr uint32_t OFF_LN1 = OFF_MISC + 1920;
constexpr uint32_t OFF_RK1 = OFF_MISC + 2944;
constexpr uint32_t OFF_B2 = OFF_RK1 + 3072;
constexpr uint32_t OFF_SCR = OFF_MISC + 6784;
constexpr uint32_t SMEM_BYTES = OFF_MISC + 7040;

enum : int {
  FX = 0, PX = 13, PF = 14, RX = 15, RXK = 17, SIDE = 18, ZK = 19, RKV = 20, ST1 = 21, XF = 22, KD = 23,
  FE = 24,
  RE = 28, RF = 36,
  FWO = 42, FW1 = 50, FW2 = 58,
  AO = 70, AH = 86, AF = 102,
  DW = 126, DF = 142, DG = 158,
  SO = 182, SH = 183,
  SIDE2 = 185, KVB = 186, END = 187, OM = 188
};
#define XMC 0x3FE

__device__ uint32_t g_epoch;
__device__ uint4 g_ln1[2048];
__device__ uint4 g_cs[4 * 1728];
__device__ uint4 g_hstat[32 * 8 * 64];
__device__ __align__(128) float2 g_kv1[8 * 16 * 880];
__device__ __align__(128) uint2 g_kv2[8 * 960];
__device__ __align__(128) uint32_t g_flag[3 * 32 * 32];
__device__ __align__(128) uint8_t g_act[3 * 32 * 8 * 24576];

struct Maps { CUtensorMap m[11]; };
enum : int { M_X, M_KVF, M_KVH, M_Q2, M_QR, M_WO2, M_WOR, M_W1, M_W1R, M_W2F, M_W2H };

#define TL(id)
#define TLW(id)
#define TL0(id)
#define TC(v)
#define TS(id, v)

constexpr int SPIN_LIMIT = 1 << 19;

__device__ __forceinline__ bool elect_one() {
  uint32_t p;
  asm volatile("{.reg .pred P; elect.sync _|P, 0xffffffff; selp.u32 %0,1,0,P;}" : "=r"(p));
  return p;
}
__device__ __forceinline__ void mbar_wait(uint32_t bar, uint32_t parity = 0) {
  asm volatile("{.reg .pred p;\nW: mbarrier.try_wait.parity.shared::cta.b64 p, [%0], %1;\n@!p bra W;}" ::"r"(bar), "r"(parity) : "memory");
}
__device__ __forceinline__ void mbar_wait_cluster(uint32_t bar) {
  asm volatile("{.reg .pred p;\nW: mbarrier.try_wait.parity.acquire.cluster.shared::cta.b64 p, [%0], 0;\n@!p bra W;}" ::"r"(bar) : "memory");
}
__device__ __forceinline__ void mbar_wait_wd(uint32_t bar) {
  asm volatile("{.reg .pred p; .reg .u32 n; mov.u32 n, 0;\n"
               "W: mbarrier.try_wait.parity.shared::cta.b64 p, [%0], 0;\n"
               "@p bra D; add.u32 n, n, 1; setp.gt.u32 p, n, %1; @p trap; bra W;\n"
               "D: }" ::"r"(bar), "n"(SPIN_LIMIT) : "memory");
}
__device__ __forceinline__ void mbar_arrive(uint32_t bar, uint32_t n) {
  asm volatile("mbarrier.arrive.shared::cta.b64 _, [%0], %1;" ::"r"(bar), "r"(n) : "memory");
}
__device__ __forceinline__ void mbar_arrive_if0(int z, uint32_t bar, uint32_t n) {
  asm volatile("{.reg .pred p; setp.eq.s32 p, %2, 0; @p mbarrier.arrive.shared::cta.b64 _, [%0], %1;}" ::"r"(bar), "r"(n), "r"(z) : "memory");
}
__device__ __forceinline__ void mbar_arrive_remote_if0(int z, uint32_t bar) {
  asm volatile("{.reg .pred p; setp.eq.s32 p, %1, 0; @p mbarrier.arrive.shared::cluster.b64 _, [%0];}" ::"r"(bar), "r"(z) : "memory");
}
__device__ __forceinline__ void mbar_expect(uint32_t bar, uint32_t bytes) {
  asm volatile("mbarrier.arrive.expect_tx.shared::cta.b64 _, [%0], %1;" ::"r"(bar), "r"(bytes) : "memory");
  asm volatile("mbarrier.arrive.shared::cta.b64 _, [%0], 7;" ::"r"(bar) : "memory");
}
__device__ __forceinline__ void tma2d(uint32_t dst, const CUtensorMap* tm, uint32_t bar, int c0, int c1) {
  asm volatile("cp.async.bulk.tensor.2d.shared::cluster.global.mbarrier::complete_tx::bytes [%0],[%1,{%3,%4}],[%2];"
               ::"r"(dst), "l"(tm), "r"(bar), "r"(c0), "r"(c1) : "memory");
}
__device__ __forceinline__ void tma3d(uint32_t dst, const CUtensorMap* tm, uint32_t bar, int c0, int c1, int c2) {
  asm volatile("cp.async.bulk.tensor.3d.shared::cluster.global.mbarrier::complete_tx::bytes [%0],[%1,{%3,%4,%5}],[%2];"
               ::"r"(dst), "l"(tm), "r"(bar), "r"(c0), "r"(c1), "r"(c2) : "memory");
}
__device__ __forceinline__ void tma2d_pair(uint32_t dst, const CUtensorMap* tm, uint32_t bar, int c0, int c1) {
  asm volatile("cp.async.bulk.tensor.2d.shared::cluster.global.mbarrier::complete_tx::bytes.multicast::cluster [%0],[%1,{%3,%4}],[%2],%5;"
               ::"r"(dst), "l"(tm), "r"(bar), "r"(c0), "r"(c1), "h"((uint16_t)3) : "memory");
}
__device__ __forceinline__ void bulk_load(uint32_t dst, const void* src, uint32_t bytes, uint32_t bar) {
  asm volatile("cp.async.bulk.shared::cluster.global.mbarrier::complete_tx::bytes [%0],[%1],%2,[%3];"
               ::"r"(dst), "l"(src), "r"(bytes), "r"(bar) : "memory");
}
__device__ __forceinline__ void bulk_store(void* dst, uint32_t src, uint32_t bytes) {
  asm volatile("cp.async.bulk.global.shared::cta.bulk_group [%0],[%1],%2;" ::"l"(dst), "r"(src), "r"(bytes) : "memory");
}
__device__ __forceinline__ void bulk_commit_wait() {
  asm volatile("cp.async.bulk.commit_group;" ::: "memory");
  asm volatile("cp.async.bulk.wait_group 0;" ::: "memory");
}
__device__ __forceinline__ void l2_prefetch(const void* src, uint32_t bytes) {
  asm volatile("cp.async.bulk.prefetch.L2.global [%0], %1;" ::"l"(src), "r"(bytes) : "memory");
}
__device__ __forceinline__ void fence_gpu() { asm volatile("fence.acq_rel.gpu;" ::: "memory"); }
__device__ __forceinline__ void fence_async_smem() { asm volatile("fence.proxy.async.shared::cta;" ::: "memory"); }
__device__ __forceinline__ void fence_async_global() { asm volatile("fence.proxy.async.global;" ::: "memory"); }
__device__ __forceinline__ void st_flag(uint32_t* p, uint32_t v) {
  asm volatile("st.relaxed.gpu.global.u32 [%0], %1;" ::"l"(p), "r"(v) : "memory");
}
__device__ __forceinline__ uint32_t ld_acq(const uint32_t* p) {
  uint32_t v;
  asm volatile("ld.acquire.gpu.global.u32 %0, [%1];" : "=r"(v) : "l"(p) : "memory");
  return v;
}
__device__ __forceinline__ void wg_fence() { asm volatile("wgmma.fence.sync.aligned;" ::: "memory"); }
__device__ __forceinline__ void wg_commit() { asm volatile("wgmma.commit_group.sync.aligned;" ::: "memory"); }
template <int N> __device__ __forceinline__ void wg_wait() { asm volatile("wgmma.wait_group.sync.aligned %0;" ::"n"(N) : "memory"); }
template <int N> __device__ __forceinline__ void reg_fence(float (&a)[N]) {
#pragma unroll
  for (int i = 0; i < N; i++) asm volatile("" : "+f"(a[i])::"memory");
}
template <int ID, int N> __device__ __forceinline__ void named_bar() { asm volatile("bar.sync %0, %1;" ::"n"(ID), "n"(N) : "memory"); }
template <int N> __device__ __forceinline__ void reg_fence(uint32_t (&a)[N]) {
#pragma unroll
  for (int i = 0; i < N; i++) asm volatile("" : "+r"(a[i])::"memory");
}
__device__ __forceinline__ Desc mkdesc(uint32_t dyn, uint32_t off, uint32_t lbo, uint32_t sbo, uint32_t swz) {
  return Desc{dyn, ((off + SMEM_BASE) >> 4) + ((lbo >> 4) << 16), (sbo >> 4) | (swz << 30)};
}
__device__ __forceinline__ uint32_t pack2(float lo, float hi) {
  uint32_t r;
  asm("cvt.rn.bf16x2.f32 %0, %1, %2;" : "=r"(r) : "f"(hi), "f"(lo));
  return r;
}
__device__ __forceinline__ float bf_lo(uint32_t v) { return __uint_as_float(v << 16); }
__device__ __forceinline__ float bf_hi(uint32_t v) { return __uint_as_float(v & 0xffff0000u); }
__device__ __forceinline__ void stsm4(uint32_t addr, uint32_t a, uint32_t b, uint32_t c, uint32_t d) {
  asm volatile("stmatrix.sync.aligned.m8n8.x4.shared.b16 [%0], {%1,%2,%3,%4};" ::"r"(addr), "r"(a), "r"(b), "r"(c), "r"(d) : "memory");
}
__device__ __forceinline__ void ldsm4(uint32_t addr, uint32_t* r) {
  asm volatile("ldmatrix.sync.aligned.m8n8.x4.shared.b16 {%0,%1,%2,%3}, [%4];" : "=r"(r[0]), "=r"(r[1]), "=r"(r[2]), "=r"(r[3]) : "r"(addr) : "memory");
}
__device__ __forceinline__ float2 lds64(uint32_t a) {
  float2 v;
  asm volatile("ld.shared.v2.f32 {%0,%1}, [%2];" : "=f"(v.x), "=f"(v.y) : "r"(a) : "memory");
  return v;
}
__device__ __forceinline__ float4 lds128(uint32_t a) {
  float4 v;
  asm volatile("ld.shared.v4.f32 {%0,%1,%2,%3}, [%4];" : "=f"(v.x), "=f"(v.y), "=f"(v.z), "=f"(v.w) : "r"(a) : "memory");
  return v;
}
__device__ __forceinline__ void sts64(uint32_t a, uint32_t x, uint32_t y) {
  asm volatile("st.shared.v2.u32 [%0], {%1,%2};" ::"r"(a), "r"(x), "r"(y) : "memory");
}
__device__ __forceinline__ void sts128(uint32_t a, uint32_t x, uint32_t y, uint32_t z, uint32_t w) {
  asm volatile("st.shared.v4.u32 [%0], {%1,%2,%3,%4};" ::"r"(a), "r"(x), "r"(y), "r"(z), "r"(w) : "memory");
}
__device__ __forceinline__ float ex2(float x) {
  float r;
  asm("ex2.approx.ftz.f32 %0, %1;" : "=f"(r) : "f"(x));
  return r;
}
__device__ __forceinline__ float rcp(float x) {
  float r;
  asm("rcp.approx.ftz.f32 %0, %1;" : "=f"(r) : "f"(x));
  return r;
}
constexpr float LOG2E = 1.4426950408889634f;
__device__ __forceinline__ float phi(float z, float a, float a2) {
  float r = ex2(z * a2) + 1e-6f;
  asm("{.reg .pred p; setp.gt.f32 p, %1, 0f00000000; @p fma.rn.f32 %0, %1, %2, 0f3F800008;}" : "+f"(r) : "f"(z), "f"(a));
  return r;
}
__device__ __forceinline__ float gelu(float z, const float3& k) {
  float th;
  asm("tanh.approx.f32 %0, %1;" : "=f"(th) : "f"(z * fmaf(z * z, k.y, k.x)));
  const float hy = z * k.z;
  return fmaf(hy, th, hy);
}
__device__ __forceinline__ uint32_t rk1_frag(float m, float d, int c) {
  const uint32_t hi = pack2(m, d), lo = pack2(m - bf_lo(hi), d - bf_hi(hi));
  return c == 0 ? __byte_perm(hi, 0, 0x1010) : c == 1 ? __byte_perm(lo, hi, 0x7610) : c == 2 ? lo >> 16 : 0u;
}
__device__ __forceinline__ void rk1_store(uint32_t addr, float2 cs, uint32_t bb) {
  const uint32_t hi = pack2(cs.x, cs.y), lo = pack2(cs.x - bf_lo(hi), cs.y - bf_hi(hi));
  sts128(addr, __byte_perm(hi, lo, 0x5410), __byte_perm(hi, bb, 0x5410), bb & 0xffffu, 0);
  sts128(addr + 16, __byte_perm(hi, lo, 0x7632), __byte_perm(hi, bb, 0x7632), bb >> 16, 0);
}
constexpr uint32_t ONES = 0x3F803F80u;
__device__ __forceinline__ void ll_store(uint4* p, float a, float b, uint32_t tag) {
  asm volatile("st.relaxed.gpu.global.v4.u32 [%0], {%1,%2,%3,%2};" ::"l"(p), "r"(__float_as_uint(a)), "r"(tag), "r"(__float_as_uint(b)) : "memory");
}
__device__ __forceinline__ uint4 ll_load(const void* p) {
  uint4 v;
  asm volatile("ld.relaxed.gpu.global.v4.u32 {%0,%1,%2,%3}, [%4];" : "=r"(v.x), "=r"(v.y), "=r"(v.z), "=r"(v.w) : "l"(p) : "memory");
  return v;
}
template <int N>
__device__ __forceinline__ void ll_wait(uint4 (&v)[N], const uint4* p, int stride, uint32_t tag) {
  uint32_t bad;
  int it = 0;
  do {
    bad = 0;
#pragma unroll
    for (int m = 0; m < N; m++) v[m] = ll_load(p + m * stride);
#pragma unroll
    for (int m = 0; m < N; m++) bad |= (v[m].y ^ tag) | (v[m].w ^ tag);
  } while (__any_sync(0xffffffffu, bad) && ++it < SPIN_LIMIT);
}
__device__ __forceinline__ void ll_wait2(uint4 (&v)[8], const uint4* p, uint32_t tag) {
  uint32_t bad;
  int it = 0;
  do {
    bad = 0;
#pragma unroll
    for (int m = 0; m < 8; m++) v[m] = ll_load(p + (m >> 1) * 1728 + (m & 1));
#pragma unroll
    for (int m = 0; m < 8; m++) bad |= (v[m].y ^ tag) | (v[m].w ^ tag);
  } while (__any_sync(0xffffffffu, bad) && ++it < SPIN_LIMIT);
}
__device__ __forceinline__ float2 ll_sum4(const uint4* p, uint32_t tag) {
  uint4 v[4];
  ll_wait(v, p, 1728, tag);
  return make_float2((__uint_as_float(v[0].x) + __uint_as_float(v[1].x)) + (__uint_as_float(v[2].x) + __uint_as_float(v[3].x)),
                     (__uint_as_float(v[0].z) + __uint_as_float(v[1].z)) + (__uint_as_float(v[2].z) + __uint_as_float(v[3].z)));
}
template <bool PHI>
__device__ __forceinline__ void ln_pair(const float* z, const float (&a)[2], const float (&a2)[2], uint32_t* o) {
#pragma unroll
  for (int e = 0; e < 4; e++) {
    const int hh = e & 1;
    o[e] = PHI ? pack2(phi(z[2 * e], a[hh], a2[hh]), phi(z[2 * e + 1], a[hh], a2[hh])) : pack2(z[2 * e] * a[hh], z[2 * e + 1] * a[hh]);
  }
}

__global__ void __cluster_dims__(2, 1, 1) __launch_bounds__(384, 1)
fused_block_kernel(const __grid_constant__ Maps maps, const __nv_bfloat16* __restrict__ x, const __nv_bfloat16* __restrict__ wqkv,
                   const __nv_bfloat16* __restrict__ wo, const __nv_bfloat16* __restrict__ w1,
                   const __nv_bfloat16* __restrict__ b1, const __nv_bfloat16* __restrict__ w2,
                   const __nv_bfloat16* __restrict__ b2, __nv_bfloat16* __restrict__ out) {
  extern __shared__ __align__(1024) uint8_t smem_raw[];
  const uint32_t sb = (uint32_t)__cvta_generic_to_shared(smem_raw);
  const uint32_t bars = sb + OFF_BAR;
  const int warp = __shfl_sync(0xffffffffu, threadIdx.x >> 5, 0);
  const int lane = threadIdx.x & 31;
  if (warp < 3 && elect_one()) asm volatile("prefetch.tensormap [%0];" ::"l"(&maps.m[warp]) : "memory");

  const int cl = blockIdx.x >> 1, q = blockIdx.x & 1;
  const int u7 = ((cl - 36) * 37) >> 8;
  const int oct = cl < 4 ? 0 : cl < 36 ? 1 + 2 * ((cl - 4) & 7) : 2 + 2 * (cl - 36 - 7 * u7);
  const int u4 = cl < 4 ? cl : cl < 36 ? (cl - 4) >> 3 : u7;
  const int i = 2 * (oct & 7) + (u4 >> 1), p = 2 * (oct >> 3) + (u4 & 1);
  const int j = 2 * p + q;
  auto col_f = [](int jj) { return 160 * (jj >> 1) + 16 * (jj & 2) + 64 * (jj & 1); };
  auto col_r = [](int jj) { return 160 * (jj >> 1) + 128 - 64 * (jj & 2) + 16 * (jj & 1); };
  const int cF = col_f(j), cR = col_r(j), role = q ^ (p & 1);

  auto load_kv = [&](int s, int slot) {
    const uint32_t dst = sb + (s < 16 ? OFF_RING : 0) + slot * 12288, bar = bars + 8 * ((s < 16 ? RF : FE) + slot);
    mbar_expect(bar, 10240);
    tma3d(dst, &maps.m[M_KVF], bar, cF, 32 * s, 1);
    tma2d(dst + 8192, &maps.m[M_KVH], bar, 640 + 640 * role + cR - 16 * q, 32 * s);
  };
  auto load_x = [&](int c, int b, int slot) {
    mbar_expect(bars + 8 * (FX + b), 16384);
    tma2d(sb + slot * 16384, &maps.m[M_X], bars + 8 * (FX + b), 64 * c, 128 * i);
    tma2d(sb + slot * 16384 + 8192, &maps.m[M_X], bars + 8 * (FX + b), 64 * c, 128 * i + 64);
  };
  auto load_x_pair = [&](int c) {
    if (!(XMC >> c & 1)) return load_x(c, c, c);
    mbar_expect(bars + 8 * (FX + c), 16384);
    tma2d_pair(sb + c * 16384 + q * 8192, &maps.m[M_X], bars + 8 * (FX + c), 64 * c, 128 * i + 64 * q);
  };

  auto bar_init = [&](int n) { asm volatile("mbarrier.init.shared::cta.b64 [%0], 8;" ::"r"(bars + 8 * n) : "memory"); };
  TC(tc0);
  if (elect_one()) {
    if (warp == 8 || warp < 7) {
      const int n0 = warp == 8 ? RF : 1 + 5 * warp;
#pragma unroll
      for (int n = 0; n < 5; n++) bar_init(n0 + n);
      asm volatile("fence.mbarrier_init.release.cluster;" ::: "memory");
    }
    if (warp == 8) {
      bar_init(FX);
      load_x(0, 0, 0);
      load_kv(0, 0);
      load_kv(1, 1);
    }
  }
  __syncwarp();
  TC(tc1);
  asm volatile("barrier.cluster.arrive.relaxed.aligned;" ::: "memory");

  if (warp >= 8) {
    TC(tc2);
    asm volatile("barrier.cluster.wait.aligned;" ::: "memory");
    TC(tc3);
    if (warp == 8 && elect_one()) {
      load_x_pair(1);
      load_kv(2, 2);
      load_kv(3, 3);
      load_x_pair(2);
      load_kv(4, 4);
    }
    __syncwarp();
    if (warp == 8) { TL(40); }
    asm volatile("setmaxnreg.dec.sync.aligned.u32 88;");
    if (warp == 8) {
      TS(41, tc0); TS(42, tc1); TS(43, tc2); TS(19, tc3);
      uint32_t ph = 0;
      int slot = 0;
#pragma unroll 1
      for (int s = 5; s < 16; s++) {
        mbar_wait(bars + 8 * (RE + slot), ph);
        if (elect_one()) {
          load_kv(s, slot);
          if (s < 12) load_x_pair(s - 2);
          if (s < 13) asm volatile("prefetch.tensormap [%0];" ::"l"(&maps.m[s - 2]) : "memory");
        }
        if (s >= 12) {
          mbar_wait(bars + 8 * XF);
          if (elect_one()) load_kv(s + 4, s - 12);
        }
        TL(96 + s);
        if (++slot == 5) { slot = 0; ph ^= 1; }
      }
#pragma unroll 1
      for (int t = 0; t < 10; t++) {
        mbar_wait(bars + 8 * (RE + slot), ph);
        if (elect_one()) {
          const uint32_t dst = sb + OFF_RING + slot * 12288, bar = bars + 8 * (RF + slot);
          const int k0 = 64 * (t < 7 ? t + 3 : t - 7);
          mbar_expect(bar, 10240);
          tma3d(dst, &maps.m[M_Q2], bar, 0, k0, 5 * p + 3 * q);
          tma2d(dst + 8192, &maps.m[M_QR], bar, 80 * j + 64 - 64 * q, k0);
          if (t >= 6 && t < 9) load_x(t - 6, t + 4, t - 2);
        }
        TL(116 + t);
        if (++slot == 5) { slot = 0; ph ^= 1; }
      }
#pragma unroll 1
      for (int n = 0; n < 32; n += 4) {
        mbar_wait(bars + 8 * (RE + ((0x00432221u >> n) & 15)), n >= 24);
        if (n >= 8) mbar_wait(bars + 8 * (FWO + ((0x41765320u >> (n - 8)) & 7)));
        const int t = (0x41765320u >> n) & 7, k0 = 80 * (t == 0 ? j : t - (t <= j));
        if (elect_one()) {
          const uint32_t dst = sb + 10 * PAGE + (t < 2 ? t ^ 1 : t) * 15360, bar = bars + 8 * (FWO + t);
          mbar_expect(bar, 12800);
          tma3d(dst, &maps.m[M_WO2], bar, 0, k0, cF >> 5);
          tma2d(dst + 10240, &maps.m[M_WOR], bar, cR, k0);
        }
        TL(128 + n / 4);
      }
#pragma unroll 1
      for (int t = 0; t < 8; t++) {
        const uint32_t wb = bars + 8 * (t == 0 ? FWO + 1 : t < 5 ? DW + 2 * t - 1 : DF + t - 5);
        const int jj = t == 0 ? j : t - (t <= j);
        mbar_wait(wb);
        if (t) mbar_wait(wb + 64);
        if (t == 1 || t == 3) mbar_wait(bars + 8 * (SH + (t >> 1)));
        if (elect_one()) {
          const uint32_t dst = sb + (7 + 3 * (t < 5 ? t : t - 5)) * PAGE, bar = bars + 8 * (FW1 + t);
          mbar_expect(bar, 30720);
          tma3d(dst, &maps.m[M_W1], bar, 0, col_f(jj), 3 * j);
          tma3d(dst + 24576, &maps.m[M_W1R], bar, 0, col_r(jj), 3 * j);
        }
        TL(136 + t);
      }
#pragma unroll 1
      for (int t = 0; t < 12; t++) {
        const int t6 = t < 6 ? t : t - 6;
        const uint32_t wb = bars + 8 * (t < 6 ? DF + ((0x776544 >> (4 * t)) & 7) : DG + t6);
        const int uu = (0xA95024 >> (2 * t)) & 3, n = (0x924900 >> (2 * t)) & 3;
        const int k0 = 192 * (t < 3 ? j : 2 * (n + (n >= p)) + q) + 64 * uu;
        const uint32_t dst = sb + OFF_W2 + ((0x321045 >> (4 * t6)) & 7) * 24576, bar = bars + 8 * (FW2 + t);
        mbar_wait(wb);
        mbar_wait(wb + (t < 6 ? 64 : 96));
        if (elect_one()) {
          mbar_expect(bar, 20480);
          tma2d(dst, &maps.m[M_W2F], bar, cF, k0);
          tma2d(dst + 8192, &maps.m[M_W2F], bar, cF + 64 - 128 * q, k0);
          tma2d(dst + 16384, &maps.m[M_W2H], bar, cR - 16 * q, k0);
        }
        TL(144 + t);
      }
    } else {
      uint32_t epoch;
      asm volatile("ld.relaxed.gpu.global.u32 %0, [%1];" : "=r"(epoch) : "l"(&g_epoch) : "memory");
      epoch += 1;
      const int unit = i * 8 + j, hw = warp - 9, ht = hw * 32 + lane;
      const int part = unit & 3, cg = unit >> 2;
      auto colsum = [&](const __nv_bfloat16* wm, int ld, uint4* dst, bool active, bool first) {
        const int r4 = lane >> 3, v8 = lane & 7;
        const __nv_bfloat16* wp = wm + (part * 160 + 4 * hw + r4) * ld + 64 * cg + 8 * v8;
        uint4 v[14];
#pragma unroll
        for (int m = 0; m < 14; m++) {
          v[m] = make_uint4(0, 0, 0, 0);
          if (active && (m < 13 || hw == 0))
            asm volatile("ld.global.nc.v4.u32 {%0,%1,%2,%3}, [%4];" : "=r"(v[m].x), "=r"(v[m].y), "=r"(v[m].z), "=r"(v[m].w) : "l"(wp));
          wp += 12 * ld;
        }
        if (first && elect_one()) {
#pragma unroll 1
          for (int n = 0; n < 50; n += 10) {
#pragma unroll
            for (int e = 0; e < 10; e++) bar_init(FWO + 50 * hw + n + e);
          }
          mbar_expect(bars + 8 * (RX + hw), hw == 2 ? 8192 : 10240);
        }
        __syncwarp();
        float d[8];
#pragma unroll
        for (int e = 0; e < 8; e++) d[e] = 0.f;
#pragma unroll
        for (int m = 0; m < 14; m++) {
          d[0] += bf_lo(v[m].x); d[1] += bf_hi(v[m].x); d[2] += bf_lo(v[m].y); d[3] += bf_hi(v[m].y);
          d[4] += bf_lo(v[m].z); d[5] += bf_hi(v[m].z); d[6] += bf_lo(v[m].w); d[7] += bf_hi(v[m].w);
        }
#pragma unroll 1
        for (int o = 8; o < 32; o <<= 1) {
#pragma unroll
          for (int e = 0; e < 8; e++) d[e] += __shfl_xor_sync(0xffffffffu, d[e], o);
        }
        if (r4 & 2) { d[0] = d[4]; d[1] = d[5]; d[2] = d[6]; d[3] = d[7]; }
        if (r4 & 1) { d[0] = d[2]; d[1] = d[3]; }
        const uint32_t red = sb + OFF_SCR + lane * 8;
#pragma unroll 1
        for (int h = 0; h < 2; h++) {
          if (hw == h) sts64(red, __float_as_uint(d[0]), __float_as_uint(d[1]));
          named_bar<2, 96>();
          if (hw == h + 1) {
            const float2 a = lds64(red);
            d[0] += a.x;
            d[1] += a.y;
          }
        }
        if (hw == 2 && active) ll_store(dst + part * 1728 + 32 * cg + 4 * v8 + r4, d[0], d[1], epoch);
      };
      if (part >= 2) mbar_wait_wd(bars + 8 * (FX + 2 * part - 4));
#pragma unroll 1
      for (int pass = 0; pass < 2; pass++) {
        colsum(pass ? w1 : wqkv, pass ? 1536 : 1920, g_cs + 960 * pass, cg < (pass ? 24 : 30), !pass);
        if (pass) break;
        if (hw == 2) {
          TL(8);
          mbar_wait_wd(bars + 8 * ST1);
          if (lane < 2) {
            const uint32_t nb = lane ? 15360 : 6400;
            l2_prefetch(reinterpret_cast<const uint8_t*>(lane ? w2 : wo) + blockIdx.x * nb, nb);
          }
          uint4 v[4];
          ll_wait(v, g_ln1 + 128 * i + lane, 32, epoch);
#pragma unroll
          for (int m = 0; m < 4; m++) {
            const float nm = __uint_as_float(v[m].x) * (-1.f / 640.f);
            const float rstd = rsqrtf(fmaxf(fmaf(-nm, nm, __uint_as_float(v[m].z) * (1.f / 640.f)), 0.f) + 1e-5f);
            sts64(sb + OFF_LN1 + (lane + 32 * m) * 8, __float_as_uint(rstd), __float_as_uint(nm));
          }
          TL(10);
        } else {
          const int n = 4 * min(ht, 59);
          int col;
          if (n < 160) col = n + (n < 64 ? 640 + cF : n < 128 ? 1216 + cF : 512 + 640 * role + cR - 16 * q);
          else col = 80 * j + n - 160 + (q ? (n < 224 ? 16 : -64) : 0);
          mbar_wait(bars + 8 * (FX + 7));
          uint4 v[8];
          ll_wait2(v, g_cs + (col >> 1), epoch);
#pragma unroll
          for (int e = 0; e < 2; e++)
            rk1_store(sb + OFF_RK1 + n * 16 + 32 * e,
                      make_float2((__uint_as_float(v[e].x) + __uint_as_float(v[2 + e].x)) + (__uint_as_float(v[4 + e].x) + __uint_as_float(v[6 + e].x)),
                                  (__uint_as_float(v[e].z) + __uint_as_float(v[2 + e].z)) + (__uint_as_float(v[4 + e].z) + __uint_as_float(v[6 + e].z))), 0);
        }
        fence_async_smem();
        __syncwarp();
        mbar_arrive_if0(lane, bars + 8 * SIDE, hw == 2 ? 2 : 3);
        if (hw == 0) TL(11);
        mbar_wait_wd(bars + 8 * SIDE);
      }
      {
        if (hw == 2) {
          mbar_wait_wd(bars + 8 * ZK);
#pragma unroll 1
          for (int m = 0; m < 30; m += 3) {
#pragma unroll
            for (int e = 0; e < 3; e++) sts128(sb + OFF_KVB + ((m + e) * 32 + lane) * 16, 0, 0, 0, 0);
          }
        }
        mbar_wait_wd(bars + 8 * RKV);
        if (hw == 2) {
          if (elect_one()) {
            bulk_store(g_kv1 + (j * 16 + i) * 880, sb + OFF_KVP, 7040);
            asm volatile("cp.async.bulk.commit_group;" ::: "memory");
          }
        } else {
          const int hc = min(ht, 59), r5 = (hc * 43) >> 9;
          const float2* src = g_kv1 + j * 16 * 880 + (5 * i + r5) * 11 + min(hc - 12 * r5, 10);
          const uint32_t tag = epoch & 15;
          float sa, sc;
          uint32_t bad;
          int it = 0;
          do {
            uint32_t a[16], b[16];
#pragma unroll
            for (int m = 0; m < 16; m++)
              asm volatile("ld.relaxed.gpu.global.v2.u32 {%0,%1}, [%2];" : "=r"(a[m]), "=r"(b[m]) : "l"(src + m * 880) : "memory");
            sa = sc = 0.f;
            bad = 0;
#pragma unroll
            for (int m = 0; m < 16; m++) {
              bad |= (a[m] ^ tag) | (b[m] ^ tag);
              sa += __uint_as_float(a[m]);
              sc += __uint_as_float(b[m]);
            }
          } while (__any_sync(0xffffffffu, bad & 15) && ++it < SPIN_LIMIT);
          asm volatile("st.relaxed.gpu.global.v2.u32 [%0], {%1,%2};" ::"l"(g_kv2 + j * 960 + i * 60 + hc), "r"(pack2(sa, sc)), "r"(epoch) : "memory");
        }
        if (hw == 0) TL(5);
        named_bar<2, 96>();
        {
          uint4 v[5];
          ll_wait(v, reinterpret_cast<const uint4*>(g_kv2 + j * 960) + ht, 96, epoch);
          if (hw == 0) TL(6);
          const int d0 = ht / 6, part = ht - 6 * d0;
#pragma unroll
          for (int m = 0; m < 5; m++) {
            const int d = d0 + 16 * m, head = (d * 205) >> 12, n = 20 * head + 4 * part;
            const uint32_t a = sb + OFF_KVB + d * 16;
            const uint32_t z = head & 1 ? v[m].x << 16 : v[m].x & 0xffffu;
            if (part < 5) sts64(a + (n >> 3) * 1280 + (n & 7) * 2, v[m].x, v[m].z);
            else sts128(a + (10 + (head >> 1)) * 1280, z, z, z, z);
          }
        }
        fence_async_smem();
        __syncwarp();
        mbar_arrive_if0(lane, bars + 8 * KVB, hw == 2 ? 2 : 3);
        if (hw == 0) TL(7);
      }

      if (hw == 2) {
#pragma unroll 1
        for (int n = lane; n < 96; n += 32) {
          const uint32_t bb = *reinterpret_cast<const uint32_t*>(b1 + 192 * j + 2 * n);
          if (n < 40) {
            const uint32_t b = *reinterpret_cast<const uint32_t*>(b2 + (n < 32 ? cF + 2 * n : cR + 2 * n - 64));
            sts64(sb + OFF_B2 + n * 8, b << 16, b & 0xffff0000u);
          }
          rk1_store(sb + OFF_RK1 + n * 32, ll_sum4(g_cs + 960 + 96 * j + n, epoch), bb);
        }
        fence_async_smem();
        __syncwarp();
        mbar_arrive_if0(lane, bars + 8 * SIDE2, 8);
        TL(18);
#pragma unroll 1
        for (int s = 0; s < 2; s++) {
          uint8_t* dst = g_act + ((64 + 2 * i + s) * 8 + j) * 24576;
          mbar_wait_wd(bars + 8 * (AF + 12 * s + 1));
          if (lane == 0) bulk_store(dst + 8192, sb + s * OFF_R1 + 8192, 8192);
          __syncwarp();
          mbar_wait_wd(bars + 8 * (AF + 12 * s + 2));
          if (lane == 0) {
            bulk_store(dst + 16384, sb + s * OFF_R1 + 16384, 8192);
            bulk_commit_wait();
            mbar_arrive(bars + 8 * (DG + 12 * s + 1), 4);
            mbar_arrive(bars + 8 * (DG + 12 * s + 2), 4);
            fence_gpu();
            st_flag(g_flag + (64 + 2 * i + s) * 32 + 8 + j, epoch);
          }
          __syncwarp();
          TL(50 + s);
        }
        mbar_wait_wd(bars + 8 * END);
        if (blockIdx.x == 0 && lane == 0) g_epoch = epoch;
      } else {
        const int s = hw;
#pragma unroll 1
        for (int ph = 0; ph < 3; ph++) {
          const uint32_t ab = bars + 8 * (ph < 2 ? AO + 16 * ph + 8 * s : AF + 12 * s);
          const uint32_t bytes = ph < 2 ? 10240 : 8192;
          uint8_t* gb = g_act + (ph * 32 + 2 * i + s) * 8 * 24576;
          uint32_t* fl = g_flag + (ph * 32 + 2 * i + s) * 32;
          const int r = min(lane, 8);
          int cc = r + (r >= j), bit = cc, slot, wb, off = 0;
          if (ph == 0) {
            slot = r < 5 ? r + 2 : r == 5 ? 1 : 2 * s;
            wb = DW + (s ? (r < 6 ? r + 1 : 9) : (r < 6 ? 8 : 0));
          } else if (ph == 1) {
            slot = (0x1249u >> (2 * r)) & 3;
            wb = r < 2 ? DW + 15 : DF + 8 * s + r - 2;
          } else {
            const int uu = (r * 11) >> 5, n = r - 3 * uu;
            cc = 2 * (n + (n >= p)) + q;
            bit = cc + (uu ? 8 : 0);
            off = uu * 8192;
            slot = (r + 3) & 3;
            wb = r ? DG + 12 * s + r - 1 : DF + 8 * s + 7;
          }
          const uint32_t fb = ab + 8 * r + (ph < 2 ? 8 : 24), wbar = bars + 8 * wb;
          const uint32_t dst = sb + (ph ? s * OFF_R1 : 0) + slot * bytes;
          const uint8_t* src = gb + cc * 24576 + off;
          uint32_t pm = ph < 2 ? 0x7fu : 0x1ffu, seen = 0;
          if (pm >> lane & 1) mbar_expect(fb, bytes);
          __syncwarp();
          mbar_wait(ab);
          if (ph == 0 && s == 1) mbar_wait(bars + 8 * SO);
          if (elect_one()) {
            bulk_store(gb + j * 24576, sb + s * (ph ? OFF_R1 : PAGE), bytes);
            bulk_commit_wait();
            if (ph == 0) mbar_arrive(bars + 8 * (DW + 8 * s), 4);
            if (ph == 1 || ph + s == 0) mbar_arrive(bars + 8 * (SO + ph + s), 8);
            fence_gpu();
            st_flag(fl + j, epoch);
          }
          __syncwarp();
          TL(44 + 2 * ph + s);
          do {
            const int next = __ffs(pm) - 1;
            while (!(seen >> next & 1)) {
              seen = __ballot_sync(0xffffffffu, ld_acq(fl + bit) == epoch);
              fence_async_global();
            }
            if (next == 0) TL(52 + 2 * ph + s);
            mbar_wait(__shfl_sync(0xffffffffu, wbar, next));
            uint32_t ok;
            asm volatile("{.reg .pred p; mbarrier.test_wait.parity.shared::cta.b64 p, [%1], 0; selp.u32 %0, 1, 0, p;}" : "=r"(ok) : "r"(wbar) : "memory");
            ok &= (pm & seen) >> lane;
            if (ok) bulk_load(dst, src, bytes, fb);
            pm &= ~__ballot_sync(0xffffffffu, ok);
          } while (pm);
        }
      }
    }
  } else {
    asm volatile("barrier.cluster.wait.aligned;" ::: "memory");
    TC(tc4);
    uint32_t epoch;
    asm volatile("ld.relaxed.gpu.global.u32 %0, [%1];" : "=r"(epoch) : "l"(&g_epoch) : "memory");
    epoch += 1;
    const int s = warp >> 2, w = warp & 3, tid = threadIdx.x & 127, c = lane & 3, g = lane >> 2;
    uint32_t sb_peer;
    asm volatile("mapa.shared::cluster.u32 %0, %1, %2;" : "=r"(sb_peer) : "r"(sb), "r"(q ^ 1));
    const int row0 = 128 * i + 64 * s + 16 * w;
    const uint32_t bs8 = bars + 64 * s, bs12 = bars + 96 * s;
    uint32_t pq[20], hp[20];
    {
      float acc[80];
      const Desc dx = mkdesc(s * 512, 0, 16, 1024, 1);
      const int srow = 16 * j + 2 * warp + (lane >> 4);
      float sm = 0.f, sq = 0.f;
      float4 u;
      auto load_res = [&]() {
        const uint32_t xa = sb + (64 * s + 16 * w + (lane & 15)) * 128;
#pragma unroll
        for (int ks = 0; ks < 5; ks++) {
          const int col = ks < 4 ? cF + 16 * ks : cR;
          ldsm4(xa + (col >> 6) * 16384 + (((((col & 63) >> 3) + (lane >> 4)) ^ (lane & 7)) << 4), hp + 4 * ks);
        }
      };
#pragma unroll
      for (int st = 0; st < 20; st++) {
        if ((st & 1) == 0 && st <= 8) mbar_wait(bars + 8 * (FX + (st >> 1)));
        mbar_wait(bars + 8 * (st < 16 ? RF + st % 5 : FE + st - 16), st < 16 ? (st / 5) & 1 : 0);
        const Desc da = dx + (st >> 1) * 1024 + (st & 1) * 4;
        const Desc db = mkdesc(0, st < 16 ? OFF_RING + (st % 5) * 12288 : (st - 16) * 12288, 4096, 1024, 1);
        wg_fence();
        wgmma_ss<160, 0, 1>(acc, da, db, st != 0);
        wgmma_ss<160, 0, 1>(acc, da + 2, db + 128, 1);
        wg_commit();
        TL0(64 + st);
        if (st == 0) { TL0(0); TS(38, tc4); TS(62, (uint32_t)tl_gt); }
        if (st == 1) asm volatile("setmaxnreg.inc.sync.aligned.u32 208;");
        if (st >= 5 && st <= 13 && (st & 1)) {
          const float uu[4] = {u.x, u.y, u.z, u.w};
#pragma unroll
          for (int e = 0; e < 4; e++) {
            const float a = bf_lo(__float_as_uint(uu[e])), b = bf_hi(__float_as_uint(uu[e]));
            sm += a + b;
            sq = fmaf(a, a, fmaf(b, b, sq));
          }
        }
        if (st >= 4 && st <= 12 && (st & 1) == 0) {
          if (st > 8) mbar_wait(bars + 8 * (FX + st - 4));
          if (st > 6) mbar_wait(bars + 8 * (FX + st - 3));
          u = lds128(sb + (st - 4 + ((lane >> 3) & 1)) * 16384 + srow * 128 + (lane & 7) * 16);
        }
        if (st == 13 || st == 14) {
#pragma unroll
          for (int o = st == 13 ? 1 : 4; o < (st == 13 ? 4 : 16); o <<= 1) {
            sm += __shfl_xor_sync(0xffffffffu, sm, o);
            sq += __shfl_xor_sync(0xffffffffu, sq, o);
          }
        }
        if (st == 14) {
          if ((lane & 15) == 0) ll_store(g_ln1 + 128 * i + srow, sm, sq, epoch);
          mbar_arrive_if0(lane, bars + 8 * ST1, 1);
          TL0(39);
        }
        if (st == 8 && p < 2) load_res();
        if (st == 9) mbar_arrive_if0(lane, bars + 8 * XF, 1);
        if (st == 16 && p >= 2) load_res();
        if (st > 0) {
          wg_wait<1>();
          if (st <= 16) mbar_arrive_if0(lane, bars + 8 * (RE + (st - 1) % 5), 1);
        }
      }
      TL0(12);
      float accq[40];
      auto q_step = [&](int t) {
        if (t >= 7) mbar_wait(bars + 8 * (FX + 3 + t));
        mbar_wait(bars + 8 * (RF + (t + 1) % 5), ((t + 16) / 5) & 1);
        const Desc da = dx + (t < 7 ? t + 3 : t - 3) * 1024, db = mkdesc(0, OFF_RING + ((t + 1) % 5) * 12288, 4096, 512, 2);
        wg_fence();
#pragma unroll
        for (int ks = 0; ks < 4; ks++) wgmma_ss<80, 0, 1>(accq, da + 2 * ks, db + 64 * ks, 1);
        wg_commit();
        TL0(84 + t);
      };
      mbar_wait(bars + 8 * SIDE);
      float a1[2], a2[2];
      uint32_t rk[2];
#pragma unroll
      for (int r = 0; r < 2; r++) {
        const float2 st = lds64(sb + OFF_LN1 + (64 * s + 16 * w + g + 8 * r) * 8);
        a1[r] = st.x;
        a2[r] = st.x * LOG2E;
        rk[r] = rk1_frag(st.y, 0.f, c);
      }
      wg_fence();
      wgmma_rs<160, 0>(acc, rk[0], rk[1], 0, 0, mkdesc(0, OFF_RK1, 0, 128, 0), 1);
      wg_commit();
      wgmma_rs<80, 0>(accq, rk[0], rk[1], 0, 0, mkdesc(0, OFF_RK1 + 2560, 0, 128, 0), 0);
      q_step(0);
      const int hi = lane >> 4;
      const uint32_t rowoff = sb + (64 * s + 16 * w + (lane & 15)) * 16;
      const uint32_t remoff = sb_peer + (64 * s + 16 * w) * 16 + lane * 4;
      auto put_remote = [&](const uint32_t* r, uint32_t a) {
#pragma unroll
        for (int e = 0; e < 4; e++)
          asm volatile("st.async.shared::cluster.mbarrier::complete_tx::bytes.b32 [%0], %1, [%2];"
                       ::"r"(a + (e >> 1) * 2048 + (e & 1) * 128), "r"(r[e]), "r"(sb_peer + OFF_BAR + 8 * RXK) : "memory");
      };
      const int mF = 2 * (p & 1) - q, g0 = 2 * mF + hi;
      const uint32_t ka = rowoff + g0 * 2048;
      wg_wait<1>();
      reg_fence(acc);
      mbar_arrive_if0(lane, bars + 8 * KD, 1);
      mbar_arrive_remote_if0(lane, sb_peer + OFF_BAR + 8 * PX);
      TL0(1);
      uint32_t r[4], r2[4];
      if (role == 0) {
        ln_pair<true>(acc + 64, a1, a2, r);
        ln_pair<true>(acc + 72, a1, a2, r2);
        mbar_wait_cluster(bars + 8 * PX);
        put_remote(r, remoff + (q ? 0 : 6 * 2048));
        put_remote(r2, remoff + (q ? 2 * 2048 : 8 * 2048));
      } else {
        ln_pair<false>(acc + 64, a1, a2, r);
        ln_pair<false>(acc + 72, a1, a2, r2);
        const uint32_t a = rowoff + (hi + (q ? 17 : 10)) * 2048;
        mbar_wait(bars + 8 * KD);
        stsm4(a, r[0], r[1], r[2], r[3]);
        stsm4(a + 4096, r2[0], r2[1], r2[2], r2[3]);
      }
      q_step(1);
#pragma unroll
      for (int n = 0; n < 4; n++) {
        const int P = n == 0 ? 0 : n == 1 ? 3 : n - 1;
        ln_pair<true>(acc + 8 * P, a1, a2, r);
        ln_pair<false>(acc + 32 + 8 * P, a1, a2, r2);
        if (n == 0) mbar_wait(bars + 8 * KD);
        if (n < 2 && mF == (n ? 2 : -1)) {
          mbar_wait_cluster(bars + 8 * PX);
          put_remote(r, remoff + (n ? 0 : 8 * 2048));
          put_remote(r2, remoff + (n ? 10 * 2048 : 19 * 2048));
        } else {
          stsm4(ka + P * 4096, r[0], r[1], r[2], r[3]);
          stsm4(ka + P * 4096 + (g0 + 2 * P > 4 ? 11 * 2048 : 10 * 2048), r2[0], r2[1], r2[2], r2[3]);
        }
        if (n == 0) {
          wg_wait<1>();
          mbar_arrive_if0(lane, bars + 8 * (RE + 1), 1);
          mbar_arrive_if0(lane, bars + 8 * ZK, 1);
        }
        if (n == 1) q_step(2);
        if (n == 2) {
          wg_wait<1>();
          mbar_arrive_if0(lane, bars + 8 * (RE + 2), 1);
        }
      }
      sts128(rowoff + 15 * 2048, ONES, ONES, ONES, ONES);
      TL0(2);
      mbar_wait_cluster(bars + 8 * RXK);
      fence_async_smem();
      named_bar<1, 256>();
      TL0(3);
      float kv[24];
      {
        const Desc da = mkdesc(s * 640, 0, 128, 2048, 0), db = da + 1280;
        wg_fence();
#pragma unroll
        for (int kk = 0; kk < 8; kk++) wgmma_ss<48, 1, 1>(kv, da + 16 * kk, db + 16 * kk, kk != 0);
        wg_commit();
      }
      wg_wait<1>();
      mbar_arrive_if0(lane, bars + 8 * (RE + 3), 1);
      q_step(3);
      {
        const uint32_t tag = epoch & 15;
        wg_wait<1>();
        reg_fence(kv);
        TL0(4);
#pragma unroll
        for (int hh = 0; hh < 2; hh++) {
          const int r = 16 * w + g + 8 * hh, eb = c - 4 * s - (r < 20 ? 0 : r < 40 ? 10 : 99);
          const uint32_t a = sb + OFF_KVP + (40 * s + r) * 88;
#pragma unroll
          for (int tt = 0; tt < 7; tt++) {
            const float v0 = tt < 6 ? kv[4 * tt + 2 * hh] : s ? kv[2 * hh] : kv[20 + 2 * hh];
            const float v1 = tt < 6 ? kv[4 * tt + 2 * hh + 1] : v0;
            asm volatile("{.reg .pred p; .reg .b32 a, b; setp.lt.u32 p, %3, %4; lop3.b32 a, %1, %5, 15, 0xD8; lop3.b32 b, %2, %5, 15, 0xD8;"
                         "@p st.shared.v2.u32 [%0], {a, b};}"
                         ::"r"(tt < 6 ? a + 8 * eb + 32 * tt : a + 80), "r"(__float_as_uint(v0)), "r"(__float_as_uint(v1)),
                         "r"(tt < 6 ? eb + 4 * tt : r), "r"(tt < 6 ? 10 : 40), "r"(tag) : "memory");
          }
        }
        fence_async_smem();
        __syncwarp();
      }
      mbar_arrive_if0(lane, bars + 8 * RKV, 1);
      TL0(9);
#pragma unroll
      for (int t = 4; t < 10; t++) {
        q_step(t);
        wg_wait<1>();
        mbar_arrive_if0(lane, bars + 8 * (RE + t % 5), 1);
      }
      wg_wait<0>();
      reg_fence(accq);
      mbar_arrive_if0(lane, bars + 8 * RE, 1);
      TL0(13);
#pragma unroll
      for (int P = 0; P < 5; P++) ln_pair<true>(accq + 8 * P, a1, a2, pq + 4 * P);
      reg_fence(pq);
      TL0(14);
    }
    const uint32_t rs = sb + s * OFF_R1;
    const uint32_t stoff = (lane >> 4) * 1024 + (16 * w + (lane & 15)) * 16;
    const Desc drs = mkdesc(s * (OFF_R1 / 16), 0, 1024, 128, 0);
    float accg[80];
    {
      {
        float o[48];
        wg_fence();
        mbar_wait(bars + 8 * (s ? OM : KVB));
        TL0(15);
#pragma unroll
        for (int ks = 0; ks < 5; ks++)
          wgmma_rs<96, 1>(o, pq[4 * ks], pq[4 * ks + 1], pq[4 * ks + 2], pq[4 * ks + 3], mkdesc(ks < 4 ? 16 * q : -64 * q, OFF_KVB + 256 * ks, 128, 1280, 0), ks != 0);
        wg_commit();
        mbar_arrive_if0(lane | s, bars + 8 * OM, 2);
        wg_wait<0>();
        reg_fence(o);
        float inv[2][4];
#pragma unroll
        for (int hh = 0; hh < 2; hh++)
#pragma unroll
          for (int h = 0; h < 4; h++) inv[hh][h] = rcp(o[40 + 4 * (h >> 1) + 2 * hh + (h & 1)] + 1e-6f);
        uint32_t r[4];
#pragma unroll
        for (int t = 0; t < 10; t++) {
#pragma unroll
          for (int hh = 0; hh < 2; hh++) {
            const float f = t == 2 ? (c < 2 ? inv[hh][0] : inv[hh][1]) : t == 7 ? (c < 2 ? inv[hh][2] : inv[hh][3]) : inv[hh][(8 * t) / 20];
            r[2 * (t & 1) + hh] = pack2(o[4 * t + 2 * hh] * f, o[4 * t + 2 * hh + 1] * f);
          }
          if (t & 1) stsm4(sb + s * PAGE + stoff + (t >> 1) * 2048, r[0], r[1], r[2], r[3]);
        }
        fence_async_smem();
        __syncwarp();
        mbar_arrive_if0(lane, bs8 + 8 * AO, 2);
        TLW(16 + s);
      }
      float acc[40];
#pragma unroll
      for (int r = 0; r < 20; r++) { acc[2 * r] = bf_lo(hp[r]); acc[2 * r + 1] = bf_hi(hp[r]); }
      reg_fence(acc);
#pragma unroll
      for (int t = 0; t < 8; t++) {
        mbar_wait(bars + 8 * (FWO + t));
        mbar_wait(bs8 + 8 * (AO + t));
        TLW(160 + 8 * s + t);
        if (t == 1) TLW(20 + s);
        const Desc da = mkdesc(t == 0 ? s * 640 : t == 7 ? s * 1280 : 0, (t == 0 || t == 7 ? 0 : t < 6 ? t + 1 : 1) * PAGE, 1024, 128, 0);
        const Desc db = mkdesc(0, 10 * PAGE + (t < 2 ? t ^ 1 : t) * 15360, 5120, 512, 2);
        wg_fence();
#pragma unroll
        for (int ks = 0; ks < 5; ks++) wgmma_ss<80, 0, 1>(acc, da + 128 * ks, db + 64 * ks, 1);
        wg_commit();
        if (t == 0) wg_wait<0>();
        else if (t > 1) wg_wait<1>();
        if (t != 1) mbar_arrive_if0(lane, bs8 + 8 * (DW + (t ? t - 1 : 0)), t ? 2 : 1);
      }
      wg_wait<0>();
      reg_fence(acc);
      mbar_arrive_if0(lane, bs8 + 8 * (DW + 7), 2);
      TLW(22 + s);
#pragma unroll
      for (int r = 0; r < 20; r++) hp[r] = pack2(acc[2 * r], acc[2 * r + 1]);
      mbar_wait(bs8 + 8 * (DW + 7));
#pragma unroll
      for (int ks = 0; ks < 5; ks++)
        stsm4(rs + stoff + ks * 2048, hp[4 * ks], hp[4 * ks + 1], hp[4 * ks + 2], hp[4 * ks + 3]);
      fence_async_smem();
      __syncwarp();
      mbar_arrive_if0(lane, bs8 + 8 * AH, 2);
      reg_fence(hp);
      TLW(24 + s);
    }
    float accf[96];
    uint4 hs[4];
    const uint4* hsp = g_hstat + ((2 * i + s) * 8 + 2 * c) * 64 + 16 * w + g;
    uint32_t rk[2];
    float3 gk[2];
#pragma unroll
    for (int t = 0; t < 8; t++) {
      mbar_wait(bars + 8 * (FW1 + t));
      mbar_wait(bs8 + 8 * (AH + t));
      TLW(176 + 8 * s + t);
      if (t == 1) TLW(26 + s);
      const Desc da = drs + (t % 3) * (PAGE / 16), db = mkdesc(0, (7 + 3 * (t % 5)) * PAGE, 8192, 1024, 1);
      wg_fence();
#pragma unroll
      for (int ks = 0; ks < 4; ks++) wgmma_ss<192, 0, 1>(accf, da + 128 * ks, db + 128 * ks, (t | ks) != 0);
      wgmma_ss<192, 0, 1>(accf, da + 512, mkdesc(0, (7 + 3 * (t % 5)) * PAGE + 24576, 2048, 1024, 1), 1);
      if (t == 7) wgmma_rs<192, 0>(accf, rk[0], rk[1], 0, 0, mkdesc(0, OFF_RK1, 0, 128, 0), 1);
      wg_commit();
      if (t == 5) {
        while (__any_sync(0xffffffffu, ((hs[0].y ^ epoch) | (hs[0].w ^ epoch) | (hs[1].y ^ epoch) | (hs[1].w ^ epoch) | (hs[2].y ^ epoch) |
                                        (hs[2].w ^ epoch) | (hs[3].y ^ epoch) | (hs[3].w ^ epoch)) != 0)) {
#pragma unroll
          for (int m = 0; m < 4; m++) hs[m] = ll_load(hsp + (m >> 1) * 64 + 8 * (m & 1));
        }
#pragma unroll
        for (int hh = 0; hh < 2; hh++) {
          float sm = __uint_as_float(hs[hh].x) + __uint_as_float(hs[2 + hh].x), sq = __uint_as_float(hs[hh].z) + __uint_as_float(hs[2 + hh].z);
#pragma unroll
          for (int o = 1; o < 4; o <<= 1) {
            sm += __shfl_xor_sync(0xffffffffu, sm, o);
            sq += __shfl_xor_sync(0xffffffffu, sq, o);
          }
          gk[hh].x = sm;
          gk[hh].y = sq;
        }
      }
      if (t == 6) {
#pragma unroll
        for (int hh = 0; hh < 2; hh++) {
          const float mean = gk[hh].x * (1.f / 640.f), var = fmaxf(fmaf(-mean, mean, gk[hh].y * (1.f / 640.f)), 0.f) + 1e-5f;
          const float a = rsqrtf(var);
          rk[hh] = rk1_frag(-mean, var * a, c);
          gk[hh] = make_float3(0.7978845608028654f * a, 0.7978845608028654f * 0.044715f * a * a * a, 0.5f * a);
        }
      }
      if (t == 0) {
        float sm[2] = {0.f, 0.f}, sq[2] = {0.f, 0.f};
        mbar_wait(bars + 8 * SIDE2);
#pragma unroll
        for (int m = 0; m < 10; m++) {
          const float2 b = lds64(sb + OFF_B2 + (8 * m + 2 * c) * 4);
#pragma unroll
          for (int hh = 0; hh < 2; hh++) {
            const float h0 = bf_lo(hp[2 * m + hh]), h1 = bf_hi(hp[2 * m + hh]);
            sm[hh] += h0 + h1;
            sq[hh] = fmaf(h0, h0, fmaf(h1, h1, sq[hh]));
            const float v0 = b.x + h0, v1 = b.y + h1;
            const int e = 4 * m + 2 * hh;
            if (m < 8) { accg[e] = v0; accg[e + 1] = v1; accg[32 + e] = 0.f; accg[33 + e] = 0.f; }
            else { accg[e + 32] = q ? 0.f : v0; accg[e + 33] = q ? 0.f : v1; accg[e + 40] = q ? v0 : 0.f; accg[e + 41] = q ? v1 : 0.f; }
          }
        }
        reg_fence(accg);
#pragma unroll
        for (int o = 1; o < 4; o <<= 1) {
#pragma unroll
          for (int hh = 0; hh < 2; hh++) {
            sm[hh] += __shfl_xor_sync(0xffffffffu, sm[hh], o);
            sq[hh] += __shfl_xor_sync(0xffffffffu, sq[hh], o);
          }
        }
        if (c < 2) ll_store(g_hstat + ((2 * i + s) * 8 + j) * 64 + 16 * w + g + 8 * c, c ? sm[1] : sm[0], c ? sq[1] : sq[0], epoch);
        wg_wait<0>();
      } else if (t > 1) wg_wait<1>();
      if (t != 1) mbar_arrive_if0(lane, bs8 + 8 * (DF + (t ? t - 1 : 0)), 2);
      if (t == 3) {
#pragma unroll
        for (int m = 0; m < 4; m++) hs[m] = ll_load(hsp + (m >> 1) * 64 + 8 * (m & 1));
      }
    }
    wg_wait<0>();
    reg_fence(accf);
    mbar_arrive_if0(lane, bs8 + 8 * (DF + 7), 2);
    TLW(28 + s);
    auto g_step = [&](int t, int slot) {
      mbar_wait(bars + 8 * (FW2 + t));
      mbar_wait(bs12 + 8 * (AF + t));
      TLW(192 + 12 * s + t);
      if (t == 3) TLW(32 + s);
      const Desc da = mkdesc(drs.base + (t & 3) * 512, 0, 1024, 128, 0), db = mkdesc(slot * 1536, OFF_W2, 8192, 1024, 1);
      wg_fence();
#pragma unroll
      for (int ks = 0; ks < 4; ks++) wgmma_ss<160, 0, 1>(accg, da + 128 * ks, db + 128 * ks, 1);
      wg_commit();
    };
#pragma unroll 1
    for (int t = 0; t < 3; t++) {
      uint32_t r[16];
#pragma unroll
      for (int e = 0; e < 16; e++) r[e] = pack2(gelu(accf[2 * e], gk[e & 1]), gelu(accf[2 * e + 1], gk[e & 1]));
      mbar_wait(bs8 + 8 * (DF + 7));
#pragma unroll
      for (int n = 0; n < 4; n++) stsm4(rs + stoff + t * 8192 + n * 2048, r[4 * n], r[4 * n + 1], r[4 * n + 2], r[4 * n + 3]);
      fence_async_smem();
      __syncwarp();
      mbar_arrive_if0(lane, bs12 + 8 * (AF + t), 2);
#pragma unroll
      for (int e = 0; e < 64; e++) accf[e] = accf[e + 32];
      g_step(t, (0x045 >> (4 * t)) & 7);
      wg_wait<1>();
      mbar_arrive_if0(lane | (t == 0), bs12 + 8 * (DG + t - 1), 3 - t);
    }
    TLW(30 + s);
    wg_wait<0>();
    mbar_arrive_if0(lane, bs12 + 8 * (DG + 2), 1);
#pragma unroll
    for (int t = 3; t < 12; t++) {
      g_step(t, (0x321045 >> (4 * (t % 6))) & 7);
      if (t > 3) {
        wg_wait<1>();
        mbar_arrive_if0(lane, bs12 + 8 * (DG + t - 1), 2);
        if (t == 7) mbar_arrive_remote_if0(lane, sb_peer + OFF_BAR + 8 * PF);
      }
    }
    mbar_wait_cluster(bars + 8 * PF);
    wg_wait<0>();
    reg_fence(accg);
    mbar_arrive_if0(lane, bs12 + 8 * (DG + 11), 2);
    TLW(34 + s);
    {
      const uint32_t buf = OFF_W2 + 5 * 24576 + s * PAGE + tid * 16;
#pragma unroll
      for (int e = 0; e < 8; e++) {
        const float a = accg[64 + e], b = accg[72 + e];
        accg[64 + e] = q ? a : b;
        accg[72 + e] = q ? b : a;
      }
#pragma unroll
      for (int m = 0; m < 5; m++) {
        const float* a = accg + 32 + 8 * m;
        asm volatile("st.async.shared::cluster.mbarrier::complete_tx::bytes.v4.b32 [%0], {%1,%2,%3,%4}, [%5];"
                     ::"r"(sb_peer + buf + m * 2048), "r"(pack2(a[0], a[1])), "r"(pack2(a[2], a[3])), "r"(pack2(a[4], a[5])),
                     "r"(pack2(a[6], a[7])), "r"(sb_peer + OFF_BAR + 8 * (RX + s)) : "memory");
      }
      TLW(58 + s);
      mbar_wait(bs12 + 8 * (DG + 11));
      mbar_wait_cluster(bars + 8 * (RX + s));
      TLW(60 + s);
      float4 rx[5];
#pragma unroll
      for (int m = 0; m < 5; m++) rx[m] = lds128(sb + buf + m * 2048);
      const uint32_t stg = rs + w * 2816;
      const uint32_t sa = stg + (lane & 15) * 176 + (lane >> 4) * 16;
#pragma unroll
      for (int ks = 0; ks < 5; ks++) {
        const uint32_t u[4] = {__float_as_uint(rx[ks].x), __float_as_uint(rx[ks].y), __float_as_uint(rx[ks].z), __float_as_uint(rx[ks].w)};
        const float* a = accg + (ks < 4 ? 8 * ks : 72);
        stsm4(sa + ks * 32, pack2(a[0] + bf_lo(u[0]), a[1] + bf_hi(u[0])), pack2(a[2] + bf_lo(u[1]), a[3] + bf_hi(u[1])),
              pack2(a[4] + bf_lo(u[2]), a[5] + bf_hi(u[2])), pack2(a[6] + bf_lo(u[3]), a[7] + bf_hi(u[3])));
      }
      __syncwarp();
#pragma unroll
      for (int m = 0; m < 4; m++) rx[m] = lds128(stg + (4 * m + (lane >> 3)) * 176 + (lane & 7) * 16);
      rx[4] = lds128(stg + (lane >> 1) * 176 + 128 + (lane & 1) * 16);
      __nv_bfloat16* outp = out + (row0 + (lane >> 3)) * 640 + cF + (lane & 7) * 8;
#pragma unroll
      for (int m = 0; m < 4; m++) *reinterpret_cast<float4*>(outp + m * 4 * 640) = rx[m];
      *reinterpret_cast<float4*>(out + (row0 + (lane >> 1)) * 640 + cR + (lane & 1) * 8) = rx[4];
    }
    mbar_arrive_if0(lane, bars + 8 * END, 1);
    TLW(36 + s);
  }
}

typedef CUresult (*EncodeFn)(CUtensorMap*, CUtensorMapDataType, cuuint32_t, void*, const cuuint64_t*, const cuuint64_t*,
                             const cuuint32_t*, const cuuint32_t*, CUtensorMapInterleave, CUtensorMapSwizzle,
                             CUtensorMapL2promotion, CUtensorMapFloatOOBfill);

void make_map(EncodeFn enc, CUtensorMap* tm, const void* base, int rows, int cols, int box_rows, int box_cols, int group, int natom,
              CUtensorMapSwizzle sw) {
  const cuuint64_t dims[3] = {(cuuint64_t)(natom ? group : cols), (cuuint64_t)rows, (cuuint64_t)(cols / group)};
  const cuuint64_t strides[2] = {(cuuint64_t)cols * 2, (cuuint64_t)group * 2};
  const cuuint32_t box[3] = {(cuuint32_t)box_cols, (cuuint32_t)box_rows, (cuuint32_t)natom}, es[3] = {1, 1, 1};
  enc(tm, CU_TENSOR_MAP_DATA_TYPE_BFLOAT16, natom ? 3 : 2, const_cast<void*>(base), dims, strides, box, es,
      CU_TENSOR_MAP_INTERLEAVE_NONE, sw, CU_TENSOR_MAP_L2_PROMOTION_L2_128B, CU_TENSOR_MAP_FLOAT_OOB_FILL_NONE);
}

}

extern "C" void kernel_launch(void* const* d_in, const int* in_sizes, int n_in, void* d_out, int out_size) {
  const __nv_bfloat16* x = (const __nv_bfloat16*)d_in[0];
  const __nv_bfloat16* wqkv = (const __nv_bfloat16*)d_in[1];
  const __nv_bfloat16* wo = (const __nv_bfloat16*)d_in[2];
  const __nv_bfloat16* w1 = (const __nv_bfloat16*)d_in[4];
  const __nv_bfloat16* b1 = (const __nv_bfloat16*)d_in[5];
  const __nv_bfloat16* w2 = (const __nv_bfloat16*)d_in[6];
  const __nv_bfloat16* b2 = (const __nv_bfloat16*)d_in[7];

  void* fn = nullptr;
  cudaDriverEntryPointQueryResult qr;
  cudaGetDriverEntryPoint("cuTensorMapEncodeTiled", &fn, cudaEnableDefault, &qr);
  EncodeFn enc = (EncodeFn)fn;
  const CUtensorMapSwizzle S128 = CU_TENSOR_MAP_SWIZZLE_128B, S64 = CU_TENSOR_MAP_SWIZZLE_64B;
  Maps maps;
  make_map(enc, &maps.m[M_X], x, 2048, 640, 64, 64, 64, 0, S128);
  make_map(enc, &maps.m[M_KVF], wqkv, 640, 1920, 32, 64, 640, 2, S128);
  make_map(enc, &maps.m[M_KVH], wqkv, 640, 1920, 32, 32, 64, 0, S128);
  make_map(enc, &maps.m[M_Q2], wqkv, 640, 1920, 64, 32, 32, 2, S64);
  make_map(enc, &maps.m[M_QR], wqkv, 640, 1920, 64, 16, 64, 0, S64);
  make_map(enc, &maps.m[M_WO2], wo, 640, 640, 80, 32, 32, 2, S64);
  make_map(enc, &maps.m[M_WOR], wo, 640, 640, 80, 16, 64, 0, S64);
  make_map(enc, &maps.m[M_W1], w1, 640, 1536, 64, 64, 64, 3, S128);
  make_map(enc, &maps.m[M_W1R], w1, 640, 1536, 16, 64, 64, 3, S128);
  make_map(enc, &maps.m[M_W2F], w2, 1536, 640, 64, 64, 64, 0, S128);
  make_map(enc, &maps.m[M_W2H], w2, 1536, 640, 64, 32, 64, 0, S128);
  cudaFuncSetAttribute(fused_block_kernel, cudaFuncAttributeMaxDynamicSharedMemorySize, SMEM_BYTES);
  fused_block_kernel<<<128, 384, SMEM_BYTES>>>(maps, x, wqkv, wo, w1, b1, w2, b2, (__nv_bfloat16*)d_out);
}
```

```cpp
#include <cuda_runtime.h>
#include <cuda_bf16.h>
#include <cuda.h>
#include <stdint.h>

namespace {

struct Desc { uint32_t base, off, hi; };
__device__ __forceinline__ Desc operator+(Desc d, uint32_t o) { return Desc{d.base, d.off + o, d.hi}; }
template <int TA, int TB> __device__ __forceinline__ void wgmma_ss_n48(float (&d)[24], Desc a, Desc b, int sc) {
  asm volatile("{.reg .pred p; .reg .b32 t, u; .reg .b64 da, db; setp.ne.b32 p, %30, 0; add.u32 t, %24, %25; mov.b64 da, {t, %26}; add.u32 u, %27, %28; mov.b64 db, {u, %29};"
    "wgmma.mma_async.sync.aligned.m64n48k16.f32.bf16.bf16 {%0,%1,%2,%3,%4,%5,%6,%7,%8,%9,%10,%11,%12,%13,%14,%15,%16,%17,%18,%19,%20,%21,%22,%23}, da, db, p, 1, 1, %31, %32;}"
    : "+f"(d[0]),"+f"(d[1]),"+f"(d[2]),"+f"(d[3]),"+f"(d[4]),"+f"(d[5]),"+f"(d[6]),"+f"(d[7]),"+f"(d[8]),"+f"(d[9]),"+f"(d[10]),"+f"(d[11]),"+f"(d[12]),"+f"(d[13]),"+f"(d[14]),"+f"(d[15]),"+f"(d[16]),"+f"(d[17]),"+f"(d[18]),"+f"(d[19]),"+f"(d[20]),"+f"(d[21]),"+f"(d[22]),"+f"(d[23])
    : "r"(a.base), "r"(a.off), "r"(a.hi), "r"(b.base), "r"(b.off), "r"(b.hi), "r"(sc), "n"(TA), "n"(TB));
}
template <int TA, int TB> __device__ __forceinline__ void wgmma_ss_n80(float (&d)[40], Desc a, Desc b, int sc) {
  asm volatile("{.reg .pred p; .reg .b32 t, u; .reg .b64 da, db; setp.ne.b32 p, %46, 0; add.u32 t, %40, %41; mov.b64 da, {t, %42}; add.u32 u, %43, %44; mov.b64 db, {u, %45};"
    "wgmma.mma_async.sync.aligned.m64n80k16.f32.bf16.bf16 {%0,%1,%2,%3,%4,%5,%6,%7,%8,%9,%10,%11,%12,%13,%14,%15,%16,%17,%18,%19,%20,%21,%22,%23,%24,%25,%26,%27,%28,%29,%30,%31,%32,%33,%34,%35,%36,%37,%38,%39}, da, db, p, 1, 1, %47, %48;}"
    : "+f"(d[0]),"+f"(d[1]),"+f"(d[2]),"+f"(d[3]),"+f"(d[4]),"+f"(d[5]),"+f"(d[6]),"+f"(d[7]),"+f"(d[8]),"+f"(d[9]),"+f"(d[10]),"+f"(d[11]),"+f"(d[12]),"+f"(d[13]),"+f"(d[14]),"+f"(d[15]),"+f"(d[16]),"+f"(d[17]),"+f"(d[18]),"+f"(d[19]),"+f"(d[20]),"+f"(d[21]),"+f"(d[22]),"+f"(d[23]),"+f"(d[24]),"+f"(d[25]),"+f"(d[26]),"+f"(d[27]),"+f"(d[28]),"+f"(d[29]),"+f"(d[30]),"+f"(d[31]),"+f"(d[32]),"+f"(d[33]),"+f"(d[34]),"+f"(d[35]),"+f"(d[36]),"+f"(d[37]),"+f"(d[38]),"+f"(d[39])
    : "r"(a.base), "r"(a.off), "r"(a.hi), "r"(b.base), "r"(b.off), "r"(b.hi), "r"(sc), "n"(TA), "n"(TB));
}
template <int TA, int TB> __device__ __forceinline__ void wgmma_ss_n160(float (&d)[80], Desc a, Desc b, int sc) {
  asm volatile("{.reg .pred p; .reg .b32 t, u; .reg .b64 da, db; setp.ne.b32 p, %86, 0; add.u32 t, %80, %81; mov.b64 da, {t, %82}; add.u32 u, %83, %84; mov.b64 db, {u, %85};"
    "wgmma.mma_async.sync.aligned.m64n160k16.f32.bf16.bf16 {%0,%1,%2,%3,%4,%5,%6,%7,%8,%9,%10,%11,%12,%13,%14,%15,%16,%17,%18,%19,%20,%21,%22,%23,%24,%25,%26,%27,%28,%29,%30,%31,%32,%33,%34,%35,%36,%37,%38,%39,%40,%41,%42,%43,%44,%45,%46,%47,%48,%49,%50,%51,%52,%53,%54,%55,%56,%57,%58,%59,%60,%61,%62,%63,%64,%65,%66,%67,%68,%69,%70,%71,%72,%73,%74,%75,%76,%77,%78,%79}, da, db, p, 1, 1, %87, %88;}"
    : "+f"(d[0]),"+f"(d[1]),"+f"(d[2]),"+f"(d[3]),"+f"(d[4]),"+f"(d[5]),"+f"(d[6]),"+f"(d[7]),"+f"(d[8]),"+f"(d[9]),"+f"(d[10]),"+f"(d[11]),"+f"(d[12]),"+f"(d[13]),"+f"(d[14]),"+f"(d[15]),"+f"(d[16]),"+f"(d[17]),"+f"(d[18]),"+f"(d[19]),"+f"(d[20]),"+f"(d[21]),"+f"(d[22]),"+f"(d[23]),"+f"(d[24]),"+f"(d[25]),"+f"(d[26]),"+f"(d[27]),"+f"(d[28]),"+f"(d[29]),"+f"(d[30]),"+f"(d[31]),"+f"(d[32]),"+f"(d[33]),"+f"(d[34]),"+f"(d[35]),"+f"(d[36]),"+f"(d[37]),"+f"(d[38]),"+f"(d[39]),"+f"(d[40]),"+f"(d[41]),"+f"(d[42]),"+f"(d[43]),"+f"(d[44]),"+f"(d[45]),"+f"(d[46]),"+f"(d[47]),"+f"(d[48]),"+f"(d[49]),"+f"(d[50]),"+f"(d[51]),"+f"(d[52]),"+f"(d[53]),"+f"(d[54]),"+f"(d[55]),"+f"(d[56]),"+f"(d[57]),"+f"(d[58]),"+f"(d[59]),"+f"(d[60]),"+f"(d[61]),"+f"(d[62]),"+f"(d[63]),"+f"(d[64]),"+f"(d[65]),"+f"(d[66]),"+f"(d[67]),"+f"(d[68]),"+f"(d[69]),"+f"(d[70]),"+f"(d[71]),"+f"(d[72]),"+f"(d[73]),"+f"(d[74]),"+f"(d[75]),"+f"(d[76]),"+f"(d[77]),"+f"(d[78]),"+f"(d[79])
    : "r"(a.base), "r"(a.off), "r"(a.hi), "r"(b.base), "r"(b.off), "r"(b.hi), "r"(sc), "n"(TA), "n"(TB));
}
template <int TA, int TB> __device__ __forceinline__ void wgmma_ss_n192(float (&d)[96], Desc a, Desc b, int sc) {
  asm volatile("{.reg .pred p; .reg .b32 t, u; .reg .b64 da, db; setp.ne.b32 p, %102, 0; add.u32 t, %96, %97; mov.b64 da, {t, %98}; add.u32 u, %99, %100; mov.b64 db, {u, %101};"
    "wgmma.mma_async.sync.aligned.m64n192k16.f32.bf16.bf16 {%0,%1,%2,%3,%4,%5,%6,%7,%8,%9,%10,%11,%12,%13,%14,%15,%16,%17,%18,%19,%20,%21,%22,%23,%24,%25,%26,%27,%28,%29,%30,%31,%32,%33,%34,%35,%36,%37,%38,%39,%40,%41,%42,%43,%44,%45,%46,%47,%48,%49,%50,%51,%52,%53,%54,%55,%56,%57,%58,%59,%60,%61,%62,%63,%64,%65,%66,%67,%68,%69,%70,%71,%72,%73,%74,%75,%76,%77,%78,%79,%80,%81,%82,%83,%84,%85,%86,%87,%88,%89,%90,%91,%92,%93,%94,%95}, da, db, p, 1, 1, %103, %104;}"
    : "+f"(d[0]),"+f"(d[1]),"+f"(d[2]),"+f"(d[3]),"+f"(d[4]),"+f"(d[5]),"+f"(d[6]),"+f"(d[7]),"+f"(d[8]),"+f"(d[9]),"+f"(d[10]),"+f"(d[11]),"+f"(d[12]),"+f"(d[13]),"+f"(d[14]),"+f"(d[15]),"+f"(d[16]),"+f"(d[17]),"+f"(d[18]),"+f"(d[19]),"+f"(d[20]),"+f"(d[21]),"+f"(d[22]),"+f"(d[23]),"+f"(d[24]),"+f"(d[25]),"+f"(d[26]),"+f"(d[27]),"+f"(d[28]),"+f"(d[29]),"+f"(d[30]),"+f"(d[31]),"+f"(d[32]),"+f"(d[33]),"+f"(d[34]),"+f"(d[35]),"+f"(d[36]),"+f"(d[37]),"+f"(d[38]),"+f"(d[39]),"+f"(d[40]),"+f"(d[41]),"+f"(d[42]),"+f"(d[43]),"+f"(d[44]),"+f"(d[45]),"+f"(d[46]),"+f"(d[47]),"+f"(d[48]),"+f"(d[49]),"+f"(d[50]),"+f"(d[51]),"+f"(d[52]),"+f"(d[53]),"+f"(d[54]),"+f"(d[55]),"+f"(d[56]),"+f"(d[57]),"+f"(d[58]),"+f"(d[59]),"+f"(d[60]),"+f"(d[61]),"+f"(d[62]),"+f"(d[63]),"+f"(d[64]),"+f"(d[65]),"+f"(d[66]),"+f"(d[67]),"+f"(d[68]),"+f"(d[69]),"+f"(d[70]),"+f"(d[71]),"+f"(d[72]),"+f"(d[73]),"+f"(d[74]),"+f"(d[75]),"+f"(d[76]),"+f"(d[77]),"+f"(d[78]),"+f"(d[79]),"+f"(d[80]),"+f"(d[81]),"+f"(d[82]),"+f"(d[83]),"+f"(d[84]),"+f"(d[85]),"+f"(d[86]),"+f"(d[87]),"+f"(d[88]),"+f"(d[89]),"+f"(d[90]),"+f"(d[91]),"+f"(d[92]),"+f"(d[93]),"+f"(d[94]),"+f"(d[95])
    : "r"(a.base), "r"(a.off), "r"(a.hi), "r"(b.base), "r"(b.off), "r"(b.hi), "r"(sc), "n"(TA), "n"(TB));
}
template <int TB> __device__ __forceinline__ void wgmma_rs_n80(float (&d)[40], uint32_t a0, uint32_t a1, uint32_t a2, uint32_t a3, Desc b, int sc) {
  asm volatile("{.reg .pred p; .reg .b32 u; .reg .b64 db; setp.ne.b32 p, %47, 0; add.u32 u, %44, %45; mov.b64 db, {u, %46};"
    "wgmma.mma_async.sync.aligned.m64n80k16.f32.bf16.bf16 {%0,%1,%2,%3,%4,%5,%6,%7,%8,%9,%10,%11,%12,%13,%14,%15,%16,%17,%18,%19,%20,%21,%22,%23,%24,%25,%26,%27,%28,%29,%30,%31,%32,%33,%34,%35,%36,%37,%38,%39}, {%40,%41,%42,%43}, db, p, 1, 1, %48;}"
    : "+f"(d[0]),"+f"(d[1]),"+f"(d[2]),"+f"(d[3]),"+f"(d[4]),"+f"(d[5]),"+f"(d[6]),"+f"(d[7]),"+f"(d[8]),"+f"(d[9]),"+f"(d[10]),"+f"(d[11]),"+f"(d[12]),"+f"(d[13]),"+f"(d[14]),"+f"(d[15]),"+f"(d[16]),"+f"(d[17]),"+f"(d[18]),"+f"(d[19]),"+f"(d[20]),"+f"(d[21]),"+f"(d[22]),"+f"(d[23]),"+f"(d[24]),"+f"(d[25]),"+f"(d[26]),"+f"(d[27]),"+f"(d[28]),"+f"(d[29]),"+f"(d[30]),"+f"(d[31]),"+f"(d[32]),"+f"(d[33]),"+f"(d[34]),"+f"(d[35]),"+f"(d[36]),"+f"(d[37]),"+f"(d[38]),"+f"(d[39])
    : "r"(a0), "r"(a1), "r"(a2), "r"(a3), "r"(b.base), "r"(b.off), "r"(b.hi), "r"(sc), "n"(TB));
}
template <int TB> __device__ __forceinline__ void wgmma_rs_n96(float (&d)[48], uint32_t a0, uint32_t a1, uint32_t a2, uint32_t a3, Desc b, int sc) {
  asm volatile("{.reg .pred p; .reg .b32 u; .reg .b64 db; setp.ne.b32 p, %55, 0; add.u32 u, %52, %53; mov.b64 db, {u, %54};"
    "wgmma.mma_async.sync.aligned.m64n96k16.f32.bf16.bf16 {%0,%1,%2,%3,%4,%5,%6,%7,%8,%9,%10,%11,%12,%13,%14,%15,%16,%17,%18,%19,%20,%21,%22,%23,%24,%25,%26,%27,%28,%29,%30,%31,%32,%33,%34,%35,%36,%37,%38,%39,%40,%41,%42,%43,%44,%45,%46,%47}, {%48,%49,%50,%51}, db, p, 1, 1, %56;}"
    : "+f"(d[0]),"+f"(d[1]),"+f"(d[2]),"+f"(d[3]),"+f"(d[4]),"+f"(d[5]),"+f"(d[6]),"+f"(d[7]),"+f"(d[8]),"+f"(d[9]),"+f"(d[10]),"+f"(d[11]),"+f"(d[12]),"+f"(d[13]),"+f"(d[14]),"+f"(d[15]),"+f"(d[16]),"+f"(d[17]),"+f"(d[18]),"+f"(d[19]),"+f"(d[20]),"+f"(d[21]),"+f"(d[22]),"+f"(d[23]),"+f"(d[24]),"+f"(d[25]),"+f"(d[26]),"+f"(d[27]),"+f"(d[28]),"+f"(d[29]),"+f"(d[30]),"+f"(d[31]),"+f"(d[32]),"+f"(d[33]),"+f"(d[34]),"+f"(d[35]),"+f"(d[36]),"+f"(d[37]),"+f"(d[38]),"+f"(d[39]),"+f"(d[40]),"+f"(d[41]),"+f"(d[42]),"+f"(d[43]),"+f"(d[44]),"+f"(d[45]),"+f"(d[46]),"+f"(d[47])
    : "r"(a0), "r"(a1), "r"(a2), "r"(a3), "r"(b.base), "r"(b.off), "r"(b.hi), "r"(sc), "n"(TB));
}
template <int TB> __device__ __forceinline__ void wgmma_rs_n160(float (&d)[80], uint32_t a0, uint32_t a1, uint32_t a2, uint32_t a3, Desc b, int sc) {
  asm volatile("{.reg .pred p; .reg .b32 u; .reg .b64 db; setp.ne.b32 p, %87, 0; add.u32 u, %84, %85; mov.b64 db, {u, %86};"
    "wgmma.mma_async.sync.aligned.m64n160k16.f32.bf16.bf16 {%0,%1,%2,%3,%4,%5,%6,%7,%8,%9,%10,%11,%12,%13,%14,%15,%16,%17,%18,%19,%20,%21,%22,%23,%24,%25,%26,%27,%28,%29,%30,%31,%32,%33,%34,%35,%36,%37,%38,%39,%40,%41,%42,%43,%44,%45,%46,%47,%48,%49,%50,%51,%52,%53,%54,%55,%56,%57,%58,%59,%60,%61,%62,%63,%64,%65,%66,%67,%68,%69,%70,%71,%72,%73,%74,%75,%76,%77,%78,%79}, {%80,%81,%82,%83}, db, p, 1, 1, %88;}"
    : "+f"(d[0]),"+f"(d[1]),"+f"(d[2]),"+f"(d[3]),"+f"(d[4]),"+f"(d[5]),"+f"(d[6]),"+f"(d[7]),"+f"(d[8]),"+f"(d[9]),"+f"(d[10]),"+f"(d[11]),"+f"(d[12]),"+f"(d[13]),"+f"(d[14]),"+f"(d[15]),"+f"(d[16]),"+f"(d[17]),"+f"(d[18]),"+f"(d[19]),"+f"(d[20]),"+f"(d[21]),"+f"(d[22]),"+f"(d[23]),"+f"(d[24]),"+f"(d[25]),"+f"(d[26]),"+f"(d[27]),"+f"(d[28]),"+f"(d[29]),"+f"(d[30]),"+f"(d[31]),"+f"(d[32]),"+f"(d[33]),"+f"(d[34]),"+f"(d[35]),"+f"(d[36]),"+f"(d[37]),"+f"(d[38]),"+f"(d[39]),"+f"(d[40]),"+f"(d[41]),"+f"(d[42]),"+f"(d[43]),"+f"(d[44]),"+f"(d[45]),"+f"(d[46]),"+f"(d[47]),"+f"(d[48]),"+f"(d[49]),"+f"(d[50]),"+f"(d[51]),"+f"(d[52]),"+f"(d[53]),"+f"(d[54]),"+f"(d[55]),"+f"(d[56]),"+f"(d[57]),"+f"(d[58]),"+f"(d[59]),"+f"(d[60]),"+f"(d[61]),"+f"(d[62]),"+f"(d[63]),"+f"(d[64]),"+f"(d[65]),"+f"(d[66]),"+f"(d[67]),"+f"(d[68]),"+f"(d[69]),"+f"(d[70]),"+f"(d[71]),"+f"(d[72]),"+f"(d[73]),"+f"(d[74]),"+f"(d[75]),"+f"(d[76]),"+f"(d[77]),"+f"(d[78]),"+f"(d[79])
    : "r"(a0), "r"(a1), "r"(a2), "r"(a3), "r"(b.base), "r"(b.off), "r"(b.hi), "r"(sc), "n"(TB));
}
template <int TB> __device__ __forceinline__ void wgmma_rs_n192(float (&d)[96], uint32_t a0, uint32_t a1, uint32_t a2, uint32_t a3, Desc b, int sc) {
  asm volatile("{.reg .pred p; .reg .b32 u; .reg .b64 db; setp.ne.b32 p, %103, 0; add.u32 u, %100, %101; mov.b64 db, {u, %102};"
    "wgmma.mma_async.sync.aligned.m64n192k16.f32.bf16.bf16 {%0,%1,%2,%3,%4,%5,%6,%7,%8,%9,%10,%11,%12,%13,%14,%15,%16,%17,%18,%19,%20,%21,%22,%23,%24,%25,%26,%27,%28,%29,%30,%31,%32,%33,%34,%35,%36,%37,%38,%39,%40,%41,%42,%43,%44,%45,%46,%47,%48,%49,%50,%51,%52,%53,%54,%55,%56,%57,%58,%59,%60,%61,%62,%63,%64,%65,%66,%67,%68,%69,%70,%71,%72,%73,%74,%75,%76,%77,%78,%79,%80,%81,%82,%83,%84,%85,%86,%87,%88,%89,%90,%91,%92,%93,%94,%95}, {%96,%97,%98,%99}, db, p, 1, 1, %104;}"
    : "+f"(d[0]),"+f"(d[1]),"+f"(d[2]),"+f"(d[3]),"+f"(d[4]),"+f"(d[5]),"+f"(d[6]),"+f"(d[7]),"+f"(d[8]),"+f"(d[9]),"+f"(d[10]),"+f"(d[11]),"+f"(d[12]),"+f"(d[13]),"+f"(d[14]),"+f"(d[15]),"+f"(d[16]),"+f"(d[17]),"+f"(d[18]),"+f"(d[19]),"+f"(d[20]),"+f"(d[21]),"+f"(d[22]),"+f"(d[23]),"+f"(d[24]),"+f"(d[25]),"+f"(d[26]),"+f"(d[27]),"+f"(d[28]),"+f"(d[29]),"+f"(d[30]),"+f"(d[31]),"+f"(d[32]),"+f"(d[33]),"+f"(d[34]),"+f"(d[35]),"+f"(d[36]),"+f"(d[37]),"+f"(d[38]),"+f"(d[39]),"+f"(d[40]),"+f"(d[41]),"+f"(d[42]),"+f"(d[43]),"+f"(d[44]),"+f"(d[45]),"+f"(d[46]),"+f"(d[47]),"+f"(d[48]),"+f"(d[49]),"+f"(d[50]),"+f"(d[51]),"+f"(d[52]),"+f"(d[53]),"+f"(d[54]),"+f"(d[55]),"+f"(d[56]),"+f"(d[57]),"+f"(d[58]),"+f"(d[59]),"+f"(d[60]),"+f"(d[61]),"+f"(d[62]),"+f"(d[63]),"+f"(d[64]),"+f"(d[65]),"+f"(d[66]),"+f"(d[67]),"+f"(d[68]),"+f"(d[69]),"+f"(d[70]),"+f"(d[71]),"+f"(d[72]),"+f"(d[73]),"+f"(d[74]),"+f"(d[75]),"+f"(d[76]),"+f"(d[77]),"+f"(d[78]),"+f"(d[79]),"+f"(d[80]),"+f"(d[81]),"+f"(d[82]),"+f"(d[83]),"+f"(d[84]),"+f"(d[85]),"+f"(d[86]),"+f"(d[87]),"+f"(d[88]),"+f"(d[89]),"+f"(d[90]),"+f"(d[91]),"+f"(d[92]),"+f"(d[93]),"+f"(d[94]),"+f"(d[95])
    : "r"(a0), "r"(a1), "r"(a2), "r"(a3), "r"(b.base), "r"(b.off), "r"(b.hi), "r"(sc), "n"(TB));
}
template <int N, int TA, int TB> __device__ __forceinline__ void wgmma_ss(float (&d)[N / 2], Desc a, Desc b, int sc) {
  if constexpr (N == 48) wgmma_ss_n48<TA, TB>(d, a, b, sc);
  else if constexpr (N == 80) wgmma_ss_n80<TA, TB>(d, a, b, sc);
  else if constexpr (N == 160) wgmma_ss_n160<TA, TB>(d, a, b, sc);
  else if constexpr (N == 192) wgmma_ss_n192<TA, TB>(d, a, b, sc);
}
template <int N, int TB> __device__ __forceinline__ void wgmma_rs(float (&d)[N / 2], uint32_t a0, uint32_t a1, uint32_t a2, uint32_t a3, Desc b, int sc) {
  if constexpr (N == 80) wgmma_rs_n80<TB>(d, a0, a1, a2, a3, b, sc);
  else if constexpr (N == 96) wgmma_rs_n96<TB>(d, a0, a1, a2, a3, b, sc);
  else if constexpr (N == 160) wgmma_rs_n160<TB>(d, a0, a1, a2, a3, b, sc);
  else if constexpr (N == 192) wgmma_rs_n192<TB>(d, a0, a1, a2, a3, b, sc);
}

constexpr uint32_t SMEM_BASE = 1024;
constexpr uint32_t PAGE = 10240;
constexpr uint32_t OFF_RING = 16 * PAGE;
constexpr uint32_t OFF_KVB = 50176;
constexpr uint32_t OFF_KVP = 43008;
constexpr uint32_t OFF_R1 = 35840;
constexpr uint32_t OFF_MISC = 22 * PAGE;
constexpr uint32_t OFF_W2 = OFF_MISC - 6 * 24576;
constexpr uint32_t OFF_BAR = OFF_MISC;
constexpr uint32_t OFF_LN1 = OFF_MISC + 1920;
constexpr uint32_t OFF_RK1 = OFF_MISC + 2944;
constexpr uint32_t OFF_B2 = OFF_MISC + 1600;
constexpr uint32_t OFF_SCR = OFF_MISC + 6784;
constexpr uint32_t SMEM_BYTES = OFF_MISC + 7040;

enum : int {
  RF = 0, FX = 5, FE = 18, RX = 22, RXK = 24,
  RE = 25, PX = 30, PF = 31, SIDE = 32, ZK = 33, RKV = 34, ST1 = 35, XF = 36, KD = 37, CG = 38,
  FWO = 40, FW1 = 48, FW2 = 56,
  AO = 70, AH = 86, AF = 102,
  DW = 126, DF = 142, DG = 158,
  SO = 182, SH = 183,
  SIDE2 = 185, KVB = 186, END = 187, OM = 188
};

__device__ uint32_t g_epoch;
__device__ uint4 g_ln1[2048];
__device__ uint4 g_cs[4 * 1728];
__device__ uint4 g_hstat[32 * 8 * 64];
__device__ __align__(128) float2 g_kv1[8 * 16 * 880];
__device__ __align__(128) uint2 g_kv2[8 * 960];
__device__ __align__(128) uint32_t g_flag[3 * 32 * 32];
__device__ __align__(128) uint32_t g_hint[2 * 8 * 32];
__device__ __align__(128) uint8_t g_act[3 * 32 * 8 * 24576];

struct Maps { CUtensorMap m[11]; };
enum : int { M_X, M_KVF, M_KVH, M_Q2, M_QR, M_WO2, M_WOR, M_W1, M_W1R, M_W2F, M_W2H };

#define TL(id)
#define TLW(id)
#define TL0(id)
#define TL1(id)
#define TC(v)
#define TS(id, v)

constexpr int SPIN_LIMIT = 1 << 19;

__device__ __forceinline__ bool elect_one() {
  uint32_t p;
  asm volatile("{.reg .pred P; elect.sync _|P, 0xffffffff; selp.u32 %0,1,0,P;}" : "=r"(p));
  return p;
}
__device__ __forceinline__ void mbar_wait(uint32_t bar, uint32_t parity = 0) {
  asm volatile("{.reg .pred p;\nW: mbarrier.try_wait.parity.shared::cta.b64 p, [%0], %1;\n@!p bra W;}" ::"r"(bar), "r"(parity) : "memory");
}
__device__ __forceinline__ void mbar_wait_cluster(uint32_t bar) {
  asm volatile("{.reg .pred p;\nW: mbarrier.try_wait.parity.acquire.cluster.shared::cta.b64 p, [%0], 0;\n@!p bra W;}" ::"r"(bar) : "memory");
}
__device__ __forceinline__ void mbar_wait_wd(uint32_t bar) {
  asm volatile("{.reg .pred p; .reg .u32 n; mov.u32 n, 0;\n"
               "W: mbarrier.try_wait.parity.shared::cta.b64 p, [%0], 0;\n"
               "@p bra D; add.u32 n, n, 1; setp.gt.u32 p, n, %1; @p trap; bra W;\n"
               "D: }" ::"r"(bar), "n"(SPIN_LIMIT) : "memory");
}
__device__ __forceinline__ void mbar_arrive(uint32_t bar, uint32_t n) {
  asm volatile("mbarrier.arrive.shared::cta.b64 _, [%0], %1;" ::"r"(bar), "r"(n) : "memory");
}
__device__ __forceinline__ void mbar_arrive_if0(int z, uint32_t bar, uint32_t n) {
  asm volatile("{.reg .pred p; setp.eq.s32 p, %2, 0; @p mbarrier.arrive.shared::cta.b64 _, [%0], %1;}" ::"r"(bar), "r"(n), "r"(z) : "memory");
}
__device__ __forceinline__ void mbar_arrive_remote_if0(int z, uint32_t bar) {
  asm volatile("{.reg .pred p; setp.eq.s32 p, %1, 0; @p mbarrier.arrive.shared::cluster.b64 _, [%0];}" ::"r"(bar), "r"(z) : "memory");
}
__device__ __forceinline__ void mbar_expect(uint32_t bar, uint32_t bytes) {
  asm volatile("mbarrier.arrive.expect_tx.shared::cta.b64 _, [%0], %1;" ::"r"(bar), "r"(bytes) : "memory");
}
__device__ __forceinline__ void tma2d(uint32_t dst, const CUtensorMap* tm, uint32_t bar, int c0, int c1) {
  asm volatile("cp.async.bulk.tensor.2d.shared::cluster.global.mbarrier::complete_tx::bytes [%0],[%1,{%3,%4}],[%2];"
               ::"r"(dst), "l"(tm), "r"(bar), "r"(c0), "r"(c1) : "memory");
}
__device__ __forceinline__ void tma3d(uint32_t dst, const CUtensorMap* tm, uint32_t bar, int c0, int c1, int c2) {
  asm volatile("cp.async.bulk.tensor.3d.shared::cluster.global.mbarrier::complete_tx::bytes [%0],[%1,{%3,%4,%5}],[%2];"
               ::"r"(dst), "l"(tm), "r"(bar), "r"(c0), "r"(c1), "r"(c2) : "memory");
}
__device__ __forceinline__ void bulk_load(uint32_t dst, const void* src, uint32_t bytes, uint32_t bar) {
  asm volatile("cp.async.bulk.shared::cluster.global.mbarrier::complete_tx::bytes [%0],[%1],%2,[%3];"
               ::"r"(dst), "l"(src), "r"(bytes), "r"(bar) : "memory");
}
__device__ __forceinline__ void bulk_store(void* dst, uint32_t src, uint32_t bytes) {
  asm volatile("cp.async.bulk.global.shared::cta.bulk_group [%0],[%1],%2;" ::"l"(dst), "r"(src), "r"(bytes) : "memory");
}
__device__ __forceinline__ void bulk_commit_wait() {
  asm volatile("cp.async.bulk.commit_group;" ::: "memory");
  asm volatile("cp.async.bulk.wait_group 0;" ::: "memory");
}
__device__ __forceinline__ void l2_prefetch(const void* src, uint32_t bytes) {
  asm volatile("cp.async.bulk.prefetch.L2.global [%0], %1;" ::"l"(src), "r"(bytes) : "memory");
}
__device__ __forceinline__ void fence_gpu() { asm volatile("fence.acq_rel.gpu;" ::: "memory"); }
__device__ __forceinline__ void fence_async_smem() { asm volatile("fence.proxy.async.shared::cta;" ::: "memory"); }
__device__ __forceinline__ void fence_async_global() { asm volatile("fence.proxy.async.global;" ::: "memory"); }
__device__ __forceinline__ void st_flag(uint32_t* p, uint32_t v) {
  asm volatile("st.relaxed.gpu.global.u32 [%0], %1;" ::"l"(p), "r"(v) : "memory");
}
__device__ __forceinline__ uint32_t ld_acq(const uint32_t* p) {
  uint32_t v;
  asm volatile("ld.acquire.gpu.global.u32 %0, [%1];" : "=r"(v) : "l"(p) : "memory");
  return v;
}
__device__ __forceinline__ void wg_fence() { asm volatile("wgmma.fence.sync.aligned;" ::: "memory"); }
__device__ __forceinline__ void wg_commit() { asm volatile("wgmma.commit_group.sync.aligned;" ::: "memory"); }
template <int N> __device__ __forceinline__ void wg_wait() { asm volatile("wgmma.wait_group.sync.aligned %0;" ::"n"(N) : "memory"); }
template <int N> __device__ __forceinline__ void reg_fence(float (&a)[N]) {
#pragma unroll
  for (int i = 0; i < N; i++) asm volatile("" : "+f"(a[i])::"memory");
}
template <int ID, int N> __device__ __forceinline__ void named_bar() { asm volatile("bar.sync %0, %1;" ::"n"(ID), "n"(N) : "memory"); }
template <int N> __device__ __forceinline__ void reg_fence(uint32_t (&a)[N]) {
#pragma unroll
  for (int i = 0; i < N; i++) asm volatile("" : "+r"(a[i])::"memory");
}
__device__ __forceinline__ Desc mkdesc(uint32_t dyn, uint32_t off, uint32_t lbo, uint32_t sbo, uint32_t swz) {
  return Desc{dyn, ((off + SMEM_BASE) >> 4) + ((lbo >> 4) << 16), (sbo >> 4) | (swz << 30)};
}
__device__ __forceinline__ uint32_t pack2(float lo, float hi) {
  uint32_t r;
  asm("cvt.rn.bf16x2.f32 %0, %1, %2;" : "=r"(r) : "f"(hi), "f"(lo));
  return r;
}
__device__ __forceinline__ float bf_lo(uint32_t v) { return __uint_as_float(v << 16); }
__device__ __forceinline__ float bf_hi(uint32_t v) { return __uint_as_float(v & 0xffff0000u); }
__device__ __forceinline__ void stsm4(uint32_t addr, uint32_t a, uint32_t b, uint32_t c, uint32_t d) {
  asm volatile("stmatrix.sync.aligned.m8n8.x4.shared.b16 [%0], {%1,%2,%3,%4};" ::"r"(addr), "r"(a), "r"(b), "r"(c), "r"(d) : "memory");
}
__device__ __forceinline__ void ldsm4(uint32_t addr, uint32_t* r) {
  asm volatile("ldmatrix.sync.aligned.m8n8.x4.shared.b16 {%0,%1,%2,%3}, [%4];" : "=r"(r[0]), "=r"(r[1]), "=r"(r[2]), "=r"(r[3]) : "r"(addr) : "memory");
}
__device__ __forceinline__ float2 lds64(uint32_t a) {
  float2 v;
  asm volatile("ld.shared.v2.f32 {%0,%1}, [%2];" : "=f"(v.x), "=f"(v.y) : "r"(a) : "memory");
  return v;
}
__device__ __forceinline__ float4 lds128(uint32_t a) {
  float4 v;
  asm volatile("ld.shared.v4.f32 {%0,%1,%2,%3}, [%4];" : "=f"(v.x), "=f"(v.y), "=f"(v.z), "=f"(v.w) : "r"(a) : "memory");
  return v;
}
__device__ __forceinline__ void sts64(uint32_t a, uint32_t x, uint32_t y) {
  asm volatile("st.shared.v2.u32 [%0], {%1,%2};" ::"r"(a), "r"(x), "r"(y) : "memory");
}
__device__ __forceinline__ void sts128(uint32_t a, uint32_t x, uint32_t y, uint32_t z, uint32_t w) {
  asm volatile("st.shared.v4.u32 [%0], {%1,%2,%3,%4};" ::"r"(a), "r"(x), "r"(y), "r"(z), "r"(w) : "memory");
}
__device__ __forceinline__ float ex2(float x) {
  float r;
  asm("ex2.approx.ftz.f32 %0, %1;" : "=f"(r) : "f"(x));
  return r;
}
__device__ __forceinline__ float rcp(float x) {
  float r;
  asm("rcp.approx.ftz.f32 %0, %1;" : "=f"(r) : "f"(x));
  return r;
}
constexpr float LOG2E = 1.4426950408889634f;
__device__ __forceinline__ float phi(float z, float a, float a2) {
  float r = ex2(z * a2) + 1e-6f;
  asm("{.reg .pred p; setp.gt.f32 p, %1, 0f00000000; @p fma.rn.f32 %0, %1, %2, 0f3F800008;}" : "+f"(r) : "f"(z), "f"(a));
  return r;
}
__device__ __forceinline__ float gelu(float z, const float3& k) {
  float th;
  asm("tanh.approx.f32 %0, %1;" : "=f"(th) : "f"(z * fmaf(z * z, k.y, k.x)));
  const float hy = z * k.z;
  return fmaf(hy, th, hy);
}
__device__ __forceinline__ uint32_t rk1_frag(float m, float d, int c) {
  const uint32_t hi = pack2(m, d), lo = pack2(m - bf_lo(hi), d - bf_hi(hi));
  return c == 0 ? __byte_perm(hi, 0, 0x1010) : c == 1 ? __byte_perm(lo, hi, 0x7610) : c == 2 ? lo >> 16 : 0u;
}
__device__ __forceinline__ void rk1_store(uint32_t addr, float2 cs, uint32_t bb) {
  const uint32_t hi = pack2(cs.x, cs.y), lo = pack2(cs.x - bf_lo(hi), cs.y - bf_hi(hi));
  sts128(addr, __byte_perm(hi, lo, 0x5410), __byte_perm(hi, bb, 0x5410), bb & 0xffffu, 0);
  sts128(addr + 16, __byte_perm(hi, lo, 0x7632), __byte_perm(hi, bb, 0x7632), bb >> 16, 0);
}
constexpr uint32_t ONES = 0x3F803F80u;
__device__ __forceinline__ void ll_store(uint4* p, float a, float b, uint32_t tag) {
  asm volatile("st.relaxed.gpu.global.v4.u32 [%0], {%1,%2,%3,%2};" ::"l"(p), "r"(__float_as_uint(a)), "r"(tag), "r"(__float_as_uint(b)) : "memory");
}
__device__ __forceinline__ uint4 ll_load(const void* p) {
  uint4 v;
  asm volatile("ld.relaxed.gpu.global.v4.u32 {%0,%1,%2,%3}, [%4];" : "=r"(v.x), "=r"(v.y), "=r"(v.z), "=r"(v.w) : "l"(p) : "memory");
  return v;
}
template <int N>
__device__ __forceinline__ void ll_wait(uint4 (&v)[N], const uint4* p, int stride, uint32_t tag) {
  uint32_t bad;
  int it = 0;
  do {
    bad = 0;
#pragma unroll
    for (int m = 0; m < N; m++) v[m] = ll_load(p + m * stride);
#pragma unroll
    for (int m = 0; m < N; m++) bad |= (v[m].y ^ tag) | (v[m].w ^ tag);
  } while (__any_sync(0xffffffffu, bad) && ++it < SPIN_LIMIT);
}
__device__ __forceinline__ void ll_wait2(uint4 (&v)[8], const uint4* p, uint32_t tag) {
  uint32_t bad;
  int it = 0;
  do {
    bad = 0;
#pragma unroll
    for (int m = 0; m < 8; m++) v[m] = ll_load(p + (m >> 1) * 1728 + (m & 1));
#pragma unroll
    for (int m = 0; m < 8; m++) bad |= (v[m].y ^ tag) | (v[m].w ^ tag);
  } while (__any_sync(0xffffffffu, bad) && ++it < SPIN_LIMIT);
}
__device__ __forceinline__ float2 ll_sum4(const uint4* p, uint32_t tag) {
  uint4 v[4];
  ll_wait(v, p, 1728, tag);
  return make_float2((__uint_as_float(v[0].x) + __uint_as_float(v[1].x)) + (__uint_as_float(v[2].x) + __uint_as_float(v[3].x)),
                     (__uint_as_float(v[0].z) + __uint_as_float(v[1].z)) + (__uint_as_float(v[2].z) + __uint_as_float(v[3].z)));
}
__device__ __forceinline__ void poll_hint(const uint32_t* f, uint32_t want, uint32_t epoch) {
  int it = 0;
  uint32_t v;
  do {
    asm volatile("ld.relaxed.gpu.global.u32 %0, [%1];" : "=r"(v) : "l"(f) : "memory");
  } while ((__ballot_sync(0xffffffffu, v == epoch) & want) != want && ++it < SPIN_LIMIT);
}
__device__ __noinline__ float2 colsum(const __nv_bfloat16* wm, int ld, int h0, int h1) {
  const int lane = threadIdx.x & 31, r4 = lane >> 3;
  float d[8];
#pragma unroll
  for (int e = 0; e < 8; e++) d[e] = 0.f;
#pragma unroll 1
  for (int h = h0; h < h1; h++) {
    const __nv_bfloat16* wp = wm + (4 * h + r4) * ld + 8 * (lane & 7);
    uint4 v[14];
#pragma unroll
    for (int m = 0; m < 14; m++) {
      v[m] = make_uint4(0, 0, 0, 0);
      if (m < 13 || h == 0)
        asm volatile("ld.global.nc.v4.u32 {%0,%1,%2,%3}, [%4];" : "=r"(v[m].x), "=r"(v[m].y), "=r"(v[m].z), "=r"(v[m].w) : "l"(wp));
      wp += 12 * ld;
    }
#pragma unroll
    for (int m = 0; m < 14; m++) {
      d[0] += bf_lo(v[m].x); d[1] += bf_hi(v[m].x); d[2] += bf_lo(v[m].y); d[3] += bf_hi(v[m].y);
      d[4] += bf_lo(v[m].z); d[5] += bf_hi(v[m].z); d[6] += bf_lo(v[m].w); d[7] += bf_hi(v[m].w);
    }
  }
#pragma unroll 1
  for (int o = 8; o < 32; o <<= 1) {
#pragma unroll
    for (int e = 0; e < 8; e++) d[e] += __shfl_xor_sync(0xffffffffu, d[e], o);
  }
  if (r4 & 2) { d[0] = d[4]; d[1] = d[5]; d[2] = d[6]; d[3] = d[7]; }
  return r4 & 1 ? make_float2(d[2], d[3]) : make_float2(d[0], d[1]);
}
template <bool PHI>
__device__ __forceinline__ void ln_pair(const float* z, const float (&a)[2], const float (&a2)[2], uint32_t* o) {
#pragma unroll
  for (int e = 0; e < 4; e++) {
    const int hh = e & 1;
    o[e] = PHI ? pack2(phi(z[2 * e], a[hh], a2[hh]), phi(z[2 * e + 1], a[hh], a2[hh])) : pack2(z[2 * e] * a[hh], z[2 * e + 1] * a[hh]);
  }
}

__global__ void __cluster_dims__(2, 1, 1) __launch_bounds__(384, 1)
fused_block_kernel(const __grid_constant__ Maps maps, const __nv_bfloat16* __restrict__ x, const __nv_bfloat16* __restrict__ wqkv,
                   const __nv_bfloat16* __restrict__ wo, const __nv_bfloat16* __restrict__ w1,
                   const __nv_bfloat16* __restrict__ b1, const __nv_bfloat16* __restrict__ w2,
                   const __nv_bfloat16* __restrict__ b2, __nv_bfloat16* __restrict__ out) {
  extern __shared__ __align__(1024) uint8_t smem_raw[];
  const uint32_t sb = (uint32_t)__cvta_generic_to_shared(smem_raw);
  const uint32_t bars = sb + OFF_BAR;
  const int warp = __shfl_sync(0xffffffffu, threadIdx.x >> 5, 0);
  const int lane = threadIdx.x & 31;
  if (warp < 3 && elect_one()) asm volatile("prefetch.tensormap [%0];" ::"l"(&maps.m[warp]) : "memory");

  const int cl = blockIdx.x >> 1, q = blockIdx.x & 1;
  const int u7 = ((cl - 36) * 37) >> 8;
  const int oct = cl < 4 ? 0 : cl < 36 ? 1 + 2 * ((cl - 4) & 7) : 2 + 2 * (cl - 36 - 7 * u7);
  const int u4 = cl < 4 ? cl : cl < 36 ? (cl - 4) >> 3 : u7;
  const int i = 2 * (oct & 7) + (u4 >> 1), p = 2 * (oct >> 3) + (u4 & 1);
  const int j = 2 * p + q;
  auto col_f = [](int jj) { return 160 * (jj >> 1) + 16 * (jj & 2) + 64 * (jj & 1); };
  auto col_r = [](int jj) { return 160 * (jj >> 1) + 128 - 64 * (jj & 2) + 16 * (jj & 1); };
  const int cF = col_f(j), cR = col_r(j), role = q ^ (p & 1);

  auto load_kv = [&](int s) {
    const uint32_t dst = sb + (s < 16 ? OFF_RING + (s % 5) * 12288 : (s - 16) * 12288), bar = bars + 8 * (s < 16 ? RF + s % 5 : FE + s - 16);
    tma3d(dst, &maps.m[M_KVF], bar, cF, 32 * s, 1);
    tma2d(dst + 8192, &maps.m[M_KVH], bar, 640 + 640 * role + cR - 16 * q, 32 * s);
    mbar_expect(bar, 10240);
  };
  auto load_x = [&](int c, int b, int slot) {
    tma2d(sb + slot * 16384, &maps.m[M_X], bars + 8 * (FX + b), 64 * c, 128 * i);
    mbar_expect(bars + 8 * (FX + b), 16384);
  };
  auto bar_init = [&](int n, uint32_t cnt) { asm volatile("mbarrier.init.shared::cta.b64 [%0], %1;" ::"r"(bars + 8 * n), "r"(cnt) : "memory"); };

  TC(tc0);
  if (elect_one()) {
    if (warp == 8) {
#pragma unroll
      for (int n = 0; n < 10; n++) bar_init(n, 1);
      load_x(0, 0, 0);
      load_kv(0);
      load_kv(1);
      load_x(1, 1, 1);
      load_kv(2);
      load_kv(3);
      load_x(2, 2, 2);
      load_kv(4);
      load_x(3, 3, 3);
    } else if (warp < 6) {
#pragma unroll
      for (int n = 0; n < 5; n++) bar_init(10 + 5 * warp + n, warp < 3 ? 1 : 8);
      asm volatile("fence.mbarrier_init.release.cluster;" ::: "memory");
    }
  }
  __syncwarp();
  TC(tc1);
  asm volatile("barrier.cluster.arrive.relaxed.aligned;" ::: "memory");

  if (warp >= 8) {
    TC(tc2);
    asm volatile("barrier.cluster.wait.aligned;" ::: "memory");
    TC(tc3);
    asm volatile("setmaxnreg.dec.sync.aligned.u32 88;");
    if (warp == 8) {
      TL(40);
      TS(41, tc0); TS(42, tc1); TS(43, tc2); TS(19, tc3);
      if (elect_one()) {
        auto prefetch_piece = [&](const __nv_bfloat16* wm, uint32_t total, uint32_t off, uint32_t bytes) {
          l2_prefetch(reinterpret_cast<const uint8_t*>(wm) + blockIdx.x * total + off, bytes);
        };
#pragma unroll
        for (int s = 5; s < 16; s++) {
          mbar_wait(bars + 8 * (RE + s % 5), (s / 5 - 1) & 1);
          load_kv(s);
          if (s < 11) load_x(s - 1, s - 1, s - 1);
          if (s == 12) mbar_wait(bars + 8 * XF);
          if (s >= 12) load_kv(s + 4);
          if (s < 13) asm volatile("prefetch.tensormap [%0];" ::"l"(&maps.m[s - 2]) : "memory");
          if (s >= 11) prefetch_piece(wo, 6400, (s - 11) * 1280, 1280);
          TL1(96 + s);
        }
#pragma unroll
        for (int t = 0; t < 10; t++) {
          const int slot = (t + 1) % 5, k0 = 64 * (t < 7 ? t + 3 : t - 7);
          const uint32_t dst = sb + OFF_RING + slot * 12288, bar = bars + 8 * (RF + slot);
          mbar_wait(bars + 8 * (RE + slot), ((t + 11) / 5) & 1);
          tma3d(dst, &maps.m[M_Q2], bar, 0, k0, 5 * p + 3 * q);
          tma2d(dst + 8192, &maps.m[M_QR], bar, 80 * j + 64 - 64 * q, k0);
          mbar_expect(bar, 10240);
          if (t >= 6 && t < 9) load_x(t - 6, t + 4, t - 2);
          if (t < 8) prefetch_piece(w1, 15360, t * 1920, 1920);
          TL1(116 + t);
        }
#pragma unroll 1
        for (int n = 0; n < 32; n += 4) {
          const int t = (0x41765320u >> n) & 7, k0 = 80 * (t == 0 ? j : t - (t <= j));
          const uint32_t dst = sb + 10 * PAGE + (t < 2 ? t ^ 1 : t) * 15360, bar = bars + 8 * (FWO + t);
          mbar_wait(bars + 8 * (RE + ((0x00432221u >> n) & 15)), n >= 24);
          if (n >= 8) mbar_wait(bars + 8 * (FWO + ((0x41765320u >> (n - 8)) & 7)));
          tma3d(dst, &maps.m[M_WO2], bar, 0, k0, cF >> 5);
          tma2d(dst + 10240, &maps.m[M_WOR], bar, cR, k0);
          mbar_expect(bar, 12800);
          TL1(128 + n / 4);
        }
#pragma unroll 1
        for (int t = 0; t < 8; t++) {
          const uint32_t wb = bars + 8 * (t == 0 ? FWO + 1 : t < 5 ? DW + 2 * t - 1 : DF + t - 5);
          const int jj = t == 0 ? j : t - (t <= j);
          const uint32_t dst = sb + (7 + 3 * (t < 5 ? t : t - 5)) * PAGE, bar = bars + 8 * (FW1 + t);
          mbar_wait(wb);
          if (t) {
            mbar_wait(wb + 64);
            mbar_wait(bars + 8 * (t == 1 ? SH : t == 2 ? FW1 + 1 : t == 3 ? AH + 1 : DF + t - 3));
          }
          tma3d(dst, &maps.m[M_W1], bar, 0, col_f(jj), 3 * j);
          tma3d(dst + 24576, &maps.m[M_W1R], bar, 0, col_r(jj), 3 * j);
          mbar_expect(bar, 30720);
          if (t >= 3) prefetch_piece(w2, 15360, (t - 3) * 3072, 3072);
          TL1(136 + t);
        }
#pragma unroll 1
        for (int t = 0; t < 12; t++) {
          const int t6 = t < 6 ? t : t - 6;
          const uint32_t wb = bars + 8 * (t < 6 ? DF + ((0x776544 >> (4 * t)) & 7) : DG + t6);
          const int uu = (0xA95024 >> (2 * t)) & 3, n = (0x924900 >> (2 * t)) & 3;
          const int k0 = 192 * (t < 3 ? j : 2 * (n + (n >= p)) + q) + 64 * uu;
          const uint32_t dst = sb + OFF_W2 + ((0x321045 >> (4 * t6)) & 7) * 24576, bar = bars + 8 * (FW2 + t);
          mbar_wait(wb);
          mbar_wait(wb + (t < 6 ? 64 : 96));
          tma2d(dst, &maps.m[M_W2F], bar, cF, k0);
          tma2d(dst + 8192, &maps.m[M_W2F], bar, cF + 64 - 128 * q, k0);
          tma2d(dst + 16384, &maps.m[M_W2H], bar, cR - 16 * q, k0);
          mbar_expect(bar, 20480);
          TL1(144 + t);
        }
      }
    } else {
      uint32_t epoch;
      asm volatile("ld.relaxed.gpu.global.u32 %0, [%1];" : "=r"(epoch) : "l"(&g_epoch) : "memory");
      epoch += 1;
      const int unit = i * 8 + j, hw = warp - 9, ht = hw * 32 + lane;
      const int part = unit & 3, cg = unit >> 2, cpair = part * 1728 + 32 * cg + 4 * (lane & 7) + (lane >> 3);
      if (elect_one()) {
#pragma unroll 1
        for (int n = FWO + 50 * hw; n < FWO + 50 * hw + 50; n += 10) {
#pragma unroll
          for (int e = 0; e < 10; e++) bar_init(n + e, n < AO ? 1 : 8);
        }
        mbar_expect(bars + 8 * (RX + hw), hw == 2 ? 8192 : 10240);
      }
      __syncwarp();
      if (part >= 2) mbar_wait_wd(bars + 8 * (FX + 2 * part - 4));
      if (cg < 30) {
        float2 d = colsum(wqkv + part * 160 * 1920 + 64 * cg, 1920, hw, hw + 1);
        const uint32_t red = sb + OFF_SCR + lane * 8;
#pragma unroll 1
        for (int h = 0; h < 2; h++) {
          if (hw == h) sts64(red, __float_as_uint(d.x), __float_as_uint(d.y));
          named_bar<2, 96>();
          if (hw == h + 1) {
            const float2 a = lds64(red);
            d.x += a.x;
            d.y += a.y;
          }
        }
        if (hw == 2) ll_store(g_cs + cpair, d.x, d.y, epoch);
      }
      if (hw == 2) {
        TL(8);
#pragma unroll 1
        for (int n = lane; n < 40; n += 32) {
          const uint32_t b = *reinterpret_cast<const uint32_t*>(b2 + (n < 32 ? cF + 2 * n : cR + 2 * n - 64));
          sts64(sb + OFF_B2 + n * 8, b << 16, b & 0xffff0000u);
        }
        __syncwarp();
        mbar_wait_wd(bars + 8 * ST1);
        uint4 v[4];
        ll_wait(v, g_ln1 + 128 * i + lane, 32, epoch);
#pragma unroll
        for (int m = 0; m < 4; m++) {
          const float nm = __uint_as_float(v[m].x) * (-1.f / 640.f);
          const float rstd = rsqrtf(fmaxf(fmaf(-nm, nm, __uint_as_float(v[m].z) * (1.f / 640.f)), 0.f) + 1e-5f);
          sts64(sb + OFF_LN1 + (lane + 32 * m) * 8, __float_as_uint(rstd), __float_as_uint(nm));
        }
      } else {
        const int n = 4 * min(ht, 59);
        int col;
        if (n < 160) col = n + (n < 64 ? 640 + cF : n < 128 ? 1216 + cF : 512 + 640 * role + cR - 16 * q);
        else col = 80 * j + n - 160 + (q ? (n < 224 ? 16 : -64) : 0);
        mbar_wait(bars + 8 * CG);
        uint4 v[8];
        ll_wait2(v, g_cs + (col >> 1), epoch);
#pragma unroll
        for (int e = 0; e < 2; e++)
          rk1_store(sb + OFF_RK1 + n * 16 + 32 * e,
                    make_float2((__uint_as_float(v[e].x) + __uint_as_float(v[2 + e].x)) + (__uint_as_float(v[4 + e].x) + __uint_as_float(v[6 + e].x)),
                                (__uint_as_float(v[e].z) + __uint_as_float(v[2 + e].z)) + (__uint_as_float(v[4 + e].z) + __uint_as_float(v[6 + e].z))), 0);
        fence_async_smem();
      }
      __syncwarp();
      mbar_arrive_if0(lane, bars + 8 * SIDE, hw == 2 ? 2 : 3);
      if (hw != 1) TL(11 - hw / 2);
      {
        if (hw == 2) {
          mbar_wait_wd(bars + 8 * ZK);
#pragma unroll 1
          for (int m = 0; m < 30; m += 3) {
#pragma unroll
            for (int e = 0; e < 3; e++) sts128(sb + OFF_KVB + ((m + e) * 32 + lane) * 16, 0, 0, 0, 0);
          }
        }
        mbar_wait_wd(bars + 8 * RKV);
        if (hw == 2) {
          if (elect_one()) {
            bulk_store(g_kv1 + (j * 16 + i) * 880, sb + OFF_KVP, 7040);
            bulk_commit_wait();
            st_flag(g_hint + j * 32 + i, epoch);
          }
        } else {
          poll_hint(g_hint + j * 32 + lane, 0xffffu, epoch);
          if (hw == 0) TL(244);
          const int hc = min(ht, 59), r5 = (hc * 43) >> 9;
          const float2* src = g_kv1 + j * 16 * 880 + (5 * i + r5) * 11 + min(hc - 12 * r5, 10);
          const uint32_t tag = epoch & 15;
          float sa, sc;
          uint32_t bad;
          int it = 0;
          do {
            uint32_t a[16], b[16];
#pragma unroll
            for (int m = 0; m < 16; m++)
              asm volatile("ld.relaxed.gpu.global.v2.u32 {%0,%1}, [%2];" : "=r"(a[m]), "=r"(b[m]) : "l"(src + m * 880) : "memory");
            sa = sc = 0.f;
            bad = 0;
#pragma unroll
            for (int m = 0; m < 16; m++) {
              bad |= (a[m] ^ tag) | (b[m] ^ tag);
              sa += __uint_as_float(a[m]);
              sc += __uint_as_float(b[m]);
            }
          } while (__any_sync(0xffffffffu, bad & 15) && ++it < SPIN_LIMIT);
          asm volatile("st.relaxed.gpu.global.v2.u32 [%0], {%1,%2};" ::"l"(g_kv2 + j * 960 + i * 60 + hc), "r"(pack2(sa, sc)), "r"(epoch) : "memory");
          if (lane == 0) st_flag(g_hint + (8 + j) * 32 + 2 * i + hw, epoch);
        }
        if (hw == 0) TL(5);
        named_bar<2, 96>();
        poll_hint(g_hint + (8 + j) * 32 + lane, 0xffffffffu, epoch);
        if (hw == 0) TL(245);
        {
          uint4 v[5];
          ll_wait(v, reinterpret_cast<const uint4*>(g_kv2 + j * 960) + ht, 96, epoch);
          if (hw == 0) TL(6);
          const int d0 = ht / 6, part = ht - 6 * d0;
#pragma unroll
          for (int m = 0; m < 5; m++) {
            const int d = d0 + 16 * m, head = (d * 205) >> 12, n = 20 * head + 4 * part;
            const uint32_t a = sb + OFF_KVB + d * 16;
            const uint32_t z = head & 1 ? v[m].x << 16 : v[m].x & 0xffffu;
            if (part < 5) sts64(a + (n >> 3) * 1280 + (n & 7) * 2, v[m].x, v[m].z);
            else sts128(a + (10 + (head >> 1)) * 1280, z, z, z, z);
          }
        }
        fence_async_smem();
        __syncwarp();
        mbar_arrive_if0(lane, bars + 8 * KVB, hw == 2 ? 2 : 3);
        if (hw == 0) TL(7);
      }

      if (hw == 2) {
        if (cg < 24) {
          const float2 d = colsum(w1 + part * 160 * 1536 + 64 * cg, 1536, 0, 3);
          ll_store(g_cs + 960 + cpair, d.x, d.y, epoch);
        }
        mbar_wait_wd(bars + 8 * (DW + 15));
#pragma unroll 1
        for (int n = lane; n < 96; n += 32)
          rk1_store(sb + OFF_RK1 + n * 32, ll_sum4(g_cs + 960 + 96 * j + n, epoch), *reinterpret_cast<const uint32_t*>(b1 + 192 * j + 2 * n));
        fence_async_smem();
        __syncwarp();
        mbar_arrive_if0(lane, bars + 8 * SIDE2, 8);
        TL(18);
        mbar_wait_wd(bars + 8 * END);
        if (blockIdx.x == 0 && lane == 0) g_epoch = epoch;
      } else {
        const int s = hw;
#pragma unroll 1
        for (int ph = 0; ph < 3; ph++) {
          const uint32_t ab = bars + 8 * (ph < 2 ? AO + 16 * ph + 8 * s : AF + 12 * s);
          const uint32_t bytes = ph < 2 ? 10240 : 8192;
          uint8_t* gb = g_act + (ph * 32 + 2 * i + s) * 8 * 24576;
          uint32_t* fl = g_flag + (ph * 32 + 2 * i + s) * 32;
          const int r = min(lane, 8);
          int cc = r + (r >= j), bit = cc, slot, wb, off = 0;
          if (ph == 0) {
            slot = r < 5 ? r + 2 : r == 5 ? 1 : 2 * s;
            wb = DW + (s ? (r < 6 ? r + 1 : 9) : (r < 6 ? 8 : 0));
          } else if (ph == 1) {
            slot = (0x1249u >> (2 * r)) & 3;
            wb = r < 2 ? DW + 15 : DF + 8 * s + r - 2;
          } else {
            const int uu = (r * 11) >> 5, n = r - 3 * uu;
            cc = 2 * (n + (n >= p)) + q;
            bit = cc + (uu ? 8 : 0);
            off = uu * 8192;
            slot = (r + 3) & 3;
            wb = r ? DG + 12 * s + r - 1 : DF + 8 * s + 7;
          }
          const uint32_t fb = ab + 8 * r + (ph < 2 ? 8 : 24), wbar = bars + 8 * wb;
          const uint32_t dst = sb + (ph ? s * OFF_R1 : 0) + slot * bytes;
          const uint8_t* src = gb + cc * 24576 + off;
          uint32_t pm = ph < 2 ? 0x7fu : 0x1ffu, seen = 0;
          if (pm >> lane & 1) {
            mbar_expect(fb, bytes);
            mbar_arrive(fb, 7);
          }
          __syncwarp();
          auto fetch_ready = [&](uint32_t allow) {
            uint32_t ok;
            asm volatile("{.reg .pred p; mbarrier.test_wait.parity.shared::cta.b64 p, [%1], 0; selp.u32 %0, 1, 0, p;}" : "=r"(ok) : "r"(wbar) : "memory");
            ok &= (pm & seen & allow) >> lane;
            if (ok) bulk_load(dst, src, bytes, fb);
            pm &= ~__ballot_sync(0xffffffffu, ok);
          };
          auto poll = [&]() {
            seen = __ballot_sync(0xffffffffu, ld_acq(fl + bit) == epoch);
            fence_async_global();
          };
          mbar_wait(ab);
          if (ph == 0 && s == 1) mbar_wait(bars + 8 * SO);
          const uint32_t stg = sb + s * (ph ? OFF_R1 : PAGE);
          if (lane == 0) {
            bulk_store(gb + j * 24576, stg, bytes);
            bulk_commit_wait();
            if (ph == 0) mbar_arrive(bars + 8 * (DW + 8 * s), 4);
            if (ph == 1 || ph + s == 0) mbar_arrive(bars + 8 * (SO + ph + s), 8);
            fence_gpu();
            st_flag(fl + j, epoch);
          }
          __syncwarp();
          TL(44 + 2 * ph + s);
          if (ph == 2) {
            mbar_wait(ab + 8);
            if (lane == 0) bulk_store(gb + j * 24576 + 8192, stg + 8192, 8192);
            __syncwarp();
            poll();
            fetch_ready(3);
            mbar_wait(ab + 16);
            if (lane == 0) {
              bulk_store(gb + j * 24576 + 16384, stg + 16384, 8192);
              bulk_commit_wait();
            }
            __syncwarp();
            if (~seen & 7) poll();
            fetch_ready(7);
            if (lane == 0) {
              fence_gpu();
              st_flag(fl + 8 + j, epoch);
            }
            __syncwarp();
            TL(50 + s);
          }
          do {
            const int next = __ffs(pm) - 1;
            while (!(seen >> next & 1)) poll();
            if (next == 0) TL(52 + 2 * ph + s);
            mbar_wait(__shfl_sync(0xffffffffu, wbar, next));
            fetch_ready(~0u);
          } while (pm);
        }
      }
    }
  } else {
    asm volatile("barrier.cluster.wait.aligned;" ::: "memory");
    TC(tc4);
    uint32_t epoch;
    asm volatile("ld.relaxed.gpu.global.u32 %0, [%1];" : "=r"(epoch) : "l"(&g_epoch) : "memory");
    epoch += 1;
    const int s = warp >> 2, w = warp & 3, tid = threadIdx.x & 127, c = lane & 3, g = lane >> 2;
    uint32_t sb_peer;
    asm volatile("mapa.shared::cluster.u32 %0, %1, %2;" : "=r"(sb_peer) : "r"(sb), "r"(q ^ 1));
    const int row0 = 128 * i + 64 * s + 16 * w;
    const uint32_t bs8 = bars + 64 * s, bs12 = bars + 96 * s;
    uint32_t pq[20], hp[20];
    {
      float acc[80];
      const Desc dx = mkdesc(s * 512, 0, 16, 1024, 1);
      const int srow = 16 * j + 2 * warp + (lane >> 4);
      float sm = 0.f, sq = 0.f;
      float4 u;
      auto load_res = [&]() {
        const uint32_t xa = sb + (64 * s + 16 * w + (lane & 15)) * 128;
#pragma unroll
        for (int ks = 0; ks < 5; ks++) {
          const int col = ks < 4 ? cF + 16 * ks : cR;
          ldsm4(xa + (col >> 6) * 16384 + (((((col & 63) >> 3) + (lane >> 4)) ^ (lane & 7)) << 4), hp + 4 * ks);
        }
      };
#pragma unroll
      for (int st = 0; st < 20; st++) {
        if ((st & 1) == 0 && st <= 4) mbar_wait(bars + 8 * (FX + (st >> 1)));
        mbar_wait(bars + 8 * (st < 16 ? RF + st % 5 : FE + st - 16), st < 16 ? (st / 5) & 1 : 0);
        const Desc da = dx + (st >> 1) * 1024 + (st & 1) * 4;
        const Desc db = mkdesc(0, st < 16 ? OFF_RING + (st % 5) * 12288 : (st - 16) * 12288, 4096, 1024, 1);
        wg_fence();
        wgmma_ss<160, 0, 1>(acc, da, db, st != 0);
        wgmma_ss<160, 0, 1>(acc, da + 2, db + 128, 1);
        wg_commit();
        TL0(64 + st);
        if (st == 0) { TL0(0); TS(38, tc4); TS(62, (uint32_t)tl_gt); }
        if (st == 1) asm volatile("setmaxnreg.inc.sync.aligned.u32 208;");
        if (st >= 3 && st <= 11 && (st & 1)) {
          const float uu[4] = {u.x, u.y, u.z, u.w};
#pragma unroll
          for (int e = 0; e < 4; e++) {
            const float a = bf_lo(__float_as_uint(uu[e])), b = bf_hi(__float_as_uint(uu[e]));
            sm += a + b;
            sq = fmaf(a, a, fmaf(b, b, sq));
          }
        }
        if (st >= 2 && st <= 10 && (st & 1) == 0) {
          if (st > 4) mbar_wait(bars + 8 * (FX + st - 2));
          if (st > 2) mbar_wait(bars + 8 * (FX + st - 1));
          u = lds128(sb + (st - 2 + ((lane >> 3) & 1)) * 16384 + srow * 128 + (lane & 7) * 16);
        }
        if (st == 11 || st == 12) {
#pragma unroll
          for (int o = st == 11 ? 1 : 4; o < (st == 11 ? 4 : 16); o <<= 1) {
            sm += __shfl_xor_sync(0xffffffffu, sm, o);
            sq += __shfl_xor_sync(0xffffffffu, sq, o);
          }
        }
        if (st == 12) {
          if ((lane & 15) == 0) ll_store(g_ln1 + 128 * i + srow, sm, sq, epoch);
          TL0(39);
        }
        if (st == 13) mbar_arrive_if0(lane, bars + 8 * CG, 1);
        if (st == 14) mbar_arrive_if0(lane, bars + 8 * ST1, 1);
        if (st == 7 && p < 2) load_res();
        if (st == 8) mbar_arrive_if0(lane, bars + 8 * XF, 1);
        if (st == 16 && p >= 2) load_res();
        if (st > 0) {
          wg_wait<1>();
          if (st <= 16) mbar_arrive_if0(lane, bars + 8 * (RE + (st - 1) % 5), 1);
        }
      }
      TL0(12);
      float accq[40];
      auto q_step = [&](int t) {
        if (t >= 7) mbar_wait(bars + 8 * (FX + 3 + t));
        mbar_wait(bars + 8 * (RF + (t + 1) % 5), ((t + 16) / 5) & 1);
        const Desc da = dx + (t < 7 ? t + 3 : t - 3) * 1024, db = mkdesc(0, OFF_RING + ((t + 1) % 5) * 12288, 4096, 512, 2);
        wg_fence();
#pragma unroll
        for (int ks = 0; ks < 4; ks++) wgmma_ss<80, 0, 1>(accq, da + 2 * ks, db + 64 * ks, 1);
        wg_commit();
        TL0(84 + t);
      };
      mbar_wait(bars + 8 * SIDE);
      float a1[2], a2[2];
      uint32_t rk[2];
#pragma unroll
      for (int r = 0; r < 2; r++) {
        const float2 st = lds64(sb + OFF_LN1 + (64 * s + 16 * w + g + 8 * r) * 8);
        a1[r] = st.x;
        a2[r] = st.x * LOG2E;
        rk[r] = rk1_frag(st.y, 0.f, c);
      }
      wg_fence();
      wgmma_rs<160, 0>(acc, rk[0], rk[1], 0, 0, mkdesc(0, OFF_RK1, 0, 128, 0), 1);
      wg_commit();
      wgmma_rs<80, 0>(accq, rk[0], rk[1], 0, 0, mkdesc(0, OFF_RK1 + 2560, 0, 128, 0), 0);
      q_step(0);
      const int hi = lane >> 4;
      const uint32_t rowoff = sb + (64 * s + 16 * w + (lane & 15)) * 16;
      const uint32_t remoff = sb_peer + (64 * s + 16 * w) * 16 + lane * 4;
      auto put_remote = [&](const uint32_t* r, uint32_t a) {
#pragma unroll
        for (int e = 0; e < 4; e++)
          asm volatile("st.async.shared::cluster.mbarrier::complete_tx::bytes.b32 [%0], %1, [%2];"
                       ::"r"(a + (e >> 1) * 2048 + (e & 1) * 128), "r"(r[e]), "r"(sb_peer + OFF_BAR + 8 * RXK) : "memory");
      };
      const int mF = 2 * (p & 1) - q, g0 = 2 * mF + hi;
      const uint32_t ka = rowoff + g0 * 2048;
      wg_wait<1>();
      reg_fence(acc);
      mbar_arrive_if0(lane, bars + 8 * KD, 1);
      mbar_arrive_remote_if0(lane, sb_peer + OFF_BAR + 8 * PX);
      TL0(1);
      uint32_t r[4], r2[4];
      if (role == 0) {
        ln_pair<true>(acc + 64, a1, a2, r);
        ln_pair<true>(acc + 72, a1, a2, r2);
        mbar_wait_cluster(bars + 8 * PX);
        put_remote(r, remoff + (q ? 0 : 6 * 2048));
        put_remote(r2, remoff + (q ? 2 * 2048 : 8 * 2048));
      } else {
        ln_pair<false>(acc + 64, a1, a2, r);
        ln_pair<false>(acc + 72, a1, a2, r2);
        const uint32_t a = rowoff + (hi + (q ? 17 : 10)) * 2048;
        mbar_wait(bars + 8 * KD);
        stsm4(a, r[0], r[1], r[2], r[3]);
        stsm4(a + 4096, r2[0], r2[1], r2[2], r2[3]);
      }
      q_step(1);
#pragma unroll
      for (int n = 0; n < 4; n++) {
        const int P = n == 0 ? 0 : n == 1 ? 3 : n - 1;
        ln_pair<true>(acc + 8 * P, a1, a2, r);
        ln_pair<false>(acc + 32 + 8 * P, a1, a2, r2);
        if (n == 0) mbar_wait(bars + 8 * KD);
        if (n < 2 && mF == (n ? 2 : -1)) {
          mbar_wait_cluster(bars + 8 * PX);
          put_remote(r, remoff + (n ? 0 : 8 * 2048));
          put_remote(r2, remoff + (n ? 10 * 2048 : 19 * 2048));
        } else {
          stsm4(ka + P * 4096, r[0], r[1], r[2], r[3]);
          stsm4(ka + P * 4096 + (g0 + 2 * P > 4 ? 11 * 2048 : 10 * 2048), r2[0], r2[1], r2[2], r2[3]);
        }
        if (n == 0) {
          wg_wait<1>();
          mbar_arrive_if0(lane, bars + 8 * (RE + 1), 1);
          mbar_arrive_if0(lane, bars + 8 * ZK, 1);
        }
        if (n == 1) q_step(2);
        if (n == 2) {
          wg_wait<1>();
          mbar_arrive_if0(lane, bars + 8 * (RE + 2), 1);
        }
      }
      sts128(rowoff + 15 * 2048, ONES, ONES, ONES, ONES);
      TL0(2);
      mbar_wait_cluster(bars + 8 * RXK);
      fence_async_smem();
      named_bar<1, 256>();
      TL0(3);
      float kv[24];
      {
        const Desc da = mkdesc(s * 640, 0, 128, 2048, 0), db = da + 1280;
        wg_fence();
#pragma unroll
        for (int kk = 0; kk < 8; kk++) wgmma_ss<48, 1, 1>(kv, da + 16 * kk, db + 16 * kk, kk != 0);
        wg_commit();
      }
      wg_wait<1>();
      mbar_arrive_if0(lane, bars + 8 * (RE + 3), 1);
      q_step(3);
      {
        const uint32_t tag = epoch & 15;
        wg_wait<1>();
        reg_fence(kv);
        TL0(4);
#pragma unroll
        for (int hh = 0; hh < 2; hh++) {
          const int r = 16 * w + g + 8 * hh, eb = c - 4 * s - (r < 20 ? 0 : r < 40 ? 10 : 99);
          const uint32_t a = sb + OFF_KVP + (40 * s + r) * 88;
#pragma unroll
          for (int tt = 0; tt < 7; tt++) {
            const float v0 = tt < 6 ? kv[4 * tt + 2 * hh] : s ? kv[2 * hh] : kv[20 + 2 * hh];
            const float v1 = tt < 6 ? kv[4 * tt + 2 * hh + 1] : v0;
            asm volatile("{.reg .pred p; .reg .b32 a, b; setp.lt.u32 p, %3, %4; lop3.b32 a, %1, %5, 15, 0xD8; lop3.b32 b, %2, %5, 15, 0xD8;"
                         "@p st.shared.v2.u32 [%0], {a, b};}"
                         ::"r"(tt < 6 ? a + 8 * eb + 32 * tt : a + 80), "r"(__float_as_uint(v0)), "r"(__float_as_uint(v1)),
                         "r"(tt < 6 ? eb + 4 * tt : r), "r"(tt < 6 ? 10 : 40), "r"(tag) : "memory");
          }
        }
        fence_async_smem();
        __syncwarp();
      }
      mbar_arrive_if0(lane, bars + 8 * RKV, 1);
      TL0(9);
#pragma unroll
      for (int t = 4; t < 10; t++) {
        q_step(t);
        wg_wait<1>();
        mbar_arrive_if0(lane, bars + 8 * (RE + t % 5), 1);
      }
      wg_wait<0>();
      reg_fence(accq);
      mbar_arrive_if0(lane, bars + 8 * RE, 1);
      TL0(13);
#pragma unroll
      for (int P = 0; P < 5; P++) ln_pair<true>(accq + 8 * P, a1, a2, pq + 4 * P);
      reg_fence(pq);
      TL0(14);
    }
    const uint32_t rs = sb + s * OFF_R1;
    const uint32_t stoff = (lane >> 4) * 1024 + (16 * w + (lane & 15)) * 16;
    const Desc drs = mkdesc(s * (OFF_R1 / 16), 0, 1024, 128, 0);
    float accg[80];
    {
      {
        float o[48];
        wg_fence();
        mbar_wait(bars + 8 * (s ? OM : KVB));
        TL0(15);
#pragma unroll
        for (int ks = 0; ks < 5; ks++)
          wgmma_rs<96, 1>(o, pq[4 * ks], pq[4 * ks + 1], pq[4 * ks + 2], pq[4 * ks + 3], mkdesc(ks < 4 ? 16 * q : -64 * q, OFF_KVB + 256 * ks, 128, 1280, 0), ks != 0);
        wg_commit();
        mbar_arrive_if0(lane | s, bars + 8 * OM, 2);
        wg_wait<0>();
        reg_fence(o);
        float inv[2][4];
#pragma unroll
        for (int hh = 0; hh < 2; hh++)
#pragma unroll
          for (int h = 0; h < 4; h++) inv[hh][h] = rcp(o[40 + 4 * (h >> 1) + 2 * hh + (h & 1)] + 1e-6f);
        uint32_t r[4];
#pragma unroll
        for (int t = 0; t < 10; t++) {
#pragma unroll
          for (int hh = 0; hh < 2; hh++) {
            const float f = t == 2 ? (c < 2 ? inv[hh][0] : inv[hh][1]) : t == 7 ? (c < 2 ? inv[hh][2] : inv[hh][3]) : inv[hh][(8 * t) / 20];
            r[2 * (t & 1) + hh] = pack2(o[4 * t + 2 * hh] * f, o[4 * t + 2 * hh + 1] * f);
          }
          if (t & 1) stsm4(sb + s * PAGE + stoff + (t >> 1) * 2048, r[0], r[1], r[2], r[3]);
        }
        fence_async_smem();
        __syncwarp();
        mbar_arrive_if0(lane, bs8 + 8 * AO, 2);
        TLW(16 + s);
      }
      float acc[40];
#pragma unroll
      for (int r = 0; r < 20; r++) { acc[2 * r] = bf_lo(hp[r]); acc[2 * r + 1] = bf_hi(hp[r]); }
      reg_fence(acc);
#pragma unroll
      for (int t = 0; t < 8; t++) {
        mbar_wait(bars + 8 * (FWO + t));
        mbar_wait(bs8 + 8 * (AO + t));
        TLW(160 + 8 * s + t);
        if (t == 1) TLW(20 + s);
        const Desc da = mkdesc(t == 0 ? s * 640 : t == 7 ? s * 1280 : 0, (t == 0 || t == 7 ? 0 : t < 6 ? t + 1 : 1) * PAGE, 1024, 128, 0);
        const Desc db = mkdesc(0, 10 * PAGE + (t < 2 ? t ^ 1 : t) * 15360, 5120, 512, 2);
        wg_fence();
#pragma unroll
        for (int ks = 0; ks < 5; ks++) wgmma_ss<80, 0, 1>(acc, da + 128 * ks, db + 64 * ks, 1);
        wg_commit();
        if (t == 0) wg_wait<0>();
        else if (t > 1) wg_wait<1>();
        if (t != 1) mbar_arrive_if0(lane, bs8 + 8 * (DW + (t ? t - 1 : 0)), t ? 2 : 1);
      }
      wg_wait<0>();
      reg_fence(acc);
      mbar_arrive_if0(lane, bs8 + 8 * (DW + 7), 2);
      TLW(22 + s);
#pragma unroll
      for (int r = 0; r < 20; r++) hp[r] = pack2(acc[2 * r], acc[2 * r + 1]);
      mbar_wait(bs8 + 8 * (DW + 7));
#pragma unroll
      for (int ks = 0; ks < 5; ks++)
        stsm4(rs + stoff + ks * 2048, hp[4 * ks], hp[4 * ks + 1], hp[4 * ks + 2], hp[4 * ks + 3]);
      fence_async_smem();
      __syncwarp();
      mbar_arrive_if0(lane, bs8 + 8 * AH, 2);
      reg_fence(hp);
      TLW(24 + s);
    }
    float accf[96];
    uint4 hs[4];
    const uint4* hsp = g_hstat + ((2 * i + s) * 8 + 2 * c) * 64 + 16 * w + g;
    uint32_t rk[2];
    float3 gk[2];
#pragma unroll
    for (int t = 0; t < 8; t++) {
      mbar_wait(bars + 8 * (FW1 + t));
      mbar_wait(bs8 + 8 * (AH + t));
      TLW(176 + 8 * s + t);
      if (t == 1) TLW(26 + s);
      const Desc da = drs + (t % 3) * (PAGE / 16), db = mkdesc(0, (7 + 3 * (t % 5)) * PAGE, 8192, 1024, 1);
      wg_fence();
#pragma unroll
      for (int ks = 0; ks < 4; ks++) wgmma_ss<192, 0, 1>(accf, da + 128 * ks, db + 128 * ks, (t | ks) != 0);
      wgmma_ss<192, 0, 1>(accf, da + 512, mkdesc(0, (7 + 3 * (t % 5)) * PAGE + 24576, 2048, 1024, 1), 1);
      if (t == 7) wgmma_rs<192, 0>(accf, rk[0], rk[1], 0, 0, mkdesc(0, OFF_RK1, 0, 128, 0), 1);
      wg_commit();
      if (t == 5) {
        while (__any_sync(0xffffffffu, ((hs[0].y ^ epoch) | (hs[0].w ^ epoch) | (hs[1].y ^ epoch) | (hs[1].w ^ epoch) | (hs[2].y ^ epoch) |
                                        (hs[2].w ^ epoch) | (hs[3].y ^ epoch) | (hs[3].w ^ epoch)) != 0)) {
#pragma unroll
          for (int m = 0; m < 4; m++) hs[m] = ll_load(hsp + (m >> 1) * 64 + 8 * (m & 1));
        }
#pragma unroll
        for (int hh = 0; hh < 2; hh++) {
          float sm = __uint_as_float(hs[hh].x) + __uint_as_float(hs[2 + hh].x), sq = __uint_as_float(hs[hh].z) + __uint_as_float(hs[2 + hh].z);
#pragma unroll
          for (int o = 1; o < 4; o <<= 1) {
            sm += __shfl_xor_sync(0xffffffffu, sm, o);
            sq += __shfl_xor_sync(0xffffffffu, sq, o);
          }
          gk[hh].x = sm;
          gk[hh].y = sq;
        }
      }
      if (t == 6) {
        mbar_wait(bars + 8 * SIDE2);
#pragma unroll
        for (int hh = 0; hh < 2; hh++) {
          const float mean = gk[hh].x * (1.f / 640.f), var = fmaxf(fmaf(-mean, mean, gk[hh].y * (1.f / 640.f)), 0.f) + 1e-5f;
          const float a = rsqrtf(var);
          rk[hh] = rk1_frag(-mean, var * a, c);
          gk[hh] = make_float3(0.7978845608028654f * a, 0.7978845608028654f * 0.044715f * a * a * a, 0.5f * a);
        }
      }
      if (t == 0) {
        float sm[2] = {0.f, 0.f}, sq[2] = {0.f, 0.f};
#pragma unroll
        for (int m = 0; m < 10; m++) {
          const float2 b = lds64(sb + OFF_B2 + (8 * m + 2 * c) * 4);
#pragma unroll
          for (int hh = 0; hh < 2; hh++) {
            const float h0 = bf_lo(hp[2 * m + hh]), h1 = bf_hi(hp[2 * m + hh]);
            sm[hh] += h0 + h1;
            sq[hh] = fmaf(h0, h0, fmaf(h1, h1, sq[hh]));
            const float v0 = b.x + h0, v1 = b.y + h1;
            const int e = 4 * m + 2 * hh;
            if (m < 8) { accg[e] = v0; accg[e + 1] = v1; accg[32 + e] = 0.f; accg[33 + e] = 0.f; }
            else { accg[e + 32] = q ? 0.f : v0; accg[e + 33] = q ? 0.f : v1; accg[e + 40] = q ? v0 : 0.f; accg[e + 41] = q ? v1 : 0.f; }
          }
        }
        reg_fence(accg);
#pragma unroll
        for (int o = 1; o < 4; o <<= 1) {
#pragma unroll
          for (int hh = 0; hh < 2; hh++) {
            sm[hh] += __shfl_xor_sync(0xffffffffu, sm[hh], o);
            sq[hh] += __shfl_xor_sync(0xffffffffu, sq[hh], o);
          }
        }
        if (c < 2) ll_store(g_hstat + ((2 * i + s) * 8 + j) * 64 + 16 * w + g + 8 * c, c ? sm[1] : sm[0], c ? sq[1] : sq[0], epoch);
        wg_wait<0>();
      } else if (t > 1) wg_wait<1>();
      if (t != 1) mbar_arrive_if0(lane, bs8 + 8 * (DF + (t ? t - 1 : 0)), 2);
      if (t == 3) {
#pragma unroll
        for (int m = 0; m < 4; m++) hs[m] = ll_load(hsp + (m >> 1) * 64 + 8 * (m & 1));
      }
    }
    wg_wait<0>();
    reg_fence(accf);
    mbar_arrive_if0(lane, bs8 + 8 * (DF + 7), 2);
    TLW(28 + s);
    auto g_step = [&](int t, int slot) {
      mbar_wait(bars + 8 * (FW2 + t));
      mbar_wait(bs12 + 8 * (AF + t));
      TLW(192 + 12 * s + t);
      if (t == 3) TLW(32 + s);
      const Desc da = mkdesc(drs.base + (t & 3) * 512, 0, 1024, 128, 0), db = mkdesc(slot * 1536, OFF_W2, 8192, 1024, 1);
      wg_fence();
#pragma unroll
      for (int ks = 0; ks < 4; ks++) wgmma_ss<160, 0, 1>(accg, da + 128 * ks, db + 128 * ks, 1);
      wg_commit();
    };
#pragma unroll 1
    for (int t = 0; t < 3; t++) {
      uint32_t r[16];
#pragma unroll
      for (int e = 0; e < 16; e++) r[e] = pack2(gelu(accf[2 * e], gk[e & 1]), gelu(accf[2 * e + 1], gk[e & 1]));
      mbar_wait(bs8 + 8 * (DF + 7));
#pragma unroll
      for (int n = 0; n < 4; n++) stsm4(rs + stoff + t * 8192 + n * 2048, r[4 * n], r[4 * n + 1], r[4 * n + 2], r[4 * n + 3]);
      fence_async_smem();
      __syncwarp();
      mbar_arrive_if0(lane, bs12 + 8 * (AF + t), 2);
#pragma unroll
      for (int e = 0; e < 64; e++) accf[e] = accf[e + 32];
      g_step(t, (0x045 >> (4 * t)) & 7);
      wg_wait<1>();
      mbar_arrive_if0(lane | (t == 0), bs12 + 8 * (DG + t - 1), 2);
    }
    TLW(30 + s);
    wg_wait<0>();
    mbar_arrive_if0(lane, bs12 + 8 * (DG + 2), 2);
#pragma unroll
    for (int t = 3; t < 12; t++) {
      g_step(t, (0x321045 >> (4 * (t % 6))) & 7);
      if (t > 3) {
        wg_wait<1>();
        mbar_arrive_if0(lane, bs12 + 8 * (DG + t - 1), 2);
        if (t == 7) mbar_arrive_remote_if0(lane, sb_peer + OFF_BAR + 8 * PF);
      }
    }
    mbar_wait_cluster(bars + 8 * PF);
    wg_wait<0>();
    reg_fence(accg);
    mbar_arrive_if0(lane, bs12 + 8 * (DG + 11), 2);
    TLW(34 + s);
    {
      const uint32_t buf = OFF_W2 + 5 * 24576 + s * PAGE + tid * 16;
#pragma unroll
      for (int e = 0; e < 8; e++) {
        const float a = accg[64 + e], b = accg[72 + e];
        accg[64 + e] = q ? a : b;
        accg[72 + e] = q ? b : a;
      }
#pragma unroll
      for (int m = 0; m < 5; m++) {
        const float* a = accg + 32 + 8 * m;
        asm volatile("st.async.shared::cluster.mbarrier::complete_tx::bytes.v4.b32 [%0], {%1,%2,%3,%4}, [%5];"
                     ::"r"(sb_peer + buf + m * 2048), "r"(pack2(a[0], a[1])), "r"(pack2(a[2], a[3])), "r"(pack2(a[4], a[5])),
                     "r"(pack2(a[6], a[7])), "r"(sb_peer + OFF_BAR + 8 * (RX + s)) : "memory");
      }
      TLW(58 + s);
      mbar_wait(bs12 + 8 * (DG + 11));
      mbar_wait_cluster(bars + 8 * (RX + s));
      TLW(60 + s);
      float4 rx[5];
#pragma unroll
      for (int m = 0; m < 5; m++) rx[m] = lds128(sb + buf + m * 2048);
      const uint32_t stg = rs + w * 2816;
      const uint32_t sa = stg + (lane & 15) * 176 + (lane >> 4) * 16;
#pragma unroll
      for (int ks = 0; ks < 5; ks++) {
        const uint32_t u[4] = {__float_as_uint(rx[ks].x), __float_as_uint(rx[ks].y), __float_as_uint(rx[ks].z), __float_as_uint(rx[ks].w)};
        const float* a = accg + (ks < 4 ? 8 * ks : 72);
        stsm4(sa + ks * 32, pack2(a[0] + bf_lo(u[0]), a[1] + bf_hi(u[0])), pack2(a[2] + bf_lo(u[1]), a[3] + bf_hi(u[1])),
              pack2(a[4] + bf_lo(u[2]), a[5] + bf_hi(u[2])), pack2(a[6] + bf_lo(u[3]), a[7] + bf_hi(u[3])));
      }
      __syncwarp();
#pragma unroll
      for (int m = 0; m < 4; m++) rx[m] = lds128(stg + (4 * m + (lane >> 3)) * 176 + (lane & 7) * 16);
      rx[4] = lds128(stg + (lane >> 1) * 176 + 128 + (lane & 1) * 16);
      __nv_bfloat16* outp = out + (row0 + (lane >> 3)) * 640 + cF + (lane & 7) * 8;
#pragma unroll
      for (int m = 0; m < 4; m++) *reinterpret_cast<float4*>(outp + m * 4 * 640) = rx[m];
      *reinterpret_cast<float4*>(out + (row0 + (lane >> 1)) * 640 + cR + (lane & 1) * 8) = rx[4];
    }
    mbar_arrive_if0(lane, bars + 8 * END, 1);
    TLW(36 + s);
  }
}

typedef CUresult (*EncodeFn)(CUtensorMap*, CUtensorMapDataType, cuuint32_t, void*, const cuuint64_t*, const cuuint64_t*,
                             const cuuint32_t*, const cuuint32_t*, CUtensorMapInterleave, CUtensorMapSwizzle,
                             CUtensorMapL2promotion, CUtensorMapFloatOOBfill);

void make_map(EncodeFn enc, CUtensorMap* tm, const void* base, int rows, int cols, int box_rows, int box_cols, int group, int natom,
              CUtensorMapSwizzle sw) {
  const cuuint64_t dims[3] = {(cuuint64_t)(natom ? group : cols), (cuuint64_t)rows, (cuuint64_t)(cols / group)};
  const cuuint64_t strides[2] = {(cuuint64_t)cols * 2, (cuuint64_t)group * 2};
  const cuuint32_t box[3] = {(cuuint32_t)box_cols, (cuuint32_t)box_rows, (cuuint32_t)natom}, es[3] = {1, 1, 1};
  enc(tm, CU_TENSOR_MAP_DATA_TYPE_BFLOAT16, natom ? 3 : 2, const_cast<void*>(base), dims, strides, box, es,
      CU_TENSOR_MAP_INTERLEAVE_NONE, sw, CU_TENSOR_MAP_L2_PROMOTION_L2_128B, CU_TENSOR_MAP_FLOAT_OOB_FILL_NONE);
}

}

extern "C" void kernel_launch(void* const* d_in, const int* in_sizes, int n_in, void* d_out, int out_size) {
  const __nv_bfloat16* x = (const __nv_bfloat16*)d_in[0];
  const __nv_bfloat16* wqkv = (const __nv_bfloat16*)d_in[1];
  const __nv_bfloat16* wo = (const __nv_bfloat16*)d_in[2];
  const __nv_bfloat16* w1 = (const __nv_bfloat16*)d_in[4];
  const __nv_bfloat16* b1 = (const __nv_bfloat16*)d_in[5];
  const __nv_bfloat16* w2 = (const __nv_bfloat16*)d_in[6];
  const __nv_bfloat16* b2 = (const __nv_bfloat16*)d_in[7];

  void* fn = nullptr;
  cudaDriverEntryPointQueryResult qr;
  cudaGetDriverEntryPoint("cuTensorMapEncodeTiled", &fn, cudaEnableDefault, &qr);
  EncodeFn enc = (EncodeFn)fn;
  const CUtensorMapSwizzle S128 = CU_TENSOR_MAP_SWIZZLE_128B, S64 = CU_TENSOR_MAP_SWIZZLE_64B;
  Maps maps;
  make_map(enc, &maps.m[M_X], x, 2048, 640, 128, 64, 64, 0, S128);
  make_map(enc, &maps.m[M_KVF], wqkv, 640, 1920, 32, 64, 640, 2, S128);
  make_map(enc, &maps.m[M_KVH], wqkv, 640, 1920, 32, 32, 64, 0, S128);
  make_map(enc, &maps.m[M_Q2], wqkv, 640, 1920, 64, 32, 32, 2, S64);
  make_map(enc, &maps.m[M_QR], wqkv, 640, 1920, 64, 16, 64, 0, S64);
  make_map(enc, &maps.m[M_WO2], wo, 640, 640, 80, 32, 32, 2, S64);
  make_map(enc, &maps.m[M_WOR], wo, 640, 640, 80, 16, 64, 0, S64);
  make_map(enc, &maps.m[M_W1], w1, 640, 1536, 64, 64, 64, 3, S128);
  make_map(enc, &maps.m[M_W1R], w1, 640, 1536, 16, 64, 64, 3, S128);
  make_map(enc, &maps.m[M_W2F], w2, 1536, 640, 64, 64, 64, 0, S128);
  make_map(enc, &maps.m[M_W2H], w2, 1536, 640, 64, 32, 64, 0, S128);
  cudaFuncSetAttribute(fused_block_kernel, cudaFuncAttributeMaxDynamicSharedMemorySize, SMEM_BYTES);
  fused_block_kernel<<<128, 384, SMEM_BYTES>>>(maps, x, wqkv, wo, w1, b1, w2, b2, (__nv_bfloat16*)d_out);
}
```

```cpp
#include <cuda_runtime.h>
#include <cuda_bf16.h>
#include <cuda.h>
#include <stdint.h>

namespace {

struct Desc { uint32_t base, off, hi; };
__device__ __forceinline__ Desc operator+(Desc d, uint32_t o) { return Desc{d.base, d.off + o, d.hi}; }
template <int TA, int TB> __device__ __forceinline__ void wgmma_ss_n48(float (&d)[24], Desc a, Desc b, int sc) {
  asm volatile("{.reg .pred p; .reg .b32 t, u; .reg .b64 da, db; setp.ne.b32 p, %30, 0; add.u32 t, %24, %25; mov.b64 da, {t, %26}; add.u32 u, %27, %28; mov.b64 db, {u, %29};"
    "wgmma.mma_async.sync.aligned.m64n48k16.f32.bf16.bf16 {%0,%1,%2,%3,%4,%5,%6,%7,%8,%9,%10,%11,%12,%13,%14,%15,%16,%17,%18,%19,%20,%21,%22,%23}, da, db, p, 1, 1, %31, %32;}"
    : "+f"(d[0]),"+f"(d[1]),"+f"(d[2]),"+f"(d[3]),"+f"(d[4]),"+f"(d[5]),"+f"(d[6]),"+f"(d[7]),"+f"(d[8]),"+f"(d[9]),"+f"(d[10]),"+f"(d[11]),"+f"(d[12]),"+f"(d[13]),"+f"(d[14]),"+f"(d[15]),"+f"(d[16]),"+f"(d[17]),"+f"(d[18]),"+f"(d[19]),"+f"(d[20]),"+f"(d[21]),"+f"(d[22]),"+f"(d[23])
    : "r"(a.base), "r"(a.off), "r"(a.hi), "r"(b.base), "r"(b.off), "r"(b.hi), "r"(sc), "n"(TA), "n"(TB));
}
template <int TA, int TB> __device__ __forceinline__ void wgmma_ss_n80(float (&d)[40], Desc a, Desc b, int sc) {
  asm volatile("{.reg .pred p; .reg .b32 t, u; .reg .b64 da, db; setp.ne.b32 p, %46, 0; add.u32 t, %40, %41; mov.b64 da, {t, %42}; add.u32 u, %43, %44; mov.b64 db, {u, %45};"
    "wgmma.mma_async.sync.aligned.m64n80k16.f32.bf16.bf16 {%0,%1,%2,%3,%4,%5,%6,%7,%8,%9,%10,%11,%12,%13,%14,%15,%16,%17,%18,%19,%20,%21,%22,%23,%24,%25,%26,%27,%28,%29,%30,%31,%32,%33,%34,%35,%36,%37,%38,%39}, da, db, p, 1, 1, %47, %48;}"
    : "+f"(d[0]),"+f"(d[1]),"+f"(d[2]),"+f"(d[3]),"+f"(d[4]),"+f"(d[5]),"+f"(d[6]),"+f"(d[7]),"+f"(d[8]),"+f"(d[9]),"+f"(d[10]),"+f"(d[11]),"+f"(d[12]),"+f"(d[13]),"+f"(d[14]),"+f"(d[15]),"+f"(d[16]),"+f"(d[17]),"+f"(d[18]),"+f"(d[19]),"+f"(d[20]),"+f"(d[21]),"+f"(d[22]),"+f"(d[23]),"+f"(d[24]),"+f"(d[25]),"+f"(d[26]),"+f"(d[27]),"+f"(d[28]),"+f"(d[29]),"+f"(d[30]),"+f"(d[31]),"+f"(d[32]),"+f"(d[33]),"+f"(d[34]),"+f"(d[35]),"+f"(d[36]),"+f"(d[37]),"+f"(d[38]),"+f"(d[39])
    : "r"(a.base), "r"(a.off), "r"(a.hi), "r"(b.base), "r"(b.off), "r"(b.hi), "r"(sc), "n"(TA), "n"(TB));
}
template <int TA, int TB> __device__ __forceinline__ void wgmma_ss_n160(float (&d)[80], Desc a, Desc b, int sc) {
  asm volatile("{.reg .pred p; .reg .b32 t, u; .reg .b64 da, db; setp.ne.b32 p, %86, 0; add.u32 t, %80, %81; mov.b64 da, {t, %82}; add.u32 u, %83, %84; mov.b64 db, {u, %85};"
    "wgmma.mma_async.sync.aligned.m64n160k16.f32.bf16.bf16 {%0,%1,%2,%3,%4,%5,%6,%7,%8,%9,%10,%11,%12,%13,%14,%15,%16,%17,%18,%19,%20,%21,%22,%23,%24,%25,%26,%27,%28,%29,%30,%31,%32,%33,%34,%35,%36,%37,%38,%39,%40,%41,%42,%43,%44,%45,%46,%47,%48,%49,%50,%51,%52,%53,%54,%55,%56,%57,%58,%59,%60,%61,%62,%63,%64,%65,%66,%67,%68,%69,%70,%71,%72,%73,%74,%75,%76,%77,%78,%79}, da, db, p, 1, 1, %87, %88;}"
    : "+f"(d[0]),"+f"(d[1]),"+f"(d[2]),"+f"(d[3]),"+f"(d[4]),"+f"(d[5]),"+f"(d[6]),"+f"(d[7]),"+f"(d[8]),"+f"(d[9]),"+f"(d[10]),"+f"(d[11]),"+f"(d[12]),"+f"(d[13]),"+f"(d[14]),"+f"(d[15]),"+f"(d[16]),"+f"(d[17]),"+f"(d[18]),"+f"(d[19]),"+f"(d[20]),"+f"(d[21]),"+f"(d[22]),"+f"(d[23]),"+f"(d[24]),"+f"(d[25]),"+f"(d[26]),"+f"(d[27]),"+f"(d[28]),"+f"(d[29]),"+f"(d[30]),"+f"(d[31]),"+f"(d[32]),"+f"(d[33]),"+f"(d[34]),"+f"(d[35]),"+f"(d[36]),"+f"(d[37]),"+f"(d[38]),"+f"(d[39]),"+f"(d[40]),"+f"(d[41]),"+f"(d[42]),"+f"(d[43]),"+f"(d[44]),"+f"(d[45]),"+f"(d[46]),"+f"(d[47]),"+f"(d[48]),"+f"(d[49]),"+f"(d[50]),"+f"(d[51]),"+f"(d[52]),"+f"(d[53]),"+f"(d[54]),"+f"(d[55]),"+f"(d[56]),"+f"(d[57]),"+f"(d[58]),"+f"(d[59]),"+f"(d[60]),"+f"(d[61]),"+f"(d[62]),"+f"(d[63]),"+f"(d[64]),"+f"(d[65]),"+f"(d[66]),"+f"(d[67]),"+f"(d[68]),"+f"(d[69]),"+f"(d[70]),"+f"(d[71]),"+f"(d[72]),"+f"(d[73]),"+f"(d[74]),"+f"(d[75]),"+f"(d[76]),"+f"(d[77]),"+f"(d[78]),"+f"(d[79])
    : "r"(a.base), "r"(a.off), "r"(a.hi), "r"(b.base), "r"(b.off), "r"(b.hi), "r"(sc), "n"(TA), "n"(TB));
}
template <int TA, int TB> __device__ __forceinline__ void wgmma_ss_n192(float (&d)[96], Desc a, Desc b, int sc) {
  asm volatile("{.reg .pred p; .reg .b32 t, u; .reg .b64 da, db; setp.ne.b32 p, %102, 0; add.u32 t, %96, %97; mov.b64 da, {t, %98}; add.u32 u, %99, %100; mov.b64 db, {u, %101};"
    "wgmma.mma_async.sync.aligned.m64n192k16.f32.bf16.bf16 {%0,%1,%2,%3,%4,%5,%6,%7,%8,%9,%10,%11,%12,%13,%14,%15,%16,%17,%18,%19,%20,%21,%22,%23,%24,%25,%26,%27,%28,%29,%30,%31,%32,%33,%34,%35,%36,%37,%38,%39,%40,%41,%42,%43,%44,%45,%46,%47,%48,%49,%50,%51,%52,%53,%54,%55,%56,%57,%58,%59,%60,%61,%62,%63,%64,%65,%66,%67,%68,%69,%70,%71,%72,%73,%74,%75,%76,%77,%78,%79,%80,%81,%82,%83,%84,%85,%86,%87,%88,%89,%90,%91,%92,%93,%94,%95}, da, db, p, 1, 1, %103, %104;}"
    : "+f"(d[0]),"+f"(d[1]),"+f"(d[2]),"+f"(d[3]),"+f"(d[4]),"+f"(d[5]),"+f"(d[6]),"+f"(d[7]),"+f"(d[8]),"+f"(d[9]),"+f"(d[10]),"+f"(d[11]),"+f"(d[12]),"+f"(d[13]),"+f"(d[14]),"+f"(d[15]),"+f"(d[16]),"+f"(d[17]),"+f"(d[18]),"+f"(d[19]),"+f"(d[20]),"+f"(d[21]),"+f"(d[22]),"+f"(d[23]),"+f"(d[24]),"+f"(d[25]),"+f"(d[26]),"+f"(d[27]),"+f"(d[28]),"+f"(d[29]),"+f"(d[30]),"+f"(d[31]),"+f"(d[32]),"+f"(d[33]),"+f"(d[34]),"+f"(d[35]),"+f"(d[36]),"+f"(d[37]),"+f"(d[38]),"+f"(d[39]),"+f"(d[40]),"+f"(d[41]),"+f"(d[42]),"+f"(d[43]),"+f"(d[44]),"+f"(d[45]),"+f"(d[46]),"+f"(d[47]),"+f"(d[48]),"+f"(d[49]),"+f"(d[50]),"+f"(d[51]),"+f"(d[52]),"+f"(d[53]),"+f"(d[54]),"+f"(d[55]),"+f"(d[56]),"+f"(d[57]),"+f"(d[58]),"+f"(d[59]),"+f"(d[60]),"+f"(d[61]),"+f"(d[62]),"+f"(d[63]),"+f"(d[64]),"+f"(d[65]),"+f"(d[66]),"+f"(d[67]),"+f"(d[68]),"+f"(d[69]),"+f"(d[70]),"+f"(d[71]),"+f"(d[72]),"+f"(d[73]),"+f"(d[74]),"+f"(d[75]),"+f"(d[76]),"+f"(d[77]),"+f"(d[78]),"+f"(d[79]),"+f"(d[80]),"+f"(d[81]),"+f"(d[82]),"+f"(d[83]),"+f"(d[84]),"+f"(d[85]),"+f"(d[86]),"+f"(d[87]),"+f"(d[88]),"+f"(d[89]),"+f"(d[90]),"+f"(d[91]),"+f"(d[92]),"+f"(d[93]),"+f"(d[94]),"+f"(d[95])
    : "r"(a.base), "r"(a.off), "r"(a.hi), "r"(b.base), "r"(b.off), "r"(b.hi), "r"(sc), "n"(TA), "n"(TB));
}
template <int TB> __device__ __forceinline__ void wgmma_rs_n80(float (&d)[40], uint32_t a0, uint32_t a1, uint32_t a2, uint32_t a3, Desc b, int sc) {
  asm volatile("{.reg .pred p; .reg .b32 u; .reg .b64 db; setp.ne.b32 p, %47, 0; add.u32 u, %44, %45; mov.b64 db, {u, %46};"
    "wgmma.mma_async.sync.aligned.m64n80k16.f32.bf16.bf16 {%0,%1,%2,%3,%4,%5,%6,%7,%8,%9,%10,%11,%12,%13,%14,%15,%16,%17,%18,%19,%20,%21,%22,%23,%24,%25,%26,%27,%28,%29,%30,%31,%32,%33,%34,%35,%36,%37,%38,%39}, {%40,%41,%42,%43}, db, p, 1, 1, %48;}"
    : "+f"(d[0]),"+f"(d[1]),"+f"(d[2]),"+f"(d[3]),"+f"(d[4]),"+f"(d[5]),"+f"(d[6]),"+f"(d[7]),"+f"(d[8]),"+f"(d[9]),"+f"(d[10]),"+f"(d[11]),"+f"(d[12]),"+f"(d[13]),"+f"(d[14]),"+f"(d[15]),"+f"(d[16]),"+f"(d[17]),"+f"(d[18]),"+f"(d[19]),"+f"(d[20]),"+f"(d[21]),"+f"(d[22]),"+f"(d[23]),"+f"(d[24]),"+f"(d[25]),"+f"(d[26]),"+f"(d[27]),"+f"(d[28]),"+f"(d[29]),"+f"(d[30]),"+f"(d[31]),"+f"(d[32]),"+f"(d[33]),"+f"(d[34]),"+f"(d[35]),"+f"(d[36]),"+f"(d[37]),"+f"(d[38]),"+f"(d[39])
    : "r"(a0), "r"(a1), "r"(a2), "r"(a3), "r"(b.base), "r"(b.off), "r"(b.hi), "r"(sc), "n"(TB));
}
template <int TB> __device__ __forceinline__ void wgmma_rs_n96(float (&d)[48], uint32_t a0, uint32_t a1, uint32_t a2, uint32_t a3, Desc b, int sc) {
  asm volatile("{.reg .pred p; .reg .b32 u; .reg .b64 db; setp.ne.b32 p, %55, 0; add.u32 u, %52, %53; mov.b64 db, {u, %54};"
    "wgmma.mma_async.sync.aligned.m64n96k16.f32.bf16.bf16 {%0,%1,%2,%3,%4,%5,%6,%7,%8,%9,%10,%11,%12,%13,%14,%15,%16,%17,%18,%19,%20,%21,%22,%23,%24,%25,%26,%27,%28,%29,%30,%31,%32,%33,%34,%35,%36,%37,%38,%39,%40,%41,%42,%43,%44,%45,%46,%47}, {%48,%49,%50,%51}, db, p, 1, 1, %56;}"
    : "+f"(d[0]),"+f"(d[1]),"+f"(d[2]),"+f"(d[3]),"+f"(d[4]),"+f"(d[5]),"+f"(d[6]),"+f"(d[7]),"+f"(d[8]),"+f"(d[9]),"+f"(d[10]),"+f"(d[11]),"+f"(d[12]),"+f"(d[13]),"+f"(d[14]),"+f"(d[15]),"+f"(d[16]),"+f"(d[17]),"+f"(d[18]),"+f"(d[19]),"+f"(d[20]),"+f"(d[21]),"+f"(d[22]),"+f"(d[23]),"+f"(d[24]),"+f"(d[25]),"+f"(d[26]),"+f"(d[27]),"+f"(d[28]),"+f"(d[29]),"+f"(d[30]),"+f"(d[31]),"+f"(d[32]),"+f"(d[33]),"+f"(d[34]),"+f"(d[35]),"+f"(d[36]),"+f"(d[37]),"+f"(d[38]),"+f"(d[39]),"+f"(d[40]),"+f"(d[41]),"+f"(d[42]),"+f"(d[43]),"+f"(d[44]),"+f"(d[45]),"+f"(d[46]),"+f"(d[47])
    : "r"(a0), "r"(a1), "r"(a2), "r"(a3), "r"(b.base), "r"(b.off), "r"(b.hi), "r"(sc), "n"(TB));
}
template <int TB> __device__ __forceinline__ void wgmma_rs_n160(float (&d)[80], uint32_t a0, uint32_t a1, uint32_t a2, uint32_t a3, Desc b, int sc) {
  asm volatile("{.reg .pred p; .reg .b32 u; .reg .b64 db; setp.ne.b32 p, %87, 0; add.u32 u, %84, %85; mov.b64 db, {u, %86};"
    "wgmma.mma_async.sync.aligned.m64n160k16.f32.bf16.bf16 {%0,%1,%2,%3,%4,%5,%6,%7,%8,%9,%10,%11,%12,%13,%14,%15,%16,%17,%18,%19,%20,%21,%22,%23,%24,%25,%26,%27,%28,%29,%30,%31,%32,%33,%34,%35,%36,%37,%38,%39,%40,%41,%42,%43,%44,%45,%46,%47,%48,%49,%50,%51,%52,%53,%54,%55,%56,%57,%58,%59,%60,%61,%62,%63,%64,%65,%66,%67,%68,%69,%70,%71,%72,%73,%74,%75,%76,%77,%78,%79}, {%80,%81,%82,%83}, db, p, 1, 1, %88;}"
    : "+f"(d[0]),"+f"(d[1]),"+f"(d[2]),"+f"(d[3]),"+f"(d[4]),"+f"(d[5]),"+f"(d[6]),"+f"(d[7]),"+f"(d[8]),"+f"(d[9]),"+f"(d[10]),"+f"(d[11]),"+f"(d[12]),"+f"(d[13]),"+f"(d[14]),"+f"(d[15]),"+f"(d[16]),"+f"(d[17]),"+f"(d[18]),"+f"(d[19]),"+f"(d[20]),"+f"(d[21]),"+f"(d[22]),"+f"(d[23]),"+f"(d[24]),"+f"(d[25]),"+f"(d[26]),"+f"(d[27]),"+f"(d[28]),"+f"(d[29]),"+f"(d[30]),"+f"(d[31]),"+f"(d[32]),"+f"(d[33]),"+f"(d[34]),"+f"(d[35]),"+f"(d[36]),"+f"(d[37]),"+f"(d[38]),"+f"(d[39]),"+f"(d[40]),"+f"(d[41]),"+f"(d[42]),"+f"(d[43]),"+f"(d[44]),"+f"(d[45]),"+f"(d[46]),"+f"(d[47]),"+f"(d[48]),"+f"(d[49]),"+f"(d[50]),"+f"(d[51]),"+f"(d[52]),"+f"(d[53]),"+f"(d[54]),"+f"(d[55]),"+f"(d[56]),"+f"(d[57]),"+f"(d[58]),"+f"(d[59]),"+f"(d[60]),"+f"(d[61]),"+f"(d[62]),"+f"(d[63]),"+f"(d[64]),"+f"(d[65]),"+f"(d[66]),"+f"(d[67]),"+f"(d[68]),"+f"(d[69]),"+f"(d[70]),"+f"(d[71]),"+f"(d[72]),"+f"(d[73]),"+f"(d[74]),"+f"(d[75]),"+f"(d[76]),"+f"(d[77]),"+f"(d[78]),"+f"(d[79])
    : "r"(a0), "r"(a1), "r"(a2), "r"(a3), "r"(b.base), "r"(b.off), "r"(b.hi), "r"(sc), "n"(TB));
}
template <int TB> __device__ __forceinline__ void wgmma_rs_n192(float (&d)[96], uint32_t a0, uint32_t a1, uint32_t a2, uint32_t a3, Desc b, int sc) {
  asm volatile("{.reg .pred p; .reg .b32 u; .reg .b64 db; setp.ne.b32 p, %103, 0; add.u32 u, %100, %101; mov.b64 db, {u, %102};"
    "wgmma.mma_async.sync.aligned.m64n192k16.f32.bf16.bf16 {%0,%1,%2,%3,%4,%5,%6,%7,%8,%9,%10,%11,%12,%13,%14,%15,%16,%17,%18,%19,%20,%21,%22,%23,%24,%25,%26,%27,%28,%29,%30,%31,%32,%33,%34,%35,%36,%37,%38,%39,%40,%41,%42,%43,%44,%45,%46,%47,%48,%49,%50,%51,%52,%53,%54,%55,%56,%57,%58,%59,%60,%61,%62,%63,%64,%65,%66,%67,%68,%69,%70,%71,%72,%73,%74,%75,%76,%77,%78,%79,%80,%81,%82,%83,%84,%85,%86,%87,%88,%89,%90,%91,%92,%93,%94,%95}, {%96,%97,%98,%99}, db, p, 1, 1, %104;}"
    : "+f"(d[0]),"+f"(d[1]),"+f"(d[2]),"+f"(d[3]),"+f"(d[4]),"+f"(d[5]),"+f"(d[6]),"+f"(d[7]),"+f"(d[8]),"+f"(d[9]),"+f"(d[10]),"+f"(d[11]),"+f"(d[12]),"+f"(d[13]),"+f"(d[14]),"+f"(d[15]),"+f"(d[16]),"+f"(d[17]),"+f"(d[18]),"+f"(d[19]),"+f"(d[20]),"+f"(d[21]),"+f"(d[22]),"+f"(d[23]),"+f"(d[24]),"+f"(d[25]),"+f"(d[26]),"+f"(d[27]),"+f"(d[28]),"+f"(d[29]),"+f"(d[30]),"+f"(d[31]),"+f"(d[32]),"+f"(d[33]),"+f"(d[34]),"+f"(d[35]),"+f"(d[36]),"+f"(d[37]),"+f"(d[38]),"+f"(d[39]),"+f"(d[40]),"+f"(d[41]),"+f"(d[42]),"+f"(d[43]),"+f"(d[44]),"+f"(d[45]),"+f"(d[46]),"+f"(d[47]),"+f"(d[48]),"+f"(d[49]),"+f"(d[50]),"+f"(d[51]),"+f"(d[52]),"+f"(d[53]),"+f"(d[54]),"+f"(d[55]),"+f"(d[56]),"+f"(d[57]),"+f"(d[58]),"+f"(d[59]),"+f"(d[60]),"+f"(d[61]),"+f"(d[62]),"+f"(d[63]),"+f"(d[64]),"+f"(d[65]),"+f"(d[66]),"+f"(d[67]),"+f"(d[68]),"+f"(d[69]),"+f"(d[70]),"+f"(d[71]),"+f"(d[72]),"+f"(d[73]),"+f"(d[74]),"+f"(d[75]),"+f"(d[76]),"+f"(d[77]),"+f"(d[78]),"+f"(d[79]),"+f"(d[80]),"+f"(d[81]),"+f"(d[82]),"+f"(d[83]),"+f"(d[84]),"+f"(d[85]),"+f"(d[86]),"+f"(d[87]),"+f"(d[88]),"+f"(d[89]),"+f"(d[90]),"+f"(d[91]),"+f"(d[92]),"+f"(d[93]),"+f"(d[94]),"+f"(d[95])
    : "r"(a0), "r"(a1), "r"(a2), "r"(a3), "r"(b.base), "r"(b.off), "r"(b.hi), "r"(sc), "n"(TB));
}
template <int N, int TA, int TB> __device__ __forceinline__ void wgmma_ss(float (&d)[N / 2], Desc a, Desc b, int sc) {
  if constexpr (N == 48) wgmma_ss_n48<TA, TB>(d, a, b, sc);
  else if constexpr (N == 80) wgmma_ss_n80<TA, TB>(d, a, b, sc);
  else if constexpr (N == 160) wgmma_ss_n160<TA, TB>(d, a, b, sc);
  else if constexpr (N == 192) wgmma_ss_n192<TA, TB>(d, a, b, sc);
}
template <int N, int TB> __device__ __forceinline__ void wgmma_rs(float (&d)[N / 2], uint32_t a0, uint32_t a1, uint32_t a2, uint32_t a3, Desc b, int sc) {
  if constexpr (N == 80) wgmma_rs_n80<TB>(d, a0, a1, a2, a3, b, sc);
  else if constexpr (N == 96) wgmma_rs_n96<TB>(d, a0, a1, a2, a3, b, sc);
  else if constexpr (N == 160) wgmma_rs_n160<TB>(d, a0, a1, a2, a3, b, sc);
  else if constexpr (N == 192) wgmma_rs_n192<TB>(d, a0, a1, a2, a3, b, sc);
}

constexpr uint32_t SMEM_BASE = 1024;
constexpr uint32_t PAGE = 10240;
constexpr uint32_t OFF_RING = 16 * PAGE;
constexpr uint32_t OFF_KVB = 50176;
constexpr uint32_t OFF_KVP = 43008;
constexpr uint32_t OFF_R1 = 35840;
constexpr uint32_t OFF_MISC = 22 * PAGE;
constexpr uint32_t OFF_W2 = OFF_MISC - 6 * 24576;
constexpr uint32_t OFF_BAR = OFF_MISC;
constexpr uint32_t OFF_LN1 = OFF_MISC + 1920;
constexpr uint32_t OFF_RK1 = OFF_MISC + 2944;
constexpr uint32_t OFF_B2 = OFF_MISC + 1600;
constexpr uint32_t OFF_SCR = OFF_MISC + 6784;
constexpr uint32_t SMEM_BYTES = OFF_MISC + 7040;

enum : int {
  RF = 0, FX = 5, FE = 18, RX = 22, RXK = 24,
  RE = 25, PX = 30, PF = 31, SIDE = 32, ZK = 33, RKV = 34, ST1 = 35, XF = 36, KD = 37, CG = 38,
  FWO = 40, FW1 = 48, FW2 = 56,
  AO = 70, AH = 86, AF = 102,
  DW = 126, DF = 142, DG = 158,
  SIDE2 = 185, KVB = 186, END = 187, OM = 188
};

__device__ uint32_t g_epoch;
__device__ uint4 g_ln1[2048];
__device__ uint4 g_cs[4 * 1728];
__device__ uint4 g_hstat[32 * 8 * 64];
__device__ __align__(128) float g_kv[8 * 1696];
__device__ __align__(128) uint32_t g_flag[(3 * 32 + 16) * 32];
__device__ __align__(128) uint8_t g_act[3 * 32 * 8 * 24576];

struct Maps { CUtensorMap m[11]; };
enum : int { M_X, M_KVF, M_KVH, M_Q2, M_QR, M_WO2, M_WOR, M_W1, M_W1R, M_W2F, M_W2H };

#define TL(id)
#define TLW(id)
#define TL0(id)
#define TL1(id)
#define TC(v)
#define TS(id, v)

constexpr int SPIN_LIMIT = 1 << 19;

__device__ __forceinline__ bool elect_one() {
  uint32_t p;
  asm volatile("{.reg .pred P; elect.sync _|P, 0xffffffff; selp.u32 %0,1,0,P;}" : "=r"(p));
  return p;
}
__device__ __forceinline__ void mbar_wait(uint32_t bar, uint32_t parity = 0) {
  asm volatile("{.reg .pred p;\nW: mbarrier.try_wait.parity.shared::cta.b64 p, [%0], %1;\n@!p bra W;}" ::"r"(bar), "r"(parity) : "memory");
}
__device__ __forceinline__ void mbar_wait_cluster(uint32_t bar) {
  asm volatile("{.reg .pred p;\nW: mbarrier.try_wait.parity.acquire.cluster.shared::cta.b64 p, [%0], 0;\n@!p bra W;}" ::"r"(bar) : "memory");
}
__device__ __forceinline__ void mbar_wait_wd(uint32_t bar) {
  asm volatile("{.reg .pred p; .reg .u32 n; mov.u32 n, 0;\n"
               "W: mbarrier.try_wait.parity.shared::cta.b64 p, [%0], 0;\n"
               "@p bra D; add.u32 n, n, 1; setp.gt.u32 p, n, %1; @p trap; bra W;\n"
               "D: }" ::"r"(bar), "n"(SPIN_LIMIT) : "memory");
}
__device__ __forceinline__ uint32_t mbar_test(uint32_t bar) {
  uint32_t ok;
  asm volatile("{.reg .pred p; mbarrier.test_wait.parity.shared::cta.b64 p, [%1], 0; selp.u32 %0, 1, 0, p;}" : "=r"(ok) : "r"(bar) : "memory");
  return ok;
}
__device__ __forceinline__ void mbar_arrive(uint32_t bar, uint32_t n) {
  asm volatile("mbarrier.arrive.shared::cta.b64 _, [%0], %1;" ::"r"(bar), "r"(n) : "memory");
}
__device__ __forceinline__ void mbar_arrive_if0(int z, uint32_t bar, uint32_t n) {
  asm volatile("{.reg .pred p; setp.eq.s32 p, %2, 0; @p mbarrier.arrive.shared::cta.b64 _, [%0], %1;}" ::"r"(bar), "r"(n), "r"(z) : "memory");
}
__device__ __forceinline__ void mbar_arrive_remote_if0(int z, uint32_t bar) {
  asm volatile("{.reg .pred p; setp.eq.s32 p, %1, 0; @p mbarrier.arrive.shared::cluster.b64 _, [%0];}" ::"r"(bar), "r"(z) : "memory");
}
__device__ __forceinline__ void mbar_expect(uint32_t bar, uint32_t bytes) {
  asm volatile("mbarrier.arrive.expect_tx.shared::cta.b64 _, [%0], %1;" ::"r"(bar), "r"(bytes) : "memory");
}
__device__ __forceinline__ void tma2d(uint32_t dst, const CUtensorMap* tm, uint32_t bar, int c0, int c1) {
  asm volatile("cp.async.bulk.tensor.2d.shared::cluster.global.mbarrier::complete_tx::bytes [%0],[%1,{%3,%4}],[%2];"
               ::"r"(dst), "l"(tm), "r"(bar), "r"(c0), "r"(c1) : "memory");
}
__device__ __forceinline__ void tma3d(uint32_t dst, const CUtensorMap* tm, uint32_t bar, int c0, int c1, int c2) {
  asm volatile("cp.async.bulk.tensor.3d.shared::cluster.global.mbarrier::complete_tx::bytes [%0],[%1,{%3,%4,%5}],[%2];"
               ::"r"(dst), "l"(tm), "r"(bar), "r"(c0), "r"(c1), "r"(c2) : "memory");
}
__device__ __forceinline__ void bulk_load(uint32_t dst, const void* src, uint32_t bytes, uint32_t bar) {
  asm volatile("cp.async.bulk.shared::cluster.global.mbarrier::complete_tx::bytes [%0],[%1],%2,[%3];"
               ::"r"(dst), "l"(src), "r"(bytes), "r"(bar) : "memory");
}
__device__ __forceinline__ void l2_prefetch(const void* src, uint32_t bytes) {
  asm volatile("cp.async.bulk.prefetch.L2.global [%0], %1;" ::"l"(src), "r"(bytes) : "memory");
}
__device__ __forceinline__ void fence_async_smem() { asm volatile("fence.proxy.async.shared::cta;" ::: "memory"); }
__device__ __forceinline__ void fence_async_global() { asm volatile("fence.proxy.async.global;" ::: "memory"); }
__device__ __forceinline__ void flag_release(uint32_t* p, uint32_t bits) {
  asm volatile("fence.release.gpu;" ::: "memory");
  asm volatile("red.relaxed.gpu.global.xor.b32 [%0], %1;" ::"l"(p), "r"(bits) : "memory");
}
__device__ __forceinline__ uint32_t flag_read(const uint32_t* p, uint32_t epoch) {
  uint32_t v;
  asm volatile("ld.relaxed.gpu.global.u32 %0, [%1];" : "=r"(v) : "l"(p) : "memory");
  return v ^ ((epoch & 1) - 1);
}
__device__ __forceinline__ void flag_wait(const uint32_t* p, uint32_t want, uint32_t epoch) {
  int it = 0;
  while ((flag_read(p, epoch) & want) != want && ++it < SPIN_LIMIT) {}
  asm volatile("fence.acquire.gpu;" ::: "memory");
}
__device__ __forceinline__ void stg32(const void* p, uint32_t v) { asm volatile("st.global.u32 [%0], %1;" ::"l"(p), "r"(v) : "memory"); }
__device__ __forceinline__ void wg_fence() { asm volatile("wgmma.fence.sync.aligned;" ::: "memory"); }
__device__ __forceinline__ void wg_commit() { asm volatile("wgmma.commit_group.sync.aligned;" ::: "memory"); }
template <int N> __device__ __forceinline__ void wg_wait() { asm volatile("wgmma.wait_group.sync.aligned %0;" ::"n"(N) : "memory"); }
template <int N> __device__ __forceinline__ void reg_fence(float (&a)[N]) {
#pragma unroll
  for (int i = 0; i < N; i++) asm volatile("" : "+f"(a[i])::"memory");
}
template <int ID, int N> __device__ __forceinline__ void named_bar() { asm volatile("bar.sync %0, %1;" ::"n"(ID), "n"(N) : "memory"); }
template <int N> __device__ __forceinline__ void reg_fence(uint32_t (&a)[N]) {
#pragma unroll
  for (int i = 0; i < N; i++) asm volatile("" : "+r"(a[i])::"memory");
}
__device__ __forceinline__ Desc mkdesc(uint32_t dyn, uint32_t off, uint32_t lbo, uint32_t sbo, uint32_t swz) {
  return Desc{dyn, ((off + SMEM_BASE) >> 4) + ((lbo >> 4) << 16), (sbo >> 4) | (swz << 30)};
}
__device__ __forceinline__ uint32_t pack2(float lo, float hi) {
  uint32_t r;
  asm("cvt.rn.bf16x2.f32 %0, %1, %2;" : "=r"(r) : "f"(hi), "f"(lo));
  return r;
}
__device__ __forceinline__ float bf_lo(uint32_t v) { return __uint_as_float(v << 16); }
__device__ __forceinline__ float bf_hi(uint32_t v) { return __uint_as_float(v & 0xffff0000u); }
__device__ __forceinline__ void stsm4(uint32_t addr, uint32_t a, uint32_t b, uint32_t c, uint32_t d) {
  asm volatile("stmatrix.sync.aligned.m8n8.x4.shared.b16 [%0], {%1,%2,%3,%4};" ::"r"(addr), "r"(a), "r"(b), "r"(c), "r"(d) : "memory");
}
__device__ __forceinline__ void ldsm4(uint32_t addr, uint32_t* r) {
  asm volatile("ldmatrix.sync.aligned.m8n8.x4.shared.b16 {%0,%1,%2,%3}, [%4];" : "=r"(r[0]), "=r"(r[1]), "=r"(r[2]), "=r"(r[3]) : "r"(addr) : "memory");
}
__device__ __forceinline__ float2 lds64(uint32_t a) {
  float2 v;
  asm volatile("ld.shared.v2.f32 {%0,%1}, [%2];" : "=f"(v.x), "=f"(v.y) : "r"(a) : "memory");
  return v;
}
__device__ __forceinline__ float4 lds128(uint32_t a) {
  float4 v;
  asm volatile("ld.shared.v4.f32 {%0,%1,%2,%3}, [%4];" : "=f"(v.x), "=f"(v.y), "=f"(v.z), "=f"(v.w) : "r"(a) : "memory");
  return v;
}
__device__ __forceinline__ void sts64(uint32_t a, uint32_t x, uint32_t y) {
  asm volatile("st.shared.v2.u32 [%0], {%1,%2};" ::"r"(a), "r"(x), "r"(y) : "memory");
}
__device__ __forceinline__ void sts128(uint32_t a, uint32_t x, uint32_t y, uint32_t z, uint32_t w) {
  asm volatile("st.shared.v4.u32 [%0], {%1,%2,%3,%4};" ::"r"(a), "r"(x), "r"(y), "r"(z), "r"(w) : "memory");
}
__device__ __forceinline__ float ex2(float x) {
  float r;
  asm("ex2.approx.ftz.f32 %0, %1;" : "=f"(r) : "f"(x));
  return r;
}
__device__ __forceinline__ float rcp(float x) {
  float r;
  asm("rcp.approx.ftz.f32 %0, %1;" : "=f"(r) : "f"(x));
  return r;
}
constexpr float LOG2E = 1.4426950408889634f;
__device__ __forceinline__ float phi(float z, float a, float a2) {
  float r = ex2(z * a2) + 1e-6f;
  asm("{.reg .pred p; setp.gt.f32 p, %1, 0f00000000; @p fma.rn.f32 %0, %1, %2, 0f3F800008;}" : "+f"(r) : "f"(z), "f"(a));
  return r;
}
__device__ __forceinline__ float gelu(float z, const float3& k) {
  float th;
  asm("tanh.approx.f32 %0, %1;" : "=f"(th) : "f"(z * fmaf(z * z, k.y, k.x)));
  const float hy = z * k.z;
  return fmaf(hy, th, hy);
}
__device__ __forceinline__ uint32_t rk1_frag(float m, float d, int c) {
  const uint32_t hi = pack2(m, d), lo = pack2(m - bf_lo(hi), d - bf_hi(hi));
  return __byte_perm(c & 2 ? 0u : hi, c == 3 ? 0u : lo, 0x107632541010ull >> (16 * c) & 0xffff);
}
__device__ __forceinline__ void rk1_store(uint32_t addr, float2 cs, uint32_t bb) {
  const uint32_t hi = pack2(cs.x, cs.y), lo = pack2(cs.x - bf_lo(hi), cs.y - bf_hi(hi));
  sts128(addr, __byte_perm(hi, lo, 0x5410), __byte_perm(hi, bb, 0x5410), bb & 0xffffu, 0);
  sts128(addr + 16, __byte_perm(hi, lo, 0x7632), __byte_perm(hi, bb, 0x7632), bb >> 16, 0);
}
constexpr uint32_t ONES = 0x3F803F80u;
__device__ __forceinline__ void ll_store(uint4* p, float a, float b, uint32_t tag) {
  asm volatile("st.relaxed.gpu.global.v4.u32 [%0], {%1,%2,%3,%2};" ::"l"(p), "r"(__float_as_uint(a)), "r"(tag), "r"(__float_as_uint(b)) : "memory");
}
__device__ __forceinline__ uint4 ll_load(const void* p) {
  uint4 v;
  asm volatile("ld.relaxed.gpu.global.v4.u32 {%0,%1,%2,%3}, [%4];" : "=r"(v.x), "=r"(v.y), "=r"(v.z), "=r"(v.w) : "l"(p) : "memory");
  return v;
}
template <int N>
__device__ __forceinline__ void ll_wait(uint4 (&v)[N], const uint4* p, int stride, uint32_t tag) {
  uint32_t bad;
  int it = 0;
  do {
    bad = 0;
#pragma unroll
    for (int m = 0; m < N; m++) v[m] = ll_load(p + m * stride);
#pragma unroll
    for (int m = 0; m < N; m++) bad |= (v[m].y ^ tag) | (v[m].w ^ tag);
  } while (__any_sync(0xffffffffu, bad) && ++it < SPIN_LIMIT);
}
__device__ __forceinline__ void ll_wait2(uint4 (&v)[8], const uint4* p, uint32_t tag) {
  uint32_t bad;
  int it = 0;
  do {
    bad = 0;
#pragma unroll
    for (int m = 0; m < 8; m++) v[m] = ll_load(p + (m >> 1) * 1728 + (m & 1));
#pragma unroll
    for (int m = 0; m < 8; m++) bad |= (v[m].y ^ tag) | (v[m].w ^ tag);
  } while (__any_sync(0xffffffffu, bad) && ++it < SPIN_LIMIT);
}
__device__ __forceinline__ float2 ll_sum4(const uint4* p, uint32_t tag) {
  uint4 v[4];
  ll_wait(v, p, 1728, tag);
  return make_float2((__uint_as_float(v[0].x) + __uint_as_float(v[1].x)) + (__uint_as_float(v[2].x) + __uint_as_float(v[3].x)),
                     (__uint_as_float(v[0].z) + __uint_as_float(v[1].z)) + (__uint_as_float(v[2].z) + __uint_as_float(v[3].z)));
}
__device__ __noinline__ float2 colsum(const __nv_bfloat16* wm, int ld, int h0, int h1) {
  const int lane = threadIdx.x & 31, r4 = lane >> 3;
  float d[8];
#pragma unroll
  for (int e = 0; e < 8; e++) d[e] = 0.f;
#pragma unroll 1
  for (int h = h0; h < h1; h++) {
    const __nv_bfloat16* wp = wm + (4 * h + r4) * ld + 8 * (lane & 7);
    uint4 v[14];
#pragma unroll
    for (int m = 0; m < 14; m++) {
      v[m] = make_uint4(0, 0, 0, 0);
      if (m < 13 || h == 0)
        asm volatile("ld.global.nc.v4.u32 {%0,%1,%2,%3}, [%4];" : "=r"(v[m].x), "=r"(v[m].y), "=r"(v[m].z), "=r"(v[m].w) : "l"(wp));
      wp += 12 * ld;
    }
#pragma unroll
    for (int m = 0; m < 14; m++) {
      d[0] += bf_lo(v[m].x); d[1] += bf_hi(v[m].x); d[2] += bf_lo(v[m].y); d[3] += bf_hi(v[m].y);
      d[4] += bf_lo(v[m].z); d[5] += bf_hi(v[m].z); d[6] += bf_lo(v[m].w); d[7] += bf_hi(v[m].w);
    }
  }
#pragma unroll 1
  for (int o = 8; o < 32; o <<= 1) {
#pragma unroll
    for (int e = 0; e < 8; e++) d[e] += __shfl_xor_sync(0xffffffffu, d[e], o);
  }
  if (r4 & 2) { d[0] = d[4]; d[1] = d[5]; d[2] = d[6]; d[3] = d[7]; }
  return r4 & 1 ? make_float2(d[2], d[3]) : make_float2(d[0], d[1]);
}
template <bool PHI>
__device__ __forceinline__ void ln_pair(const float* z, const float (&a)[2], const float (&a2)[2], uint32_t* o) {
#pragma unroll
  for (int e = 0; e < 4; e++) {
    const int hh = e & 1;
    o[e] = PHI ? pack2(phi(z[2 * e], a[hh], a2[hh]), phi(z[2 * e + 1], a[hh], a2[hh])) : pack2(z[2 * e] * a[hh], z[2 * e + 1] * a[hh]);
  }
}

__global__ void __cluster_dims__(2, 1, 1) __launch_bounds__(384, 1)
fused_block_kernel(const __grid_constant__ Maps maps, const __nv_bfloat16* __restrict__ x, const __nv_bfloat16* __restrict__ wqkv,
                   const __nv_bfloat16* __restrict__ wo, const __nv_bfloat16* __restrict__ w1,
                   const __nv_bfloat16* __restrict__ b1, const __nv_bfloat16* __restrict__ w2,
                   const __nv_bfloat16* __restrict__ b2, __nv_bfloat16* __restrict__ out) {
  extern __shared__ __align__(1024) uint8_t smem_raw[];
  const uint32_t sb = (uint32_t)__cvta_generic_to_shared(smem_raw);
  const uint32_t bars = sb + OFF_BAR;
  const int warp = __shfl_sync(0xffffffffu, threadIdx.x >> 5, 0);
  const int lane = threadIdx.x & 31;
  if (warp < 3 && elect_one()) asm volatile("prefetch.tensormap [%0];" ::"l"(&maps.m[warp]) : "memory");

  const int cl = blockIdx.x >> 1, q = blockIdx.x & 1;
  const int u7 = ((cl - 36) * 37) >> 8;
  const int oct = cl < 4 ? 0 : cl < 36 ? 1 + 2 * ((cl - 4) & 7) : 2 + 2 * (cl - 36 - 7 * u7);
  const int u4 = cl < 4 ? cl : cl < 36 ? (cl - 4) >> 3 : u7;
  const int i = 2 * (oct & 7) + (u4 >> 1), p = 2 * (oct >> 3) + (u4 & 1);
  const int j = 2 * p + q;
  auto col_f = [](int jj) { return 160 * (jj >> 1) + 16 * (jj & 2) + 64 * (jj & 1); };
  auto col_r = [](int jj) { return 160 * (jj >> 1) + 128 - 64 * (jj & 2) + 16 * (jj & 1); };
  const int cF = col_f(j), cR = col_r(j), role = q ^ (p & 1);

  auto load_kv = [&](int s) {
    const uint32_t dst = sb + (s < 16 ? OFF_RING + (s % 5) * 12288 : (s - 16) * 12288), bar = bars + 8 * (s < 16 ? RF + s % 5 : FE + s - 16);
    tma3d(dst, &maps.m[M_KVF], bar, cF, 32 * s, 1);
    tma2d(dst + 8192, &maps.m[M_KVH], bar, 640 + 640 * role + cR - 16 * q, 32 * s);
    mbar_expect(bar, 10240);
  };
  auto load_x = [&](int c, int b, int slot) {
    tma2d(sb + slot * 16384, &maps.m[M_X], bars + 8 * (FX + b), 64 * c, 128 * i);
    mbar_expect(bars + 8 * (FX + b), 16384);
  };
  auto bar_init = [&](int n, uint32_t cnt) { asm volatile("mbarrier.init.shared::cta.b64 [%0], %1;" ::"r"(bars + 8 * n), "r"(cnt) : "memory"); };

  TC(tc0);
  if (elect_one()) {
    if (warp == 8) {
      bar_init(RF, 1);
      bar_init(RF + 1, 1);
      bar_init(FX, 1);
      load_x(0, 0, 0);
      load_kv(0);
      load_kv(1);
    } else if (warp < 8) {
#pragma unroll
      for (int n = 0; n < 5; n++)
        if (warp > (n == 0 ? 1 : n == 1 ? 0 : -1)) bar_init(5 * warp + n, warp < 5 ? 1 : 8);
      asm volatile("fence.mbarrier_init.release.cluster;" ::: "memory");
    }
  }
  TC(tc1);
  __syncthreads();
  asm volatile("barrier.cluster.arrive.relaxed.aligned;" ::: "memory");

  if (warp >= 8) {
    TC(tc2);
    if (warp == 8) {
      if (elect_one()) {
        load_x(1, 1, 1);
        load_kv(2);
        load_kv(3);
        load_x(2, 2, 2);
        load_kv(4);
        load_x(3, 3, 3);
      }
      __syncwarp();
    }
    TC(tc3);
    asm volatile("setmaxnreg.dec.sync.aligned.u32 88;");
    if (warp == 8) {
      asm volatile("barrier.cluster.wait.aligned;" ::: "memory");
      TL(40);
      TS(41, tc0); TS(42, tc1); TS(43, tc2); TS(19, tc3);
      if (elect_one()) {
        auto prefetch_piece = [&](const __nv_bfloat16* wm, uint32_t total, uint32_t off, uint32_t bytes) {
          l2_prefetch(reinterpret_cast<const uint8_t*>(wm) + blockIdx.x * total + off, bytes);
        };
#pragma unroll
        for (int s = 5; s < 16; s++) {
          mbar_wait(bars + 8 * (RE + s % 5), (s / 5 - 1) & 1);
          load_kv(s);
          if (s < 11) load_x(s - 1, s - 1, s - 1);
          if (s == 12) mbar_wait(bars + 8 * XF);
          if (s >= 12) load_kv(s + 4);
          if (s < 13) asm volatile("prefetch.tensormap [%0];" ::"l"(&maps.m[s - 2]) : "memory");
          if (s >= 11) prefetch_piece(wo, 6400, (s - 11) * 1280, 1280);
          TL1(96 + s);
        }
#pragma unroll
        for (int t = 0; t < 10; t++) {
          const int slot = (t + 1) % 5, k0 = 64 * (t < 7 ? t + 3 : t - 7);
          const uint32_t dst = sb + OFF_RING + slot * 12288, bar = bars + 8 * (RF + slot);
          mbar_wait(bars + 8 * (RE + slot), ((t + 11) / 5) & 1);
          tma3d(dst, &maps.m[M_Q2], bar, 0, k0, 5 * p + 3 * q);
          tma2d(dst + 8192, &maps.m[M_QR], bar, 80 * j + 64 - 64 * q, k0);
          mbar_expect(bar, 10240);
          if (t >= 6 && t < 9) load_x(t - 6, t + 4, t - 2);
          if (t < 8) prefetch_piece(w1, 15360, t * 1920, 1920);
          TL1(116 + t);
        }
#pragma unroll 1
        for (int n = 0; n < 32; n += 4) {
          const int t = (0x41765320u >> n) & 7, k0 = 80 * (t == 0 ? j : t - (t <= j));
          const uint32_t dst = sb + 10 * PAGE + (t < 2 ? t ^ 1 : t) * 15360, bar = bars + 8 * (FWO + t);
          mbar_wait(bars + 8 * (RE + ((0x00432221u >> n) & 15)), n >= 24);
          if (n >= 8) mbar_wait(bars + 8 * (FWO + ((0x41765320u >> (n - 8)) & 7)));
          tma3d(dst, &maps.m[M_WO2], bar, 0, k0, cF >> 5);
          tma2d(dst + 10240, &maps.m[M_WOR], bar, cR, k0);
          mbar_expect(bar, 12800);
          TL1(128 + n / 4);
        }
#pragma unroll 1
        for (int t = 0; t < 8; t++) {
          const uint32_t wb = bars + 8 * (t == 0 ? FWO + 1 : t < 5 ? DW + 2 * t - 1 : DF + t - 5);
          const int jj = t == 0 ? j : t - (t <= j);
          const uint32_t dst = sb + (7 + 3 * (t < 5 ? t : t - 5)) * PAGE, bar = bars + 8 * (FW1 + t);
          mbar_wait(wb);
          if (t) {
            mbar_wait(wb + 64);
            mbar_wait(bars + 8 * (t == 1 ? AH : t < 4 ? FW1 + t - 1 : t == 4 ? AH + 2 : DF + t - 4));
          }
          tma3d(dst, &maps.m[M_W1], bar, 0, col_f(jj), 3 * j);
          tma3d(dst + 24576, &maps.m[M_W1R], bar, 0, col_r(jj), 3 * j);
          mbar_expect(bar, 30720);
          if (t >= 3) prefetch_piece(w2, 15360, (t - 3) * 3072, 3072);
          TL1(136 + t);
        }
#pragma unroll 1
        for (int t = 0; t < 12; t++) {
          const int t6 = t < 6 ? t : t - 6;
          const uint32_t wb = bars + 8 * (t < 6 ? DF + ((0x776544 >> (4 * t)) & 7) : DG + t6);
          const int uu = (0xA95024 >> (2 * t)) & 3, n = (0x924900 >> (2 * t)) & 3;
          const int k0 = 192 * (t < 3 ? j : 2 * (n + (n >= p)) + q) + 64 * uu;
          const uint32_t dst = sb + OFF_W2 + ((0x321045 >> (4 * t6)) & 7) * 24576, bar = bars + 8 * (FW2 + t);
          mbar_wait(wb);
          mbar_wait(wb + (t < 6 ? 64 : 96));
          tma2d(dst, &maps.m[M_W2F], bar, cF, k0);
          tma2d(dst + 8192, &maps.m[M_W2F], bar, cF + 64 - 128 * q, k0);
          tma2d(dst + 16384, &maps.m[M_W2H], bar, cR - 16 * q, k0);
          mbar_expect(bar, 20480);
          TL1(144 + t);
        }
      }
    } else {
      const int unit = i * 8 + j, hw = warp - 9, part = unit & 3, cg = unit >> 2;
      uint32_t epoch;
      asm volatile("ld.relaxed.gpu.global.u32 %0, [%1];" : "=r"(epoch) : "l"(&g_epoch) : "memory");
      epoch += 1;
      if (hw == 0 && lane < 28 && i < 15) *reinterpret_cast<float4*>(g_kv + j * 1696 + i * 112 + lane * 4) = make_float4(0.f, 0.f, 0.f, 0.f);
      if (hw == 0) TL(248);
      if (part >= 2) mbar_wait_wd(bars + 8 * (FX + 2 * part - 4));
      const int ht = hw * 32 + lane, cpair = part * 1728 + 32 * cg + 4 * (lane & 7) + (lane >> 3);
      if (cg < 30) {
        float2 csum = colsum(wqkv + part * 160 * 1920 + 64 * cg, 1920, hw, hw + 1);
        const uint32_t red = sb + OFF_SCR + lane * 8;
#pragma unroll 1
        for (int h = 0; h < 2; h++) {
          if (hw == h) sts64(red, __float_as_uint(csum.x), __float_as_uint(csum.y));
          named_bar<2, 96>();
          if (hw == h + 1) {
            const float2 a = lds64(red);
            csum.x += a.x;
            csum.y += a.y;
          }
        }
        if (hw == 2) ll_store(g_cs + cpair, csum.x, csum.y, epoch);
      }
      asm volatile("barrier.cluster.wait.aligned;" ::: "memory");
      if (elect_one()) {
#pragma unroll 1
        for (int n = FWO + 50 * hw; n < FWO + 50 * hw + 50; n += 10) {
#pragma unroll
          for (int e = 0; e < 10; e++) bar_init(n + e, n < AO ? 1 : 8);
        }
        mbar_expect(bars + 8 * (RX + hw), hw == 2 ? 8192 : 10240);
        if (hw == 0) flag_release(g_flag + (96 + j) * 32, 1u << i);
      }
      __syncwarp();
      if (hw == 2) {
        TL(8);
#pragma unroll 1
        for (int n = lane; n < 40; n += 32) {
          const uint32_t b = *reinterpret_cast<const uint32_t*>(b2 + (n < 32 ? cF + 2 * n : cR + 2 * n - 64));
          sts64(sb + OFF_B2 + n * 8, b << 16, b & 0xffff0000u);
        }
        __syncwarp();
        mbar_wait_wd(bars + 8 * ST1);
        uint4 v[4];
        ll_wait(v, g_ln1 + 128 * i + lane, 32, epoch);
#pragma unroll
        for (int m = 0; m < 4; m++) {
          const float nm = __uint_as_float(v[m].x) * (-1.f / 640.f);
          const float rstd = rsqrtf(fmaxf(fmaf(-nm, nm, __uint_as_float(v[m].z) * (1.f / 640.f)), 0.f) + 1e-5f);
          sts64(sb + OFF_LN1 + (lane + 32 * m) * 8, __float_as_uint(rstd), __float_as_uint(nm));
        }
      } else {
        const int n = 4 * min(ht, 59);
        int col;
        if (n < 160) col = n + (n < 64 ? 640 + cF : n < 128 ? 1216 + cF : 512 + 640 * role + cR - 16 * q);
        else col = 80 * j + n - 160 + (q ? (n < 224 ? 16 : -64) : 0);
        mbar_wait(bars + 8 * CG);
        uint4 v[8];
        ll_wait2(v, g_cs + (col >> 1), epoch);
#pragma unroll
        for (int e = 0; e < 2; e++)
          rk1_store(sb + OFF_RK1 + n * 16 + 32 * e,
                    make_float2((__uint_as_float(v[e].x) + __uint_as_float(v[2 + e].x)) + (__uint_as_float(v[4 + e].x) + __uint_as_float(v[6 + e].x)),
                                (__uint_as_float(v[e].z) + __uint_as_float(v[2 + e].z)) + (__uint_as_float(v[4 + e].z) + __uint_as_float(v[6 + e].z))), 0);
        fence_async_smem();
      }
      __syncwarp();
      mbar_arrive_if0(lane, bars + 8 * SIDE, hw == 2 ? 2 : 3);
      if (hw != 1) TL(11 - hw / 2);
      {
        if (hw == 2) {
          flag_wait(g_flag + (96 + j) * 32, 0xffffu, epoch);
          fence_async_global();
          mbar_wait_wd(bars + 8 * RKV);
          if (elect_one()) {
            asm volatile("cp.reduce.async.bulk.global.shared::cta.bulk_group.add.f32 [%0], [%1], 6720;" ::"l"(g_kv + j * 1696), "r"(sb + OFF_KVP) : "memory");
            asm volatile("cp.async.bulk.commit_group;" ::: "memory");
            asm volatile("cp.async.bulk.wait_group 0;" ::: "memory");
            flag_release(g_flag + (104 + j) * 32, 1u << i);
          }
          TL(5);
        } else {
          mbar_wait_wd(bars + 8 * ZK);
#pragma unroll 1
          for (int m = 0; m < 15; m += 3) {
#pragma unroll
            for (int e = 0; e < 3; e++) sts128(sb + OFF_KVB + ((m + e) * 64 + ht) * 16, 0, 0, 0, 0);
          }
        }
        const int d0 = ht < 80 ? (ht * 205) >> 10 : ht - 80, pt = ht - 5 * d0;
        uint32_t da[5];
#pragma unroll
        for (int m = 0; m < 5; m++) {
          const int d = d0 + 16 * m, head = (d * 205) >> 12, n = 20 * head + 4 * pt;
          da[m] = sb + OFF_KVB + d * 16 + (ht < 80 ? (n >> 3) * 1280 + (n & 7) * 2 : (10 + (head >> 1)) * 1280 + (head & 1));
        }
        reg_fence(da);
        named_bar<2, 96>();
        flag_wait(g_flag + (104 + j) * 32, 0xffffu, epoch);
        if (hw == 0) TL(6);
        if (ht < 80) {
          uint4 v[5];
#pragma unroll
          for (int m = 0; m < 5; m++) v[m] = ll_load(g_kv + j * 1696 + (ht + 80 * m) * 4);
#pragma unroll
          for (int m = 0; m < 5; m++)
            sts64(da[m], pack2(__uint_as_float(v[m].x), __uint_as_float(v[m].y)), pack2(__uint_as_float(v[m].z), __uint_as_float(v[m].w)));
        } else {
          float z[5];
#pragma unroll
          for (int m = 0; m < 5; m++) asm volatile("ld.relaxed.gpu.global.f32 %0, [%1];" : "=f"(z[m]) : "l"(g_kv + j * 1696 + 1520 + ht + 16 * m) : "memory");
#pragma unroll
          for (int m = 0; m < 5; m++) {
            const uint32_t zz = pack2(z[m], 0.f) << (16 * (da[m] & 1));
            sts128(da[m] & ~1u, zz, zz, zz, zz);
          }
        }
        fence_async_smem();
        __syncwarp();
        mbar_arrive_if0(lane, bars + 8 * KVB, hw == 2 ? 2 : 3);
        if (hw == 0) TL(7);
      }

      if (hw == 2) {
        if (cg < 24) {
          const float2 d = colsum(w1 + part * 160 * 1536 + 64 * cg, 1536, 0, 3);
          ll_store(g_cs + 960 + cpair, d.x, d.y, epoch);
        }
        mbar_wait_wd(bars + 8 * (DW + 15));
#pragma unroll 1
        for (int n = lane; n < 96; n += 32)
          rk1_store(sb + OFF_RK1 + n * 32, ll_sum4(g_cs + 960 + 96 * j + n, epoch), *reinterpret_cast<const uint32_t*>(b1 + 192 * j + 2 * n));
        fence_async_smem();
        __syncwarp();
        mbar_arrive_if0(lane, bars + 8 * SIDE2, 8);
        TL(18);
        const uint32_t eb = bars + 8 * (AF + 12 * ((lane >> 1) & 1) + 1 + (lane & 1));
        uint32_t pm = 15;
        do {
          mbar_wait_wd(__shfl_sync(0xffffffffu, eb, __ffs(pm) - 1));
          const uint32_t ok = mbar_test(eb) & (pm >> lane);
          if (ok) flag_release(g_flag + (64 + 2 * i + (lane >> 1)) * 32, 0x100u << (8 * (lane & 1) + j));
          pm &= ~__ballot_sync(0xffffffffu, ok);
        } while (pm);
        mbar_wait_wd(bars + 8 * END);
        if (blockIdx.x == 0 && lane == 0) g_epoch = epoch;
      } else {
        const int s = hw;
#pragma unroll 1
        for (int ph = 0; ph < 3; ph++) {
          const uint32_t ab = bars + 8 * (ph < 2 ? AO + 16 * ph + 8 * s : AF + 12 * s);
          const uint32_t bytes = ph < 2 ? 10240 : 8192;
          uint8_t* gb = g_act + (ph * 32 + 2 * i + s) * 8 * 24576;
          uint32_t* fl = g_flag + (ph * 32 + 2 * i + s) * 32;
          const int r = min(lane, 8);
          int cc = r + (r >= j), bit = cc, slot, wb, off = 0;
          if (ph == 0) {
            slot = r;
            wb = s ? DW + r + 1 : AO + 8;
          } else if (ph == 1) {
            slot = (0x0924u >> (2 * r)) & 3;
            wb = r < 3 ? DW + (s ? 15 : 9 + r) : DF + 8 * s + r - 2;
          } else {
            const int uu = (r * 11) >> 5, n = r - 3 * uu;
            cc = 2 * (n + (n >= p)) + q;
            bit = cc + 8 * uu;
            off = uu * 8192;
            slot = r & 3;
            wb = r < 4 ? DF + 8 * s + 7 : DG + 12 * s + r - 1;
          }
          const uint32_t fb = ab + 8 * r + (ph < 2 ? 8 : 24), wbar = bars + 8 * wb;
          const uint32_t dst = sb + (ph ? s * OFF_R1 : 0) + slot * bytes;
          const uint8_t* src = gb + cc * 24576 + off;
          uint32_t pm = ph < 2 ? 0x7fu : 0x1ffu, seen = 0;
          if (pm >> lane & 1) {
            mbar_expect(fb, bytes);
            mbar_arrive(fb, 7);
          }
          __syncwarp();
          mbar_wait(ab);
          if (elect_one()) flag_release(fl, 1u << j);
          __syncwarp();
          TL(44 + 2 * ph + s);
          do {
            const int next = __ffs(pm) - 1;
            if (!(seen >> next & 1)) {
              do seen = __ballot_sync(0xffffffffu, flag_read(fl, epoch) >> bit & 1);
              while (!(seen >> next & 1));
              asm volatile("fence.acquire.gpu;" ::: "memory");
              fence_async_global();
            }
            if (next == 0) TL(52 + 2 * ph + s);
            mbar_wait(__shfl_sync(0xffffffffu, wbar, next));
            const uint32_t ok = mbar_test(wbar) & ((pm & seen) >> lane);
            if (ok) bulk_load(dst, src, bytes, fb);
            pm &= ~__ballot_sync(0xffffffffu, ok);
          } while (pm);
        }
      }
    }
  } else {
    TC(tc4);
    uint32_t epoch;
    asm volatile("ld.relaxed.gpu.global.u32 %0, [%1];" : "=r"(epoch) : "l"(&g_epoch) : "memory");
    epoch += 1;
    const int s = warp >> 2, w = warp & 3, tid = threadIdx.x & 127, c = lane & 3, g = lane >> 2;
    uint32_t sb_peer;
    asm volatile("mapa.shared::cluster.u32 %0, %1, %2;" : "=r"(sb_peer) : "r"(sb), "r"(q ^ 1));
    const int row0 = 128 * i + 64 * s + 16 * w;
    const uint32_t bs8 = bars + 64 * s, bs12 = bars + 96 * s;
    uint32_t pq[20], hp[20];
    {
      float acc[80];
      const Desc dx = mkdesc(s * 512, 0, 16, 1024, 1);
      const int srow = 16 * j + 2 * warp + (lane >> 4);
      float sm = 0.f, sq = 0.f;
      float4 u;
      auto load_res = [&]() {
        const uint32_t xa = sb + (64 * s + 16 * w + (lane & 15)) * 128;
#pragma unroll
        for (int ks = 0; ks < 5; ks++) {
          const int col = ks < 4 ? cF + 16 * ks : cR;
          ldsm4(xa + (col >> 6) * 16384 + (((((col & 63) >> 3) + (lane >> 4)) ^ (lane & 7)) << 4), hp + 4 * ks);
        }
      };
#pragma unroll
      for (int st = 0; st < 20; st++) {
        if ((st & 1) == 0 && st <= 4) mbar_wait(bars + 8 * (FX + (st >> 1)));
        mbar_wait(bars + 8 * (st < 16 ? RF + st % 5 : FE + st - 16), st < 16 ? (st / 5) & 1 : 0);
        const Desc da = dx + (st >> 1) * 1024 + (st & 1) * 4;
        const Desc db = mkdesc(0, st < 16 ? OFF_RING + (st % 5) * 12288 : (st - 16) * 12288, 4096, 1024, 1);
        wg_fence();
        wgmma_ss<160, 0, 1>(acc, da, db, st != 0);
        wgmma_ss<160, 0, 1>(acc, da + 2, db + 128, 1);
        wg_commit();
        TL0(64 + st);
        if (st == 0) { TL0(0); TS(38, tc4); TS(62, (uint32_t)tl_gt); }
        if (st == 15) asm volatile("barrier.cluster.wait.aligned;" ::: "memory");
        if (st == 1) asm volatile("setmaxnreg.inc.sync.aligned.u32 208;");
        if (st >= 3 && st <= 11 && (st & 1)) {
          const float uu[4] = {u.x, u.y, u.z, u.w};
#pragma unroll
          for (int e = 0; e < 4; e++) {
            const float a = bf_lo(__float_as_uint(uu[e])), b = bf_hi(__float_as_uint(uu[e]));
            sm += a + b;
            sq = fmaf(a, a, fmaf(b, b, sq));
          }
        }
        if (st >= 2 && st <= 10 && (st & 1) == 0) {
          if (st > 4) mbar_wait(bars + 8 * (FX + st - 2));
          if (st > 2) mbar_wait(bars + 8 * (FX + st - 1));
          u = lds128(sb + (st - 2 + ((lane >> 3) & 1)) * 16384 + srow * 128 + (lane & 7) * 16);
        }
        if (st == 11 || st == 12) {
#pragma unroll
          for (int o = st == 11 ? 1 : 4; o < (st == 11 ? 4 : 16); o <<= 1) {
            sm += __shfl_xor_sync(0xffffffffu, sm, o);
            sq += __shfl_xor_sync(0xffffffffu, sq, o);
          }
        }
        if (st == 12) {
          if ((lane & 15) == 0) ll_store(g_ln1 + 128 * i + srow, sm, sq, epoch);
          TL0(39);
        }
        if (st == 13) mbar_arrive_if0(lane, bars + 8 * CG, 1);
        if (st == 14) mbar_arrive_if0(lane, bars + 8 * ST1, 1);
        if (st == 7 && p < 2) load_res();
        if (st == 8) mbar_arrive_if0(lane, bars + 8 * XF, 1);
        if (st == 16 && p >= 2) load_res();
        if (st > 0) {
          wg_wait<1>();
          if (st <= 16) mbar_arrive_if0(lane, bars + 8 * (RE + (st - 1) % 5), 1);
        }
      }
      TL0(12);
      float accq[40];
      auto q_step = [&](int t) {
        if (t >= 7) mbar_wait(bars + 8 * (FX + 3 + t));
        mbar_wait(bars + 8 * (RF + (t + 1) % 5), ((t + 16) / 5) & 1);
        const Desc da = dx + (t < 7 ? t + 3 : t - 3) * 1024, db = mkdesc(0, OFF_RING + ((t + 1) % 5) * 12288, 4096, 512, 2);
        wg_fence();
#pragma unroll
        for (int ks = 0; ks < 4; ks++) wgmma_ss<80, 0, 1>(accq, da + 2 * ks, db + 64 * ks, 1);
        wg_commit();
        TL0(84 + t);
      };
      mbar_wait(bars + 8 * SIDE);
      float a1[2], a2[2];
      uint32_t rk[2];
#pragma unroll
      for (int r = 0; r < 2; r++) {
        const float2 st = lds64(sb + OFF_LN1 + (64 * s + 16 * w + g + 8 * r) * 8);
        a1[r] = st.x;
        a2[r] = st.x * LOG2E;
        rk[r] = rk1_frag(st.y, 0.f, c);
      }
      wg_fence();
      wgmma_rs<160, 0>(acc, rk[0], rk[1], 0, 0, mkdesc(0, OFF_RK1, 0, 128, 0), 1);
      wg_commit();
      wgmma_rs<80, 0>(accq, rk[0], rk[1], 0, 0, mkdesc(0, OFF_RK1 + 2560, 0, 128, 0), 0);
      q_step(0);
      const int hi = lane >> 4;
      const uint32_t rowoff = sb + (64 * s + 16 * w + (lane & 15)) * 16;
      const uint32_t remoff = sb_peer + (64 * s + 16 * w) * 16 + lane * 4;
      auto put_remote = [&](const uint32_t* r, uint32_t a) {
#pragma unroll
        for (int e = 0; e < 4; e++)
          asm volatile("st.async.shared::cluster.mbarrier::complete_tx::bytes.b32 [%0], %1, [%2];"
                       ::"r"(a + (e >> 1) * 2048 + (e & 1) * 128), "r"(r[e]), "r"(sb_peer + OFF_BAR + 8 * RXK) : "memory");
      };
      const int mF = 2 * (p & 1) - q, g0 = 2 * mF + hi;
      const uint32_t ka = rowoff + g0 * 2048;
      wg_wait<1>();
      reg_fence(acc);
      mbar_arrive_if0(lane, bars + 8 * KD, 1);
      mbar_arrive_remote_if0(lane, sb_peer + OFF_BAR + 8 * PX);
      TL0(1);
      uint32_t r[4], r2[4];
      if (role == 0) {
        ln_pair<true>(acc + 64, a1, a2, r);
        ln_pair<true>(acc + 72, a1, a2, r2);
        mbar_wait_cluster(bars + 8 * PX);
        put_remote(r, remoff + (q ? 0 : 6 * 2048));
        put_remote(r2, remoff + (q ? 2 * 2048 : 8 * 2048));
      } else {
        ln_pair<false>(acc + 64, a1, a2, r);
        ln_pair<false>(acc + 72, a1, a2, r2);
        const uint32_t a = rowoff + (hi + (q ? 17 : 10)) * 2048;
        mbar_wait(bars + 8 * KD);
        stsm4(a, r[0], r[1], r[2], r[3]);
        stsm4(a + 4096, r2[0], r2[1], r2[2], r2[3]);
      }
      q_step(1);
#pragma unroll
      for (int n = 0; n < 4; n++) {
        const int P = n == 0 ? 0 : n == 1 ? 3 : n - 1;
        ln_pair<true>(acc + 8 * P, a1, a2, r);
        ln_pair<false>(acc + 32 + 8 * P, a1, a2, r2);
        if (n == 0) mbar_wait(bars + 8 * KD);
        if (n < 2 && mF == (n ? 2 : -1)) {
          mbar_wait_cluster(bars + 8 * PX);
          put_remote(r, remoff + (n ? 0 : 8 * 2048));
          put_remote(r2, remoff + (n ? 10 * 2048 : 19 * 2048));
        } else {
          stsm4(ka + P * 4096, r[0], r[1], r[2], r[3]);
          stsm4(ka + P * 4096 + (g0 + 2 * P > 4 ? 11 * 2048 : 10 * 2048), r2[0], r2[1], r2[2], r2[3]);
        }
        if (n == 0) {
          wg_wait<1>();
          mbar_arrive_if0(lane, bars + 8 * (RE + 1), 1);
          mbar_arrive_if0(lane, bars + 8 * ZK, 1);
        }
        if (n == 1) q_step(2);
        if (n == 2) {
          wg_wait<1>();
          mbar_arrive_if0(lane, bars + 8 * (RE + 2), 1);
        }
      }
      sts128(rowoff + 15 * 2048, ONES, ONES, ONES, ONES);
      TL0(2);
      mbar_wait_cluster(bars + 8 * RXK);
      fence_async_smem();
      named_bar<1, 256>();
      TL0(3);
      float kv[24];
      {
        const Desc da = mkdesc(s * 640, 0, 128, 2048, 0), db = da + 1280;
        wg_fence();
#pragma unroll
        for (int kk = 0; kk < 8; kk++) wgmma_ss<48, 1, 1>(kv, da + 16 * kk, db + 16 * kk, kk != 0);
        wg_commit();
      }
      wg_wait<1>();
      mbar_arrive_if0(lane, bars + 8 * (RE + 3), 1);
      q_step(3);
      {
        wg_wait<1>();
        reg_fence(kv);
        TL0(4);
#pragma unroll
        for (int hh = 0; hh < 2; hh++) {
          const int r = 16 * w + g + 8 * hh, eb = c - 4 * s - (r < 20 ? 0 : r < 40 ? 10 : 99);
          const uint32_t a = sb + OFF_KVP + (40 * s + r) * 80 + 8 * eb;
#pragma unroll
          for (int tt = 0; tt < 6; tt++)
            asm volatile("{.reg .pred p; setp.lt.u32 p, %3, 10; @p st.shared.v2.f32 [%0], {%1, %2};}"
                         ::"r"(a + 32 * tt), "f"(kv[4 * tt + 2 * hh]), "f"(kv[4 * tt + 2 * hh + 1]), "r"(eb + 4 * tt) : "memory");
          asm volatile("{.reg .pred p; setp.lt.u32 p, %2, 40; @p st.shared.f32 [%0], %1;}"
                       ::"r"(sb + OFF_KVP + 6400 + (40 * s + r) * 4), "f"(s ? kv[2 * hh] : kv[20 + 2 * hh]), "r"(r) : "memory");
        }
        fence_async_smem();
        __syncwarp();
      }
      mbar_arrive_if0(lane, bars + 8 * RKV, 1);
      TL0(9);
#pragma unroll
      for (int t = 4; t < 10; t++) {
        q_step(t);
        wg_wait<1>();
        mbar_arrive_if0(lane, bars + 8 * (RE + t % 5), 1);
      }
      wg_wait<0>();
      reg_fence(accq);
      mbar_arrive_if0(lane, bars + 8 * RE, 1);
      TL0(13);
#pragma unroll
      for (int P = 0; P < 5; P++) ln_pair<true>(accq + 8 * P, a1, a2, pq + 4 * P);
      reg_fence(pq);
      TL0(14);
    }
    const uint32_t rs = sb + s * OFF_R1;
    const uint8_t* gout = g_act + ((2 * i + s) * 8 + j) * 24576 + 256 * w + 4 * lane;
    const Desc drs = mkdesc(s * (OFF_R1 / 16), 0, 1024, 128, 0);
    float accg[80];
    {
      {
        float o[48];
        wg_fence();
        mbar_wait(bars + 8 * (s ? OM : KVB));
        TL0(15);
#pragma unroll
        for (int ks = 0; ks < 5; ks++)
          wgmma_rs<96, 1>(o, pq[4 * ks], pq[4 * ks + 1], pq[4 * ks + 2], pq[4 * ks + 3], mkdesc(ks < 4 ? 16 * q : -64 * q, OFF_KVB + 256 * ks, 128, 1280, 0), ks != 0);
        wg_commit();
        mbar_arrive_if0(lane | s, bars + 8 * OM, 2);
        wg_wait<0>();
        reg_fence(o);
        float inv[2][4];
#pragma unroll
        for (int hh = 0; hh < 2; hh++)
#pragma unroll
          for (int h = 0; h < 4; h++) inv[hh][h] = rcp(o[40 + 4 * (h >> 1) + 2 * hh + (h & 1)] + 1e-6f);
        if (s) mbar_wait(bars + 8 * AO);
#pragma unroll
        for (int t = 0; t < 10; t++) {
#pragma unroll
          for (int hh = 0; hh < 2; hh++) {
            const float f = t == 2 ? (c < 2 ? inv[hh][0] : inv[hh][1]) : t == 7 ? (c < 2 ? inv[hh][2] : inv[hh][3]) : inv[hh][(8 * t) / 20];
            pq[2 * t + hh] = pack2(o[4 * t + 2 * hh] * f, o[4 * t + 2 * hh + 1] * f);
            stg32(gout + t * 1024 + hh * 128, pq[2 * t + hh]);
          }
        }
        __syncwarp();
        mbar_arrive_if0(lane, bs8 + 8 * AO, 2);
        TLW(16 + s);
      }
      float acc[40];
#pragma unroll
      for (int r = 0; r < 20; r++) { acc[2 * r] = bf_lo(hp[r]); acc[2 * r + 1] = bf_hi(hp[r]); }
      reg_fence(acc);
#pragma unroll
      for (int t = 0; t < 8; t++) {
        mbar_wait(bars + 8 * (FWO + t));
        if (t) mbar_wait(bs8 + 8 * (AO + t));
        TLW(160 + 8 * s + t);
        if (t == 1) TLW(20 + s);
        const Desc da = mkdesc(0, (t - 1) * PAGE, 1024, 128, 0);
        const Desc db = mkdesc(0, 10 * PAGE + (t < 2 ? t ^ 1 : t) * 15360, 5120, 512, 2);
        wg_fence();
#pragma unroll
        for (int ks = 0; ks < 5; ks++) {
          if (t == 0) wgmma_rs<80, 1>(acc, pq[4 * ks], pq[4 * ks + 1], pq[4 * ks + 2], pq[4 * ks + 3], db + 64 * ks, 1);
          else wgmma_ss<80, 0, 1>(acc, da + 128 * ks, db + 64 * ks, 1);
        }
        wg_commit();
        if (t > 1) {
          wg_wait<1>();
          mbar_arrive_if0(lane, bs8 + 8 * (DW + t - 1), 2);
        }
      }
      wg_wait<0>();
      reg_fence(acc);
      mbar_arrive_if0(lane, bs8 + 8 * (DW + 7), 2);
      TLW(22 + s);
#pragma unroll
      for (int r = 0; r < 20; r++) {
        hp[r] = pack2(acc[2 * r], acc[2 * r + 1]);
        stg32(gout + 32 * 8 * 24576 + (r >> 1) * 1024 + (r & 1) * 128, hp[r]);
      }
      __syncwarp();
      mbar_arrive_if0(lane, bs8 + 8 * AH, 2);
      TLW(24 + s);
    }
    float accf[96];
    uint4 hs[4];
    const uint4* hsp = g_hstat + ((2 * i + s) * 8 + 2 * c) * 64 + 16 * w + g;
    uint32_t rk[2];
    float3 gk[2];
#pragma unroll
    for (int t = 0; t < 8; t++) {
      mbar_wait(bars + 8 * (FW1 + t));
      if (t) mbar_wait(bs8 + 8 * (AH + t));
      TLW(176 + 8 * s + t);
      if (t == 1) TLW(26 + s);
      const Desc da = drs + ((t + 2) % 3) * (PAGE / 16), db = mkdesc(0, (7 + 3 * (t % 5)) * PAGE, 8192, 1024, 1);
      wg_fence();
#pragma unroll
      for (int ks = 0; ks < 5; ks++) {
        const Desc dk = ks < 4 ? db + 128 * ks : mkdesc(0, (7 + 3 * (t % 5)) * PAGE + 24576, 2048, 1024, 1);
        if (t == 0) wgmma_rs<192, 1>(accf, hp[4 * ks], hp[4 * ks + 1], hp[4 * ks + 2], hp[4 * ks + 3], dk, ks != 0);
        else wgmma_ss<192, 0, 1>(accf, da + 128 * ks, dk, 1);
      }
      if (t == 7) wgmma_rs<192, 0>(accf, rk[0], rk[1], 0, 0, mkdesc(0, OFF_RK1, 0, 128, 0), 1);
      wg_commit();
      if (t == 5) {
        while (__any_sync(0xffffffffu, ((hs[0].y ^ epoch) | (hs[0].w ^ epoch) | (hs[1].y ^ epoch) | (hs[1].w ^ epoch) | (hs[2].y ^ epoch) |
                                        (hs[2].w ^ epoch) | (hs[3].y ^ epoch) | (hs[3].w ^ epoch)) != 0)) {
#pragma unroll
          for (int m = 0; m < 4; m++) hs[m] = ll_load(hsp + (m >> 1) * 64 + 8 * (m & 1));
        }
#pragma unroll
        for (int hh = 0; hh < 2; hh++) {
          float sm = __uint_as_float(hs[hh].x) + __uint_as_float(hs[2 + hh].x), sq = __uint_as_float(hs[hh].z) + __uint_as_float(hs[2 + hh].z);
#pragma unroll
          for (int o = 1; o < 4; o <<= 1) {
            sm += __shfl_xor_sync(0xffffffffu, sm, o);
            sq += __shfl_xor_sync(0xffffffffu, sq, o);
          }
          gk[hh].x = sm;
          gk[hh].y = sq;
        }
      }
      if (t == 6) {
        mbar_wait(bars + 8 * SIDE2);
#pragma unroll
        for (int hh = 0; hh < 2; hh++) {
          const float mean = gk[hh].x * (1.f / 640.f), var = fmaxf(fmaf(-mean, mean, gk[hh].y * (1.f / 640.f)), 0.f) + 1e-5f;
          const float a = rsqrtf(var);
          rk[hh] = rk1_frag(-mean, var * a, c);
          gk[hh] = make_float3(0.7978845608028654f * a, 0.7978845608028654f * 0.044715f * a * a * a, 0.5f * a);
        }
      }
      if (t == 0) {
        wg_wait<0>();
        mbar_arrive_if0(lane, bs8 + 8 * DF, 2);
        float sm[2] = {0.f, 0.f}, sq[2] = {0.f, 0.f};
#pragma unroll
        for (int m = 0; m < 10; m++) {
          const float2 b = lds64(sb + OFF_B2 + (8 * m + 2 * c) * 4);
#pragma unroll
          for (int hh = 0; hh < 2; hh++) {
            const float h0 = bf_lo(hp[2 * m + hh]), h1 = bf_hi(hp[2 * m + hh]);
            sm[hh] += h0 + h1;
            sq[hh] = fmaf(h0, h0, fmaf(h1, h1, sq[hh]));
            const float v0 = b.x + h0, v1 = b.y + h1;
            const int e = 4 * m + 2 * hh;
            if (m < 8) { accg[e] = v0; accg[e + 1] = v1; accg[32 + e] = 0.f; accg[33 + e] = 0.f; }
            else { accg[e + 32] = q ? 0.f : v0; accg[e + 33] = q ? 0.f : v1; accg[e + 40] = q ? v0 : 0.f; accg[e + 41] = q ? v1 : 0.f; }
          }
        }
        reg_fence(accg);
#pragma unroll
        for (int o = 1; o < 4; o <<= 1) {
#pragma unroll
          for (int hh = 0; hh < 2; hh++) {
            sm[hh] += __shfl_xor_sync(0xffffffffu, sm[hh], o);
            sq[hh] += __shfl_xor_sync(0xffffffffu, sq[hh], o);
          }
        }
        if (c < 2) ll_store(g_hstat + ((2 * i + s) * 8 + j) * 64 + 16 * w + g + 8 * c, c ? sm[1] : sm[0], c ? sq[1] : sq[0], epoch);
      } else if (t > 1) {
        wg_wait<1>();
        mbar_arrive_if0(lane, bs8 + 8 * (DF + t - 1), 2);
      }
      if (t == 3) {
#pragma unroll
        for (int m = 0; m < 4; m++) hs[m] = ll_load(hsp + (m >> 1) * 64 + 8 * (m & 1));
      }
    }
    wg_wait<0>();
    reg_fence(accf);
    mbar_arrive_if0(lane, bs8 + 8 * (DF + 7), 2);
    TLW(28 + s);
    uint32_t fp[48];
#pragma unroll
    for (int t = 0; t < 12; t++) {
      if (t < 3) {
#pragma unroll
        for (int e = 16 * t; e < 16 * t + 16; e++) {
          fp[e] = pack2(gelu(accf[2 * e], gk[e & 1]), gelu(accf[2 * e + 1], gk[e & 1]));
          stg32(gout + 64 * 8 * 24576 + (e >> 1) * 1024 + (e & 1) * 128, fp[e]);
        }
        __syncwarp();
        mbar_arrive_if0(lane, bs12 + 8 * (AF + t), 2);
        if (t == 2) TLW(30 + s);
      }
      mbar_wait(bars + 8 * (FW2 + t));
      if (t >= 3) mbar_wait(bs12 + 8 * (AF + t));
      TLW(192 + 12 * s + t);
      if (t == 3) TLW(32 + s);
      const Desc da = drs + ((t + 1) & 3) * 512, db = mkdesc(0, OFF_W2 + ((0x321045 >> (4 * (t % 6))) & 7) * 24576, 8192, 1024, 1);
      wg_fence();
#pragma unroll
      for (int ks = 0; ks < 4; ks++) {
        if (t < 3) wgmma_rs<160, 1>(accg, fp[16 * t + 4 * ks], fp[16 * t + 4 * ks + 1], fp[16 * t + 4 * ks + 2], fp[16 * t + 4 * ks + 3], db + 128 * ks, 1);
        else wgmma_ss<160, 0, 1>(accg, da + 128 * ks, db + 128 * ks, 1);
      }
      wg_commit();
      if (t != 0 && t != 3) {
        wg_wait<1>();
        mbar_arrive_if0(lane, bs12 + 8 * (DG + t - 1), 2);
        if (t == 7) mbar_arrive_remote_if0(lane, sb_peer + OFF_BAR + 8 * PF);
      }
      if (t == 2) {
        wg_wait<0>();
        mbar_arrive_if0(lane, bs12 + 8 * (DG + 2), 2);
      }
    }
    mbar_wait_cluster(bars + 8 * PF);
    wg_wait<0>();
    reg_fence(accg);
    mbar_arrive_if0(lane, bs12 + 8 * (DG + 11), 2);
    TLW(34 + s);
    {
      const uint32_t buf = OFF_W2 + 5 * 24576 + s * PAGE + tid * 16;
#pragma unroll
      for (int e = 0; e < 8; e++) {
        const float a = accg[64 + e], b = accg[72 + e];
        accg[64 + e] = q ? a : b;
        accg[72 + e] = q ? b : a;
      }
#pragma unroll
      for (int m = 0; m < 5; m++) {
        const float* a = accg + 32 + 8 * m;
        asm volatile("st.async.shared::cluster.mbarrier::complete_tx::bytes.v4.b32 [%0], {%1,%2,%3,%4}, [%5];"
                     ::"r"(sb_peer + buf + m * 2048), "r"(pack2(a[0], a[1])), "r"(pack2(a[2], a[3])), "r"(pack2(a[4], a[5])),
                     "r"(pack2(a[6], a[7])), "r"(sb_peer + OFF_BAR + 8 * (RX + s)) : "memory");
      }
      TLW(58 + s);
      mbar_wait(bs12 + 8 * (DG + 11));
      mbar_wait_cluster(bars + 8 * (RX + s));
      TLW(60 + s);
      float4 rx[5];
#pragma unroll
      for (int m = 0; m < 5; m++) rx[m] = lds128(sb + buf + m * 2048);
      const uint32_t stg = rs + w * 2816;
      const uint32_t sa = stg + (lane & 15) * 176 + (lane >> 4) * 16;
#pragma unroll
      for (int ks = 0; ks < 5; ks++) {
        const uint32_t u[4] = {__float_as_uint(rx[ks].x), __float_as_uint(rx[ks].y), __float_as_uint(rx[ks].z), __float_as_uint(rx[ks].w)};
        const float* a = accg + (ks < 4 ? 8 * ks : 72);
        stsm4(sa + ks * 32, pack2(a[0] + bf_lo(u[0]), a[1] + bf_hi(u[0])), pack2(a[2] + bf_lo(u[1]), a[3] + bf_hi(u[1])),
              pack2(a[4] + bf_lo(u[2]), a[5] + bf_hi(u[2])), pack2(a[6] + bf_lo(u[3]), a[7] + bf_hi(u[3])));
      }
      __syncwarp();
#pragma unroll
      for (int m = 0; m < 4; m++) rx[m] = lds128(stg + (4 * m + (lane >> 3)) * 176 + (lane & 7) * 16);
      rx[4] = lds128(stg + (lane >> 1) * 176 + 128 + (lane & 1) * 16);
      __nv_bfloat16* outp = out + (row0 + (lane >> 3)) * 640 + cF + (lane & 7) * 8;
#pragma unroll
      for (int m = 0; m < 4; m++) *reinterpret_cast<float4*>(outp + m * 4 * 640) = rx[m];
      *reinterpret_cast<float4*>(out + (row0 + (lane >> 1)) * 640 + cR + (lane & 1) * 8) = rx[4];
    }
    mbar_arrive_if0(lane, bars + 8 * END, 1);
    TLW(36 + s);
  }
}

typedef CUresult (*EncodeFn)(CUtensorMap*, CUtensorMapDataType, cuuint32_t, void*, const cuuint64_t*, const cuuint64_t*,
                             const cuuint32_t*, const cuuint32_t*, CUtensorMapInterleave, CUtensorMapSwizzle,
                             CUtensorMapL2promotion, CUtensorMapFloatOOBfill);

void make_map(EncodeFn enc, CUtensorMap* tm, const void* base, int rows, int cols, int box_rows, int box_cols, int group, int natom,
              CUtensorMapSwizzle sw) {
  const cuuint64_t dims[3] = {(cuuint64_t)(natom ? group : cols), (cuuint64_t)rows, (cuuint64_t)(cols / group)};
  const cuuint64_t strides[2] = {(cuuint64_t)cols * 2, (cuuint64_t)group * 2};
  const cuuint32_t box[3] = {(cuuint32_t)box_cols, (cuuint32_t)box_rows, (cuuint32_t)natom}, es[3] = {1, 1, 1};
  enc(tm, CU_TENSOR_MAP_DATA_TYPE_BFLOAT16, natom ? 3 : 2, const_cast<void*>(base), dims, strides, box, es,
      CU_TENSOR_MAP_INTERLEAVE_NONE, sw, CU_TENSOR_MAP_L2_PROMOTION_L2_128B, CU_TENSOR_MAP_FLOAT_OOB_FILL_NONE);
}

}

extern "C" void kernel_launch(void* const* d_in, const int* in_sizes, int n_in, void* d_out, int out_size) {
  const __nv_bfloat16* x = (const __nv_bfloat16*)d_in[0];
  const __nv_bfloat16* wqkv = (const __nv_bfloat16*)d_in[1];
  const __nv_bfloat16* wo = (const __nv_bfloat16*)d_in[2];
  const __nv_bfloat16* w1 = (const __nv_bfloat16*)d_in[4];
  const __nv_bfloat16* b1 = (const __nv_bfloat16*)d_in[5];
  const __nv_bfloat16* w2 = (const __nv_bfloat16*)d_in[6];
  const __nv_bfloat16* b2 = (const __nv_bfloat16*)d_in[7];

  void* fn = nullptr;
  cudaDriverEntryPointQueryResult qr;
  cudaGetDriverEntryPoint("cuTensorMapEncodeTiled", &fn, cudaEnableDefault, &qr);
  EncodeFn enc = (EncodeFn)fn;
  const CUtensorMapSwizzle S128 = CU_TENSOR_MAP_SWIZZLE_128B, S64 = CU_TENSOR_MAP_SWIZZLE_64B;
  Maps maps;
  make_map(enc, &maps.m[M_X], x, 2048, 640, 128, 64, 64, 0, S128);
  make_map(enc, &maps.m[M_KVF], wqkv, 640, 1920, 32, 64, 640, 2, S128);
  make_map(enc, &maps.m[M_KVH], wqkv, 640, 1920, 32, 32, 64, 0, S128);
  make_map(enc, &maps.m[M_Q2], wqkv, 640, 1920, 64, 32, 32, 2, S64);
  make_map(enc, &maps.m[M_QR], wqkv, 640, 1920, 64, 16, 64, 0, S64);
  make_map(enc, &maps.m[M_WO2], wo, 640, 640, 80, 32, 32, 2, S64);
  make_map(enc, &maps.m[M_WOR], wo, 640, 640, 80, 16, 64, 0, S64);
  make_map(enc, &maps.m[M_W1], w1, 640, 1536, 64, 64, 64, 3, S128);
  make_map(enc, &maps.m[M_W1R], w1, 640, 1536, 16, 64, 64, 3, S128);
  make_map(enc, &maps.m[M_W2F], w2, 1536, 640, 64, 64, 64, 0, S128);
  make_map(enc, &maps.m[M_W2H], w2, 1536, 640, 64, 32, 64, 0, S128);
  cudaFuncSetAttribute(fused_block_kernel, cudaFuncAttributeMaxDynamicSharedMemorySize, SMEM_BYTES);
  fused_block_kernel<<<128, 384, SMEM_BYTES>>>(maps, x, wqkv, wo, w1, b1, w2, b2, (__nv_bfloat16*)d_out);
}
```

```cpp
#include <cuda_runtime.h>
#include <cuda_bf16.h>
#include <cuda.h>
#include <stdint.h>

namespace {

struct Desc { uint32_t base, off, hi; };
__device__ __forceinline__ Desc operator+(Desc d, uint32_t o) { return Desc{d.base, d.off + o, d.hi}; }
template <int TA, int TB> __device__ __forceinline__ void wgmma_ss_n48(float (&d)[24], Desc a, Desc b, int sc) {
  asm volatile("{.reg .pred p; .reg .b32 t, u; .reg .b64 da, db; setp.ne.b32 p, %30, 0; add.u32 t, %24, %25; mov.b64 da, {t, %26}; add.u32 u, %27, %28; mov.b64 db, {u, %29};"
    "wgmma.mma_async.sync.aligned.m64n48k16.f32.bf16.bf16 {%0,%1,%2,%3,%4,%5,%6,%7,%8,%9,%10,%11,%12,%13,%14,%15,%16,%17,%18,%19,%20,%21,%22,%23}, da, db, p, 1, 1, %31, %32;}"
    : "+f"(d[0]),"+f"(d[1]),"+f"(d[2]),"+f"(d[3]),"+f"(d[4]),"+f"(d[5]),"+f"(d[6]),"+f"(d[7]),"+f"(d[8]),"+f"(d[9]),"+f"(d[10]),"+f"(d[11]),"+f"(d[12]),"+f"(d[13]),"+f"(d[14]),"+f"(d[15]),"+f"(d[16]),"+f"(d[17]),"+f"(d[18]),"+f"(d[19]),"+f"(d[20]),"+f"(d[21]),"+f"(d[22]),"+f"(d[23])
    : "r"(a.base), "r"(a.off), "r"(a.hi), "r"(b.base), "r"(b.off), "r"(b.hi), "r"(sc), "n"(TA), "n"(TB));
}
template <int TA, int TB> __device__ __forceinline__ void wgmma_ss_n80(float (&d)[40], Desc a, Desc b, int sc) {
  asm volatile("{.reg .pred p; .reg .b32 t, u; .reg .b64 da, db; setp.ne.b32 p, %46, 0; add.u32 t, %40, %41; mov.b64 da, {t, %42}; add.u32 u, %43, %44; mov.b64 db, {u, %45};"
    "wgmma.mma_async.sync.aligned.m64n80k16.f32.bf16.bf16 {%0,%1,%2,%3,%4,%5,%6,%7,%8,%9,%10,%11,%12,%13,%14,%15,%16,%17,%18,%19,%20,%21,%22,%23,%24,%25,%26,%27,%28,%29,%30,%31,%32,%33,%34,%35,%36,%37,%38,%39}, da, db, p, 1, 1, %47, %48;}"
    : "+f"(d[0]),"+f"(d[1]),"+f"(d[2]),"+f"(d[3]),"+f"(d[4]),"+f"(d[5]),"+f"(d[6]),"+f"(d[7]),"+f"(d[8]),"+f"(d[9]),"+f"(d[10]),"+f"(d[11]),"+f"(d[12]),"+f"(d[13]),"+f"(d[14]),"+f"(d[15]),"+f"(d[16]),"+f"(d[17]),"+f"(d[18]),"+f"(d[19]),"+f"(d[20]),"+f"(d[21]),"+f"(d[22]),"+f"(d[23]),"+f"(d[24]),"+f"(d[25]),"+f"(d[26]),"+f"(d[27]),"+f"(d[28]),"+f"(d[29]),"+f"(d[30]),"+f"(d[31]),"+f"(d[32]),"+f"(d[33]),"+f"(d[34]),"+f"(d[35]),"+f"(d[36]),"+f"(d[37]),"+f"(d[38]),"+f"(d[39])
    : "r"(a.base), "r"(a.off), "r"(a.hi), "r"(b.base), "r"(b.off), "r"(b.hi), "r"(sc), "n"(TA), "n"(TB));
}
template <int TA, int TB> __device__ __forceinline__ void wgmma_ss_n160(float (&d)[80], Desc a, Desc b, int sc) {
  asm volatile("{.reg .pred p; .reg .b32 t, u; .reg .b64 da, db; setp.ne.b32 p, %86, 0; add.u32 t, %80, %81; mov.b64 da, {t, %82}; add.u32 u, %83, %84; mov.b64 db, {u, %85};"
    "wgmma.mma_async.sync.aligned.m64n160k16.f32.bf16.bf16 {%0,%1,%2,%3,%4,%5,%6,%7,%8,%9,%10,%11,%12,%13,%14,%15,%16,%17,%18,%19,%20,%21,%22,%23,%24,%25,%26,%27,%28,%29,%30,%31,%32,%33,%34,%35,%36,%37,%38,%39,%40,%41,%42,%43,%44,%45,%46,%47,%48,%49,%50,%51,%52,%53,%54,%55,%56,%57,%58,%59,%60,%61,%62,%63,%64,%65,%66,%67,%68,%69,%70,%71,%72,%73,%74,%75,%76,%77,%78,%79}, da, db, p, 1, 1, %87, %88;}"
    : "+f"(d[0]),"+f"(d[1]),"+f"(d[2]),"+f"(d[3]),"+f"(d[4]),"+f"(d[5]),"+f"(d[6]),"+f"(d[7]),"+f"(d[8]),"+f"(d[9]),"+f"(d[10]),"+f"(d[11]),"+f"(d[12]),"+f"(d[13]),"+f"(d[14]),"+f"(d[15]),"+f"(d[16]),"+f"(d[17]),"+f"(d[18]),"+f"(d[19]),"+f"(d[20]),"+f"(d[21]),"+f"(d[22]),"+f"(d[23]),"+f"(d[24]),"+f"(d[25]),"+f"(d[26]),"+f"(d[27]),"+f"(d[28]),"+f"(d[29]),"+f"(d[30]),"+f"(d[31]),"+f"(d[32]),"+f"(d[33]),"+f"(d[34]),"+f"(d[35]),"+f"(d[36]),"+f"(d[37]),"+f"(d[38]),"+f"(d[39]),"+f"(d[40]),"+f"(d[41]),"+f"(d[42]),"+f"(d[43]),"+f"(d[44]),"+f"(d[45]),"+f"(d[46]),"+f"(d[47]),"+f"(d[48]),"+f"(d[49]),"+f"(d[50]),"+f"(d[51]),"+f"(d[52]),"+f"(d[53]),"+f"(d[54]),"+f"(d[55]),"+f"(d[56]),"+f"(d[57]),"+f"(d[58]),"+f"(d[59]),"+f"(d[60]),"+f"(d[61]),"+f"(d[62]),"+f"(d[63]),"+f"(d[64]),"+f"(d[65]),"+f"(d[66]),"+f"(d[67]),"+f"(d[68]),"+f"(d[69]),"+f"(d[70]),"+f"(d[71]),"+f"(d[72]),"+f"(d[73]),"+f"(d[74]),"+f"(d[75]),"+f"(d[76]),"+f"(d[77]),"+f"(d[78]),"+f"(d[79])
    : "r"(a.base), "r"(a.off), "r"(a.hi), "r"(b.base), "r"(b.off), "r"(b.hi), "r"(sc), "n"(TA), "n"(TB));
}
template <int TA, int TB> __device__ __forceinline__ void wgmma_ss_n192(float (&d)[96], Desc a, Desc b, int sc) {
  asm volatile("{.reg .pred p; .reg .b32 t, u; .reg .b64 da, db; setp.ne.b32 p, %102, 0; add.u32 t, %96, %97; mov.b64 da, {t, %98}; add.u32 u, %99, %100; mov.b64 db, {u, %101};"
    "wgmma.mma_async.sync.aligned.m64n192k16.f32.bf16.bf16 {%0,%1,%2,%3,%4,%5,%6,%7,%8,%9,%10,%11,%12,%13,%14,%15,%16,%17,%18,%19,%20,%21,%22,%23,%24,%25,%26,%27,%28,%29,%30,%31,%32,%33,%34,%35,%36,%37,%38,%39,%40,%41,%42,%43,%44,%45,%46,%47,%48,%49,%50,%51,%52,%53,%54,%55,%56,%57,%58,%59,%60,%61,%62,%63,%64,%65,%66,%67,%68,%69,%70,%71,%72,%73,%74,%75,%76,%77,%78,%79,%80,%81,%82,%83,%84,%85,%86,%87,%88,%89,%90,%91,%92,%93,%94,%95}, da, db, p, 1, 1, %103, %104;}"
    : "+f"(d[0]),"+f"(d[1]),"+f"(d[2]),"+f"(d[3]),"+f"(d[4]),"+f"(d[5]),"+f"(d[6]),"+f"(d[7]),"+f"(d[8]),"+f"(d[9]),"+f"(d[10]),"+f"(d[11]),"+f"(d[12]),"+f"(d[13]),"+f"(d[14]),"+f"(d[15]),"+f"(d[16]),"+f"(d[17]),"+f"(d[18]),"+f"(d[19]),"+f"(d[20]),"+f"(d[21]),"+f"(d[22]),"+f"(d[23]),"+f"(d[24]),"+f"(d[25]),"+f"(d[26]),"+f"(d[27]),"+f"(d[28]),"+f"(d[29]),"+f"(d[30]),"+f"(d[31]),"+f"(d[32]),"+f"(d[33]),"+f"(d[34]),"+f"(d[35]),"+f"(d[36]),"+f"(d[37]),"+f"(d[38]),"+f"(d[39]),"+f"(d[40]),"+f"(d[41]),"+f"(d[42]),"+f"(d[43]),"+f"(d[44]),"+f"(d[45]),"+f"(d[46]),"+f"(d[47]),"+f"(d[48]),"+f"(d[49]),"+f"(d[50]),"+f"(d[51]),"+f"(d[52]),"+f"(d[53]),"+f"(d[54]),"+f"(d[55]),"+f"(d[56]),"+f"(d[57]),"+f"(d[58]),"+f"(d[59]),"+f"(d[60]),"+f"(d[61]),"+f"(d[62]),"+f"(d[63]),"+f"(d[64]),"+f"(d[65]),"+f"(d[66]),"+f"(d[67]),"+f"(d[68]),"+f"(d[69]),"+f"(d[70]),"+f"(d[71]),"+f"(d[72]),"+f"(d[73]),"+f"(d[74]),"+f"(d[75]),"+f"(d[76]),"+f"(d[77]),"+f"(d[78]),"+f"(d[79]),"+f"(d[80]),"+f"(d[81]),"+f"(d[82]),"+f"(d[83]),"+f"(d[84]),"+f"(d[85]),"+f"(d[86]),"+f"(d[87]),"+f"(d[88]),"+f"(d[89]),"+f"(d[90]),"+f"(d[91]),"+f"(d[92]),"+f"(d[93]),"+f"(d[94]),"+f"(d[95])
    : "r"(a.base), "r"(a.off), "r"(a.hi), "r"(b.base), "r"(b.off), "r"(b.hi), "r"(sc), "n"(TA), "n"(TB));
}
template <int TB> __device__ __forceinline__ void wgmma_rs_n80(float (&d)[40], uint32_t a0, uint32_t a1, uint32_t a2, uint32_t a3, Desc b, int sc) {
  asm volatile("{.reg .pred p; .reg .b32 u; .reg .b64 db; setp.ne.b32 p, %47, 0; add.u32 u, %44, %45; mov.b64 db, {u, %46};"
    "wgmma.mma_async.sync.aligned.m64n80k16.f32.bf16.bf16 {%0,%1,%2,%3,%4,%5,%6,%7,%8,%9,%10,%11,%12,%13,%14,%15,%16,%17,%18,%19,%20,%21,%22,%23,%24,%25,%26,%27,%28,%29,%30,%31,%32,%33,%34,%35,%36,%37,%38,%39}, {%40,%41,%42,%43}, db, p, 1, 1, %48;}"
    : "+f"(d[0]),"+f"(d[1]),"+f"(d[2]),"+f"(d[3]),"+f"(d[4]),"+f"(d[5]),"+f"(d[6]),"+f"(d[7]),"+f"(d[8]),"+f"(d[9]),"+f"(d[10]),"+f"(d[11]),"+f"(d[12]),"+f"(d[13]),"+f"(d[14]),"+f"(d[15]),"+f"(d[16]),"+f"(d[17]),"+f"(d[18]),"+f"(d[19]),"+f"(d[20]),"+f"(d[21]),"+f"(d[22]),"+f"(d[23]),"+f"(d[24]),"+f"(d[25]),"+f"(d[26]),"+f"(d[27]),"+f"(d[28]),"+f"(d[29]),"+f"(d[30]),"+f"(d[31]),"+f"(d[32]),"+f"(d[33]),"+f"(d[34]),"+f"(d[35]),"+f"(d[36]),"+f"(d[37]),"+f"(d[38]),"+f"(d[39])
    : "r"(a0), "r"(a1), "r"(a2), "r"(a3), "r"(b.base), "r"(b.off), "r"(b.hi), "r"(sc), "n"(TB));
}
template <int TB> __device__ __forceinline__ void wgmma_rs_n96(float (&d)[48], uint32_t a0, uint32_t a1, uint32_t a2, uint32_t a3, Desc b, int sc) {
  asm volatile("{.reg .pred p; .reg .b32 u; .reg .b64 db; setp.ne.b32 p, %55, 0; add.u32 u, %52, %53; mov.b64 db, {u, %54};"
    "wgmma.mma_async.sync.aligned.m64n96k16.f32.bf16.bf16 {%0,%1,%2,%3,%4,%5,%6,%7,%8,%9,%10,%11,%12,%13,%14,%15,%16,%17,%18,%19,%20,%21,%22,%23,%24,%25,%26,%27,%28,%29,%30,%31,%32,%33,%34,%35,%36,%37,%38,%39,%40,%41,%42,%43,%44,%45,%46,%47}, {%48,%49,%50,%51}, db, p, 1, 1, %56;}"
    : "+f"(d[0]),"+f"(d[1]),"+f"(d[2]),"+f"(d[3]),"+f"(d[4]),"+f"(d[5]),"+f"(d[6]),"+f"(d[7]),"+f"(d[8]),"+f"(d[9]),"+f"(d[10]),"+f"(d[11]),"+f"(d[12]),"+f"(d[13]),"+f"(d[14]),"+f"(d[15]),"+f"(d[16]),"+f"(d[17]),"+f"(d[18]),"+f"(d[19]),"+f"(d[20]),"+f"(d[21]),"+f"(d[22]),"+f"(d[23]),"+f"(d[24]),"+f"(d[25]),"+f"(d[26]),"+f"(d[27]),"+f"(d[28]),"+f"(d[29]),"+f"(d[30]),"+f"(d[31]),"+f"(d[32]),"+f"(d[33]),"+f"(d[34]),"+f"(d[35]),"+f"(d[36]),"+f"(d[37]),"+f"(d[38]),"+f"(d[39]),"+f"(d[40]),"+f"(d[41]),"+f"(d[42]),"+f"(d[43]),"+f"(d[44]),"+f"(d[45]),"+f"(d[46]),"+f"(d[47])
    : "r"(a0), "r"(a1), "r"(a2), "r"(a3), "r"(b.base), "r"(b.off), "r"(b.hi), "r"(sc), "n"(TB));
}
template <int TB> __device__ __forceinline__ void wgmma_rs_n160(float (&d)[80], uint32_t a0, uint32_t a1, uint32_t a2, uint32_t a3, Desc b, int sc) {
  asm volatile("{.reg .pred p; .reg .b32 u; .reg .b64 db; setp.ne.b32 p, %87, 0; add.u32 u, %84, %85; mov.b64 db, {u, %86};"
    "wgmma.mma_async.sync.aligned.m64n160k16.f32.bf16.bf16 {%0,%1,%2,%3,%4,%5,%6,%7,%8,%9,%10,%11,%12,%13,%14,%15,%16,%17,%18,%19,%20,%21,%22,%23,%24,%25,%26,%27,%28,%29,%30,%31,%32,%33,%34,%35,%36,%37,%38,%39,%40,%41,%42,%43,%44,%45,%46,%47,%48,%49,%50,%51,%52,%53,%54,%55,%56,%57,%58,%59,%60,%61,%62,%63,%64,%65,%66,%67,%68,%69,%70,%71,%72,%73,%74,%75,%76,%77,%78,%79}, {%80,%81,%82,%83}, db, p, 1, 1, %88;}"
    : "+f"(d[0]),"+f"(d[1]),"+f"(d[2]),"+f"(d[3]),"+f"(d[4]),"+f"(d[5]),"+f"(d[6]),"+f"(d[7]),"+f"(d[8]),"+f"(d[9]),"+f"(d[10]),"+f"(d[11]),"+f"(d[12]),"+f"(d[13]),"+f"(d[14]),"+f"(d[15]),"+f"(d[16]),"+f"(d[17]),"+f"(d[18]),"+f"(d[19]),"+f"(d[20]),"+f"(d[21]),"+f"(d[22]),"+f"(d[23]),"+f"(d[24]),"+f"(d[25]),"+f"(d[26]),"+f"(d[27]),"+f"(d[28]),"+f"(d[29]),"+f"(d[30]),"+f"(d[31]),"+f"(d[32]),"+f"(d[33]),"+f"(d[34]),"+f"(d[35]),"+f"(d[36]),"+f"(d[37]),"+f"(d[38]),"+f"(d[39]),"+f"(d[40]),"+f"(d[41]),"+f"(d[42]),"+f"(d[43]),"+f"(d[44]),"+f"(d[45]),"+f"(d[46]),"+f"(d[47]),"+f"(d[48]),"+f"(d[49]),"+f"(d[50]),"+f"(d[51]),"+f"(d[52]),"+f"(d[53]),"+f"(d[54]),"+f"(d[55]),"+f"(d[56]),"+f"(d[57]),"+f"(d[58]),"+f"(d[59]),"+f"(d[60]),"+f"(d[61]),"+f"(d[62]),"+f"(d[63]),"+f"(d[64]),"+f"(d[65]),"+f"(d[66]),"+f"(d[67]),"+f"(d[68]),"+f"(d[69]),"+f"(d[70]),"+f"(d[71]),"+f"(d[72]),"+f"(d[73]),"+f"(d[74]),"+f"(d[75]),"+f"(d[76]),"+f"(d[77]),"+f"(d[78]),"+f"(d[79])
    : "r"(a0), "r"(a1), "r"(a2), "r"(a3), "r"(b.base), "r"(b.off), "r"(b.hi), "r"(sc), "n"(TB));
}
template <int TB> __device__ __forceinline__ void wgmma_rs_n192(float (&d)[96], uint32_t a0, uint32_t a1, uint32_t a2, uint32_t a3, Desc b, int sc) {
  asm volatile("{.reg .pred p; .reg .b32 u; .reg .b64 db; setp.ne.b32 p, %103, 0; add.u32 u, %100, %101; mov.b64 db, {u, %102};"
    "wgmma.mma_async.sync.aligned.m64n192k16.f32.bf16.bf16 {%0,%1,%2,%3,%4,%5,%6,%7,%8,%9,%10,%11,%12,%13,%14,%15,%16,%17,%18,%19,%20,%21,%22,%23,%24,%25,%26,%27,%28,%29,%30,%31,%32,%33,%34,%35,%36,%37,%38,%39,%40,%41,%42,%43,%44,%45,%46,%47,%48,%49,%50,%51,%52,%53,%54,%55,%56,%57,%58,%59,%60,%61,%62,%63,%64,%65,%66,%67,%68,%69,%70,%71,%72,%73,%74,%75,%76,%77,%78,%79,%80,%81,%82,%83,%84,%85,%86,%87,%88,%89,%90,%91,%92,%93,%94,%95}, {%96,%97,%98,%99}, db, p, 1, 1, %104;}"
    : "+f"(d[0]),"+f"(d[1]),"+f"(d[2]),"+f"(d[3]),"+f"(d[4]),"+f"(d[5]),"+f"(d[6]),"+f"(d[7]),"+f"(d[8]),"+f"(d[9]),"+f"(d[10]),"+f"(d[11]),"+f"(d[12]),"+f"(d[13]),"+f"(d[14]),"+f"(d[15]),"+f"(d[16]),"+f"(d[17]),"+f"(d[18]),"+f"(d[19]),"+f"(d[20]),"+f"(d[21]),"+f"(d[22]),"+f"(d[23]),"+f"(d[24]),"+f"(d[25]),"+f"(d[26]),"+f"(d[27]),"+f"(d[28]),"+f"(d[29]),"+f"(d[30]),"+f"(d[31]),"+f"(d[32]),"+f"(d[33]),"+f"(d[34]),"+f"(d[35]),"+f"(d[36]),"+f"(d[37]),"+f"(d[38]),"+f"(d[39]),"+f"(d[40]),"+f"(d[41]),"+f"(d[42]),"+f"(d[43]),"+f"(d[44]),"+f"(d[45]),"+f"(d[46]),"+f"(d[47]),"+f"(d[48]),"+f"(d[49]),"+f"(d[50]),"+f"(d[51]),"+f"(d[52]),"+f"(d[53]),"+f"(d[54]),"+f"(d[55]),"+f"(d[56]),"+f"(d[57]),"+f"(d[58]),"+f"(d[59]),"+f"(d[60]),"+f"(d[61]),"+f"(d[62]),"+f"(d[63]),"+f"(d[64]),"+f"(d[65]),"+f"(d[66]),"+f"(d[67]),"+f"(d[68]),"+f"(d[69]),"+f"(d[70]),"+f"(d[71]),"+f"(d[72]),"+f"(d[73]),"+f"(d[74]),"+f"(d[75]),"+f"(d[76]),"+f"(d[77]),"+f"(d[78]),"+f"(d[79]),"+f"(d[80]),"+f"(d[81]),"+f"(d[82]),"+f"(d[83]),"+f"(d[84]),"+f"(d[85]),"+f"(d[86]),"+f"(d[87]),"+f"(d[88]),"+f"(d[89]),"+f"(d[90]),"+f"(d[91]),"+f"(d[92]),"+f"(d[93]),"+f"(d[94]),"+f"(d[95])
    : "r"(a0), "r"(a1), "r"(a2), "r"(a3), "r"(b.base), "r"(b.off), "r"(b.hi), "r"(sc), "n"(TB));
}
template <int N, int TA, int TB> __device__ __forceinline__ void wgmma_ss(float (&d)[N / 2], Desc a, Desc b, int sc) {
  if constexpr (N == 48) wgmma_ss_n48<TA, TB>(d, a, b, sc);
  else if constexpr (N == 80) wgmma_ss_n80<TA, TB>(d, a, b, sc);
  else if constexpr (N == 160) wgmma_ss_n160<TA, TB>(d, a, b, sc);
  else if constexpr (N == 192) wgmma_ss_n192<TA, TB>(d, a, b, sc);
}
template <int N, int TB> __device__ __forceinline__ void wgmma_rs(float (&d)[N / 2], uint32_t a0, uint32_t a1, uint32_t a2, uint32_t a3, Desc b, int sc) {
  if constexpr (N == 80) wgmma_rs_n80<TB>(d, a0, a1, a2, a3, b, sc);
  else if constexpr (N == 96) wgmma_rs_n96<TB>(d, a0, a1, a2, a3, b, sc);
  else if constexpr (N == 160) wgmma_rs_n160<TB>(d, a0, a1, a2, a3, b, sc);
  else if constexpr (N == 192) wgmma_rs_n192<TB>(d, a0, a1, a2, a3, b, sc);
}

constexpr uint32_t SMEM_BASE = 1024;
constexpr uint32_t PAGE = 10240;
constexpr uint32_t OFF_RING = 16 * PAGE;
constexpr uint32_t OFF_KVB = 50176;
constexpr uint32_t OFF_KVP = 43008;
constexpr uint32_t OFF_R1 = 35840;
constexpr uint32_t OFF_MISC = 22 * PAGE;
constexpr uint32_t OFF_W2 = OFF_MISC - 6 * 24576;
constexpr uint32_t OFF_BAR = OFF_MISC;
constexpr uint32_t OFF_LN1 = OFF_MISC + 1920;
constexpr uint32_t OFF_RK1 = OFF_MISC + 2944;
constexpr uint32_t OFF_B2 = OFF_MISC + 1600;
constexpr uint32_t OFF_SCR = OFF_MISC + 6784;
constexpr uint32_t SMEM_BYTES = OFF_MISC + 7040;

enum : int {
  RF = 0, FX = 5, FE = 18, RX = 22, RXK = 24,
  RE = 25, PX = 30, PF = 31, SIDE = 32, ZK = 33, RKV = 34, ST1 = 35, XF = 36, KD = 37, CG = 38,
  FWO = 40, FW1 = 48, FW2 = 56,
  AO = 70, AH = 86, AF = 102,
  DW = 126, DF = 142, DG = 158,
  SIDE2 = 185, KVB = 186, END = 187, OM = 188
};

struct __align__(128) Scratch {
  uint8_t act[3 * 32 * 8 * 24576];
  uint4 ln1[2048];
  uint4 cs[4 * 1728];
  uint4 hstat[32 * 8 * 64];
  float kv[8 * 1696];
  uint32_t flag[(3 * 32 + 16) * 32];
  uint32_t epoch;
};
__device__ Scratch g_scratch;

struct Maps { CUtensorMap m[11]; };
enum : int { M_X, M_KVF, M_KVH, M_Q2, M_QR, M_WO2, M_WOR, M_W1, M_W1R, M_W2F, M_W2H };

#define TL(id)
#define TLW(id)
#define TL0(id)
#define TL1(id)
#define TC(v)
#define TS(id, v)

constexpr int SPIN_LIMIT = 1 << 19;

__device__ __forceinline__ bool elect_one() {
  uint32_t p;
  asm volatile("{.reg .pred P; elect.sync _|P, 0xffffffff; selp.u32 %0,1,0,P;}" : "=r"(p));
  return p;
}
__device__ __forceinline__ void mbar_wait(uint32_t bar, uint32_t parity = 0) {
  asm volatile("{.reg .pred p;\nW: mbarrier.try_wait.parity.shared::cta.b64 p, [%0], %1;\n@!p bra W;}" ::"r"(bar), "r"(parity) : "memory");
}
__device__ __forceinline__ void mbar_wait_cluster(uint32_t bar) {
  asm volatile("{.reg .pred p;\nW: mbarrier.try_wait.parity.acquire.cluster.shared::cta.b64 p, [%0], 0;\n@!p bra W;}" ::"r"(bar) : "memory");
}
__device__ __forceinline__ void mbar_wait_wd(uint32_t bar) {
  asm volatile("{.reg .pred p; .reg .u32 n; mov.u32 n, 0;\n"
               "W: mbarrier.try_wait.parity.shared::cta.b64 p, [%0], 0;\n"
               "@p bra D; add.u32 n, n, 1; setp.gt.u32 p, n, %1; @p trap; bra W;\n"
               "D: }" ::"r"(bar), "n"(SPIN_LIMIT) : "memory");
}
__device__ __forceinline__ uint32_t mbar_test(uint32_t bar) {
  uint32_t ok;
  asm volatile("{.reg .pred p; mbarrier.test_wait.parity.shared::cta.b64 p, [%1], 0; selp.u32 %0, 1, 0, p;}" : "=r"(ok) : "r"(bar) : "memory");
  return ok;
}
__device__ __forceinline__ void mbar_arrive(uint32_t bar, uint32_t n) {
  asm volatile("mbarrier.arrive.shared::cta.b64 _, [%0], %1;" ::"r"(bar), "r"(n) : "memory");
}
__device__ __forceinline__ void mbar_arrive_if0(int z, uint32_t bar, uint32_t n) {
  asm volatile("{.reg .pred p; setp.eq.s32 p, %2, 0; @p mbarrier.arrive.shared::cta.b64 _, [%0], %1;}" ::"r"(bar), "r"(n), "r"(z) : "memory");
}
__device__ __forceinline__ void mbar_arrive_remote_if0(int z, uint32_t bar) {
  asm volatile("{.reg .pred p; setp.eq.s32 p, %1, 0; @p mbarrier.arrive.shared::cluster.b64 _, [%0];}" ::"r"(bar), "r"(z) : "memory");
}
__device__ __forceinline__ void mbar_expect(uint32_t bar, uint32_t bytes) {
  asm volatile("mbarrier.arrive.expect_tx.shared::cta.b64 _, [%0], %1;" ::"r"(bar), "r"(bytes) : "memory");
}
__device__ __forceinline__ void tma2d(uint32_t dst, const CUtensorMap* tm, uint32_t bar, int c0, int c1) {
  asm volatile("cp.async.bulk.tensor.2d.shared::cluster.global.mbarrier::complete_tx::bytes [%0],[%1,{%3,%4}],[%2];"
               ::"r"(dst), "l"(tm), "r"(bar), "r"(c0), "r"(c1) : "memory");
}
__device__ __forceinline__ void tma3d(uint32_t dst, const CUtensorMap* tm, uint32_t bar, int c0, int c1, int c2) {
  asm volatile("cp.async.bulk.tensor.3d.shared::cluster.global.mbarrier::complete_tx::bytes [%0],[%1,{%3,%4,%5}],[%2];"
               ::"r"(dst), "l"(tm), "r"(bar), "r"(c0), "r"(c1), "r"(c2) : "memory");
}
__device__ __forceinline__ void bulk_load(uint32_t dst, const void* src, uint32_t bytes, uint32_t bar) {
  asm volatile("cp.async.bulk.shared::cluster.global.mbarrier::complete_tx::bytes [%0],[%1],%2,[%3];"
               ::"r"(dst), "l"(src), "r"(bytes), "r"(bar) : "memory");
}
__device__ __forceinline__ void l2_prefetch(const void* src, uint32_t bytes) {
  asm volatile("cp.async.bulk.prefetch.L2.global [%0], %1;" ::"l"(src), "r"(bytes) : "memory");
}
__device__ __forceinline__ void fence_async_smem() { asm volatile("fence.proxy.async.shared::cta;" ::: "memory"); }
__device__ __forceinline__ void fence_async_global() { asm volatile("fence.proxy.async.global;" ::: "memory"); }
__device__ __forceinline__ void flag_release(uint32_t* p, uint32_t bits) {
  asm volatile("fence.release.gpu;" ::: "memory");
  asm volatile("red.relaxed.gpu.global.xor.b32 [%0], %1;" ::"l"(p), "r"(bits) : "memory");
}
__device__ __forceinline__ uint32_t flag_read(const uint32_t* p, uint32_t epoch) {
  uint32_t v;
  asm volatile("ld.relaxed.gpu.global.u32 %0, [%1];" : "=r"(v) : "l"(p) : "memory");
  return v ^ ((epoch & 1) - 1);
}
__device__ __forceinline__ void flag_wait(const uint32_t* p, uint32_t want, uint32_t epoch) {
  int it = 0;
  while ((flag_read(p, epoch) & want) != want && ++it < SPIN_LIMIT) {}
  asm volatile("fence.acquire.gpu;" ::: "memory");
}
__device__ __forceinline__ void stg32(const void* p, uint32_t v) { asm volatile("st.global.u32 [%0], %1;" ::"l"(p), "r"(v) : "memory"); }
__device__ __forceinline__ void wg_fence() { asm volatile("wgmma.fence.sync.aligned;" ::: "memory"); }
__device__ __forceinline__ void wg_commit() { asm volatile("wgmma.commit_group.sync.aligned;" ::: "memory"); }
template <int N> __device__ __forceinline__ void wg_wait() { asm volatile("wgmma.wait_group.sync.aligned %0;" ::"n"(N) : "memory"); }
template <int N> __device__ __forceinline__ void reg_fence(float (&a)[N]) {
#pragma unroll
  for (int i = 0; i < N; i++) asm volatile("" : "+f"(a[i])::"memory");
}
template <int ID, int N> __device__ __forceinline__ void named_bar() { asm volatile("bar.sync %0, %1;" ::"n"(ID), "n"(N) : "memory"); }
template <int N> __device__ __forceinline__ void reg_fence(uint32_t (&a)[N]) {
#pragma unroll
  for (int i = 0; i < N; i++) asm volatile("" : "+r"(a[i])::"memory");
}
__device__ __forceinline__ Desc mkdesc(uint32_t dyn, uint32_t off, uint32_t lbo, uint32_t sbo, uint32_t swz) {
  return Desc{dyn, ((off + SMEM_BASE) >> 4) + ((lbo >> 4) << 16), (sbo >> 4) | (swz << 30)};
}
__device__ __forceinline__ uint32_t pack2(float lo, float hi) {
  uint32_t r;
  asm("cvt.rn.bf16x2.f32 %0, %1, %2;" : "=r"(r) : "f"(hi), "f"(lo));
  return r;
}
__device__ __forceinline__ float bf_lo(uint32_t v) { return __uint_as_float(v << 16); }
__device__ __forceinline__ float bf_hi(uint32_t v) { return __uint_as_float(v & 0xffff0000u); }
__device__ __forceinline__ void stsm4(uint32_t addr, uint32_t a, uint32_t b, uint32_t c, uint32_t d) {
  asm volatile("stmatrix.sync.aligned.m8n8.x4.shared.b16 [%0], {%1,%2,%3,%4};" ::"r"(addr), "r"(a), "r"(b), "r"(c), "r"(d) : "memory");
}
__device__ __forceinline__ void ldsm4(uint32_t addr, uint32_t* r) {
  asm volatile("ldmatrix.sync.aligned.m8n8.x4.shared.b16 {%0,%1,%2,%3}, [%4];" : "=r"(r[0]), "=r"(r[1]), "=r"(r[2]), "=r"(r[3]) : "r"(addr) : "memory");
}
__device__ __forceinline__ float2 lds64(uint32_t a) {
  float2 v;
  asm volatile("ld.shared.v2.f32 {%0,%1}, [%2];" : "=f"(v.x), "=f"(v.y) : "r"(a) : "memory");
  return v;
}
__device__ __forceinline__ float4 lds128(uint32_t a) {
  float4 v;
  asm volatile("ld.shared.v4.f32 {%0,%1,%2,%3}, [%4];" : "=f"(v.x), "=f"(v.y), "=f"(v.z), "=f"(v.w) : "r"(a) : "memory");
  return v;
}
__device__ __forceinline__ void sts64(uint32_t a, uint32_t x, uint32_t y) {
  asm volatile("st.shared.v2.u32 [%0], {%1,%2};" ::"r"(a), "r"(x), "r"(y) : "memory");
}
__device__ __forceinline__ void sts128(uint32_t a, uint32_t x, uint32_t y, uint32_t z, uint32_t w) {
  asm volatile("st.shared.v4.u32 [%0], {%1,%2,%3,%4};" ::"r"(a), "r"(x), "r"(y), "r"(z), "r"(w) : "memory");
}
__device__ __forceinline__ float ex2(float x) {
  float r;
  asm("ex2.approx.ftz.f32 %0, %1;" : "=f"(r) : "f"(x));
  return r;
}
__device__ __forceinline__ float rcp(float x) {
  float r;
  asm("rcp.approx.ftz.f32 %0, %1;" : "=f"(r) : "f"(x));
  return r;
}
constexpr float LOG2E = 1.4426950408889634f;
__device__ __forceinline__ float phi(float z, float a, float a2) {
  float r = ex2(z * a2) + 1e-6f;
  asm("{.reg .pred p; setp.gt.f32 p, %1, 0f00000000; @p fma.rn.f32 %0, %1, %2, 0f3F800008;}" : "+f"(r) : "f"(z), "f"(a));
  return r;
}
__device__ __forceinline__ float gelu(float z, const float3& k) {
  float th;
  asm("tanh.approx.f32 %0, %1;" : "=f"(th) : "f"(z * fmaf(z * z, k.y, k.x)));
  const float hy = z * k.z;
  return fmaf(hy, th, hy);
}
__device__ __forceinline__ uint32_t rk1_frag(float m, float d, int c) {
  const uint32_t hi = pack2(m, d), lo = pack2(m - bf_lo(hi), d - bf_hi(hi));
  return __byte_perm(c & 2 ? 0u : hi, c == 3 ? 0u : lo, 0x107632541010ull >> (16 * c) & 0xffff);
}
__device__ __forceinline__ void rk1_store(uint32_t addr, float2 cs, uint32_t bb) {
  const uint32_t hi = pack2(cs.x, cs.y), lo = pack2(cs.x - bf_lo(hi), cs.y - bf_hi(hi));
  sts128(addr, __byte_perm(hi, lo, 0x5410), __byte_perm(hi, bb, 0x5410), bb & 0xffffu, 0);
  sts128(addr + 16, __byte_perm(hi, lo, 0x7632), __byte_perm(hi, bb, 0x7632), bb >> 16, 0);
}
constexpr uint32_t ONES = 0x3F803F80u;
__device__ __forceinline__ void ll_store(uint4* p, float a, float b, uint32_t tag) {
  asm volatile("st.relaxed.gpu.global.v4.u32 [%0], {%1,%2,%3,%2};" ::"l"(p), "r"(__float_as_uint(a)), "r"(tag), "r"(__float_as_uint(b)) : "memory");
}
__device__ __forceinline__ uint4 ll_load(const void* p) {
  uint4 v;
  asm volatile("ld.relaxed.gpu.global.v4.u32 {%0,%1,%2,%3}, [%4];" : "=r"(v.x), "=r"(v.y), "=r"(v.z), "=r"(v.w) : "l"(p) : "memory");
  return v;
}
template <int N>
__device__ __forceinline__ void ll_wait(uint4 (&v)[N], const uint4* p, int stride, uint32_t tag) {
  uint32_t bad;
  int it = 0;
  do {
    bad = 0;
#pragma unroll
    for (int m = 0; m < N; m++) v[m] = ll_load(p + m * stride);
#pragma unroll
    for (int m = 0; m < N; m++) bad |= (v[m].y ^ tag) | (v[m].w ^ tag);
  } while (__any_sync(0xffffffffu, bad) && ++it < SPIN_LIMIT);
}
__device__ __forceinline__ void ll_wait2(uint4 (&v)[8], const uint4* p, uint32_t tag) {
  uint32_t bad;
  int it = 0;
  do {
    bad = 0;
#pragma unroll
    for (int m = 0; m < 8; m++) v[m] = ll_load(p + (m >> 1) * 1728 + (m & 1));
#pragma unroll
    for (int m = 0; m < 8; m++) bad |= (v[m].y ^ tag) | (v[m].w ^ tag);
  } while (__any_sync(0xffffffffu, bad) && ++it < SPIN_LIMIT);
}
__device__ __forceinline__ float2 ll_sum4(const uint4* p, uint32_t tag) {
  uint4 v[4];
  ll_wait(v, p, 1728, tag);
  return make_float2((__uint_as_float(v[0].x) + __uint_as_float(v[1].x)) + (__uint_as_float(v[2].x) + __uint_as_float(v[3].x)),
                     (__uint_as_float(v[0].z) + __uint_as_float(v[1].z)) + (__uint_as_float(v[2].z) + __uint_as_float(v[3].z)));
}
__device__ __noinline__ float2 colsum(const __nv_bfloat16* wm, int ld, int h0, int h1) {
  const int lane = threadIdx.x & 31, r4 = lane >> 3;
  float d[8];
#pragma unroll
  for (int e = 0; e < 8; e++) d[e] = 0.f;
#pragma unroll 1
  for (int h = h0; h < h1; h++) {
    const __nv_bfloat16* wp = wm + (4 * h + r4) * ld + 8 * (lane & 7);
    uint4 v[14];
#pragma unroll
    for (int m = 0; m < 14; m++) {
      v[m] = make_uint4(0, 0, 0, 0);
      if (m < 13 || h == 0)
        asm volatile("ld.global.nc.v4.u32 {%0,%1,%2,%3}, [%4];" : "=r"(v[m].x), "=r"(v[m].y), "=r"(v[m].z), "=r"(v[m].w) : "l"(wp));
      wp += 12 * ld;
    }
#pragma unroll
    for (int m = 0; m < 14; m++) {
      d[0] += bf_lo(v[m].x); d[1] += bf_hi(v[m].x); d[2] += bf_lo(v[m].y); d[3] += bf_hi(v[m].y);
      d[4] += bf_lo(v[m].z); d[5] += bf_hi(v[m].z); d[6] += bf_lo(v[m].w); d[7] += bf_hi(v[m].w);
    }
  }
#pragma unroll 1
  for (int o = 8; o < 32; o <<= 1) {
#pragma unroll
    for (int e = 0; e < 8; e++) d[e] += __shfl_xor_sync(0xffffffffu, d[e], o);
  }
  if (r4 & 2) { d[0] = d[4]; d[1] = d[5]; d[2] = d[6]; d[3] = d[7]; }
  return r4 & 1 ? make_float2(d[2], d[3]) : make_float2(d[0], d[1]);
}
template <bool PHI>
__device__ __forceinline__ void ln_pair(const float* z, const float (&a)[2], const float (&a2)[2], uint32_t* o) {
#pragma unroll
  for (int e = 0; e < 4; e++) {
    const int hh = e & 1;
    o[e] = PHI ? pack2(phi(z[2 * e], a[hh], a2[hh]), phi(z[2 * e + 1], a[hh], a2[hh])) : pack2(z[2 * e] * a[hh], z[2 * e + 1] * a[hh]);
  }
}

__global__ void __cluster_dims__(2, 1, 1) __launch_bounds__(384, 1)
fused_block_kernel(Scratch* __restrict__ scr, const __nv_bfloat16* __restrict__ wqkv, const __nv_bfloat16* __restrict__ wo,
                   const __nv_bfloat16* __restrict__ w1, const __nv_bfloat16* __restrict__ w2, const __nv_bfloat16* __restrict__ b2,
                   const __nv_bfloat16* __restrict__ b1, __nv_bfloat16* __restrict__ out,
                   const __grid_constant__ Maps maps) {
  extern __shared__ __align__(1024) uint8_t smem_raw[];
  const uint32_t sb = (uint32_t)__cvta_generic_to_shared(smem_raw);
  const uint32_t bars = sb + OFF_BAR;
  const int warp = __shfl_sync(0xffffffffu, threadIdx.x >> 5, 0);
  const int lane = threadIdx.x & 31;
  if (warp < 3 && elect_one()) asm volatile("prefetch.tensormap [%0];" ::"l"(&maps.m[warp]) : "memory");
  if (warp == 9 && elect_one()) l2_prefetch(b2 + (blockIdx.x & 7) * 80, 160);
  if (warp == 10 && elect_one()) l2_prefetch(b1 + (blockIdx.x & 31) * 48, 96);

  const int cl = blockIdx.x >> 1, q = blockIdx.x & 1;
  const int u7 = ((cl - 36) * 37) >> 8;
  const int oct = cl < 4 ? 0 : cl < 36 ? 1 + 2 * ((cl - 4) & 7) : 2 + 2 * (cl - 36 - 7 * u7);
  const int u4 = cl < 4 ? cl : cl < 36 ? (cl - 4) >> 3 : u7;
  const int i = 2 * (oct & 7) + (u4 >> 1), p = 2 * (oct >> 3) + (u4 & 1);
  const int j = 2 * p + q;
  auto col_f = [](int jj) { return 160 * (jj >> 1) + 16 * (jj & 2) + 64 * (jj & 1); };
  auto col_r = [](int jj) { return 160 * (jj >> 1) + 128 - 64 * (jj & 2) + 16 * (jj & 1); };
  const int cF = col_f(j), cR = col_r(j), role = q ^ (p & 1);

  auto load_kv = [&](int s) {
    const uint32_t dst = sb + (s < 16 ? OFF_RING + (s % 5) * 12288 : (s - 16) * 12288), bar = bars + 8 * (s < 16 ? RF + s % 5 : FE + s - 16);
    tma3d(dst, &maps.m[M_KVF], bar, cF, 32 * s, 1);
    tma2d(dst + 8192, &maps.m[M_KVH], bar, 640 + 640 * role + cR - 16 * q, 32 * s);
    mbar_expect(bar, 10240);
  };
  auto load_x = [&](int c, int b, int slot) {
    tma2d(sb + slot * 16384, &maps.m[M_X], bars + 8 * (FX + b), 64 * c, 128 * i);
    mbar_expect(bars + 8 * (FX + b), 16384);
  };
  auto bar_init = [&](int n, uint32_t cnt) { asm volatile("mbarrier.init.shared::cta.b64 [%0], %1;" ::"r"(bars + 8 * n), "r"(cnt) : "memory"); };

  TC(tc0);
  if (elect_one()) {
    if (warp == 8) {
      bar_init(RF, 1);
      bar_init(RF + 1, 1);
      bar_init(FX, 1);
      load_x(0, 0, 0);
      load_kv(0);
      load_kv(1);
    } else if (warp < 8) {
#pragma unroll
      for (int n = 0; n < 5; n++)
        if (warp > (n == 0 ? 1 : n == 1 ? 0 : -1)) bar_init(5 * warp + n, warp < 5 ? 1 : 8);
      asm volatile("fence.mbarrier_init.release.cluster;" ::: "memory");
    }
  }
  TC(tc1);
  __syncthreads();
  asm volatile("barrier.cluster.arrive.relaxed.aligned;" ::: "memory");

  if (warp >= 8) {
    TC(tc2);
    if (warp == 8) {
      if (elect_one()) {
        load_x(1, 1, 1);
        load_kv(2);
        load_kv(3);
        load_x(2, 2, 2);
        load_kv(4);
        load_x(3, 3, 3);
      }
      __syncwarp();
    }
    TC(tc3);
    asm volatile("setmaxnreg.dec.sync.aligned.u32 88;");
    if (warp == 8) {
      asm volatile("barrier.cluster.wait.aligned;" ::: "memory");
      TL(40);
      TS(41, tc0); TS(42, tc1); TS(43, tc2); TS(19, tc3);
      if (elect_one()) {
        auto prefetch_piece = [&](const __nv_bfloat16* wm, uint32_t total, uint32_t off, uint32_t bytes) {
          l2_prefetch(reinterpret_cast<const uint8_t*>(wm) + blockIdx.x * total + off, bytes);
        };
#pragma unroll
        for (int s = 5; s < 16; s++) {
          mbar_wait(bars + 8 * (RE + s % 5), (s / 5 - 1) & 1);
          load_kv(s);
          if (s < 11) load_x(s - 1, s - 1, s - 1);
          if (s == 12) mbar_wait(bars + 8 * XF);
          if (s >= 12) load_kv(s + 4);
          if (s < 13) asm volatile("prefetch.tensormap [%0];" ::"l"(&maps.m[s - 2]) : "memory");
          if (s >= 11) prefetch_piece(wo, 6400, (s - 11) * 1280, 1280);
          TL1(96 + s);
        }
#pragma unroll
        for (int t = 0; t < 10; t++) {
          const int slot = (t + 1) % 5, k0 = 64 * (t < 7 ? t + 3 : t - 7);
          const uint32_t dst = sb + OFF_RING + slot * 12288, bar = bars + 8 * (RF + slot);
          mbar_wait(bars + 8 * (RE + slot), ((t + 11) / 5) & 1);
          tma3d(dst, &maps.m[M_Q2], bar, 0, k0, 5 * p + 3 * q);
          tma2d(dst + 8192, &maps.m[M_QR], bar, 80 * j + 64 - 64 * q, k0);
          mbar_expect(bar, 10240);
          if (t >= 6 && t < 9) load_x(t - 6, t + 4, t - 2);
          if (t < 8) prefetch_piece(w1, 15360, t * 1920, 1920);
          TL1(116 + t);
        }
#pragma unroll 1
        for (int n = 0; n < 32; n += 4) {
          const int t = (0x41765320u >> n) & 7, k0 = 80 * (t == 0 ? j : t - (t <= j));
          const uint32_t dst = sb + 10 * PAGE + (t < 2 ? t ^ 1 : t) * 15360, bar = bars + 8 * (FWO + t);
          mbar_wait(bars + 8 * (RE + ((0x00432221u >> n) & 15)), n >= 24);
          if (n >= 8) mbar_wait(bars + 8 * (FWO + ((0x41765320u >> (n - 8)) & 7)));
          tma3d(dst, &maps.m[M_WO2], bar, 0, k0, cF >> 5);
          tma2d(dst + 10240, &maps.m[M_WOR], bar, cR, k0);
          mbar_expect(bar, 12800);
          TL1(128 + n / 4);
        }
#pragma unroll 1
        for (int t = 0; t < 8; t++) {
          const uint32_t wb = bars + 8 * (t == 0 ? FWO + 1 : t < 5 ? DW + 2 * t - 1 : DF + t - 5);
          const int jj = t == 0 ? j : t - (t <= j);
          const uint32_t dst = sb + (7 + 3 * (t < 5 ? t : t - 5)) * PAGE, bar = bars + 8 * (FW1 + t);
          mbar_wait(wb);
          if (t) {
            mbar_wait(wb + 64);
            mbar_wait(bars + 8 * (t == 1 ? AH : t < 4 ? FW1 + t - 1 : t == 4 ? AH + 2 : DF + t - 4));
          }
          tma3d(dst, &maps.m[M_W1], bar, 0, col_f(jj), 3 * j);
          tma3d(dst + 24576, &maps.m[M_W1R], bar, 0, col_r(jj), 3 * j);
          mbar_expect(bar, 30720);
          if (t >= 3) prefetch_piece(w2, 15360, (t - 3) * 3072, 3072);
          TL1(136 + t);
        }
#pragma unroll 1
        for (int t = 0; t < 12; t++) {
          const int t6 = t < 6 ? t : t - 6;
          const uint32_t wb = bars + 8 * (t < 6 ? DF + ((0x776544 >> (4 * t)) & 7) : DG + t6);
          const int uu = (0xA95024 >> (2 * t)) & 3, n = (0x924900 >> (2 * t)) & 3;
          const int k0 = 192 * (t < 3 ? j : 2 * (n + (n >= p)) + q) + 64 * uu;
          const uint32_t dst = sb + OFF_W2 + ((0x321045 >> (4 * t6)) & 7) * 24576, bar = bars + 8 * (FW2 + t);
          mbar_wait(wb);
          mbar_wait(wb + (t < 6 ? 64 : 96));
          tma2d(dst, &maps.m[M_W2F], bar, cF, k0);
          tma2d(dst + 8192, &maps.m[M_W2F], bar, cF + 64 - 128 * q, k0);
          tma2d(dst + 16384, &maps.m[M_W2H], bar, cR - 16 * q, k0);
          mbar_expect(bar, 20480);
          TL1(144 + t);
        }
      }
    } else {
      const int unit = i * 8 + j, hw = warp - 9, part = unit & 3, cg = unit >> 2;
      uint32_t epoch;
      asm volatile("ld.relaxed.gpu.global.u32 %0, [%1];" : "=r"(epoch) : "l"(&scr->epoch) : "memory");
      epoch += 1;
      if (hw == 0 && lane < 28 && i < 15) *reinterpret_cast<float4*>(scr->kv + j * 1696 + i * 112 + lane * 4) = make_float4(0.f, 0.f, 0.f, 0.f);
      if (hw == 0) TL(248);
      if (part >= 2) mbar_wait_wd(bars + 8 * (FX + 2 * part - 4));
      const int ht = hw * 32 + lane, cpair = part * 1728 + 32 * cg + 4 * (lane & 7) + (lane >> 3);
      if (cg < 30) {
        float2 csum = colsum(wqkv + part * 160 * 1920 + 64 * cg, 1920, hw, hw + 1);
        const uint32_t red = sb + OFF_SCR + lane * 8;
#pragma unroll 1
        for (int h = 0; h < 2; h++) {
          if (hw == h) sts64(red, __float_as_uint(csum.x), __float_as_uint(csum.y));
          named_bar<2, 96>();
          if (hw == h + 1) {
            const float2 a = lds64(red);
            csum.x += a.x;
            csum.y += a.y;
          }
        }
        if (hw == 2) ll_store(scr->cs + cpair, csum.x, csum.y, epoch);
      }
      asm volatile("barrier.cluster.wait.aligned;" ::: "memory");
      if (elect_one()) {
#pragma unroll 1
        for (int n = FWO + 50 * hw; n < FWO + 50 * hw + 50; n += 10) {
#pragma unroll
          for (int e = 0; e < 10; e++) bar_init(n + e, n < AO ? 1 : 8);
        }
        mbar_expect(bars + 8 * (RX + hw), hw == 2 ? 8192 : 10240);
        if (hw == 0) flag_release(scr->flag + (96 + j) * 32, 1u << i);
      }
      __syncwarp();
      if (hw == 2) {
        TL(8);
#pragma unroll 1
        for (int n = lane; n < 40; n += 32) {
          const uint32_t b = *reinterpret_cast<const uint32_t*>(b2 + (n < 32 ? cF + 2 * n : cR + 2 * n - 64));
          sts64(sb + OFF_B2 + n * 8, b << 16, b & 0xffff0000u);
        }
        __syncwarp();
        mbar_wait_wd(bars + 8 * ST1);
        uint4 v[4];
        ll_wait(v, scr->ln1 + 128 * i + lane, 32, epoch);
#pragma unroll
        for (int m = 0; m < 4; m++) {
          const float nm = __uint_as_float(v[m].x) * (-1.f / 640.f);
          const float rstd = rsqrtf(fmaxf(fmaf(-nm, nm, __uint_as_float(v[m].z) * (1.f / 640.f)), 0.f) + 1e-5f);
          sts64(sb + OFF_LN1 + (lane + 32 * m) * 8, __float_as_uint(rstd), __float_as_uint(nm));
        }
      } else {
        const int n = 4 * min(ht, 59);
        int col;
        if (n < 160) col = n + (n < 64 ? 640 + cF : n < 128 ? 1216 + cF : 512 + 640 * role + cR - 16 * q);
        else col = 80 * j + n - 160 + (q ? (n < 224 ? 16 : -64) : 0);
        mbar_wait(bars + 8 * CG);
        uint4 v[8];
        ll_wait2(v, scr->cs + (col >> 1), epoch);
#pragma unroll
        for (int e = 0; e < 2; e++)
          rk1_store(sb + OFF_RK1 + n * 16 + 32 * e,
                    make_float2((__uint_as_float(v[e].x) + __uint_as_float(v[2 + e].x)) + (__uint_as_float(v[4 + e].x) + __uint_as_float(v[6 + e].x)),
                                (__uint_as_float(v[e].z) + __uint_as_float(v[2 + e].z)) + (__uint_as_float(v[4 + e].z) + __uint_as_float(v[6 + e].z))), 0);
        fence_async_smem();
      }
      __syncwarp();
      mbar_arrive_if0(lane, bars + 8 * SIDE, hw == 2 ? 2 : 3);
      if (hw != 1) TL(11 - hw / 2);
      {
        if (hw == 2) {
          flag_wait(scr->flag + (96 + j) * 32, 0xffffu, epoch);
          fence_async_global();
          mbar_wait_wd(bars + 8 * RKV);
          if (elect_one()) {
            asm volatile("cp.reduce.async.bulk.global.shared::cta.bulk_group.add.f32 [%0], [%1], 6720;" ::"l"(scr->kv + j * 1696), "r"(sb + OFF_KVP) : "memory");
            asm volatile("cp.async.bulk.commit_group;" ::: "memory");
            asm volatile("cp.async.bulk.wait_group 0;" ::: "memory");
            flag_release(scr->flag + (104 + j) * 32, 1u << i);
          }
          TL(5);
        } else {
          mbar_wait_wd(bars + 8 * ZK);
#pragma unroll 1
          for (int m = 0; m < 15; m += 3) {
#pragma unroll
            for (int e = 0; e < 3; e++) sts128(sb + OFF_KVB + ((m + e) * 64 + ht) * 16, 0, 0, 0, 0);
          }
        }
        const int d0 = ht < 80 ? (ht * 205) >> 10 : ht - 80, pt = ht - 5 * d0;
        uint32_t da[5];
#pragma unroll
        for (int m = 0; m < 5; m++) {
          const int d = d0 + 16 * m, head = (d * 205) >> 12, n = 20 * head + 4 * pt;
          da[m] = sb + OFF_KVB + d * 16 + (ht < 80 ? (n >> 3) * 1280 + (n & 7) * 2 : (10 + (head >> 1)) * 1280 + (head & 1));
        }
        reg_fence(da);
        named_bar<2, 96>();
        flag_wait(scr->flag + (104 + j) * 32, 0xffffu, epoch);
        if (hw == 0) TL(6);
        if (ht < 80) {
          uint4 v[5];
#pragma unroll
          for (int m = 0; m < 5; m++) v[m] = ll_load(scr->kv + j * 1696 + (ht + 80 * m) * 4);
#pragma unroll
          for (int m = 0; m < 5; m++)
            sts64(da[m], pack2(__uint_as_float(v[m].x), __uint_as_float(v[m].y)), pack2(__uint_as_float(v[m].z), __uint_as_float(v[m].w)));
        } else {
          float z[5];
#pragma unroll
          for (int m = 0; m < 5; m++) asm volatile("ld.relaxed.gpu.global.f32 %0, [%1];" : "=f"(z[m]) : "l"(scr->kv + j * 1696 + 1520 + ht + 16 * m) : "memory");
#pragma unroll
          for (int m = 0; m < 5; m++) {
            const uint32_t zz = pack2(z[m], 0.f) << (16 * (da[m] & 1));
            sts128(da[m] & ~1u, zz, zz, zz, zz);
          }
        }
        fence_async_smem();
        __syncwarp();
        mbar_arrive_if0(lane, bars + 8 * KVB, hw == 2 ? 2 : 3);
        if (hw == 0) TL(7);
      }

      if (hw == 2) {
        if (cg < 24) {
          const float2 d = colsum(w1 + part * 160 * 1536 + 64 * cg, 1536, 0, 3);
          ll_store(scr->cs + 960 + cpair, d.x, d.y, epoch);
        }
        mbar_wait_wd(bars + 8 * (DW + 15));
#pragma unroll 1
        for (int n = lane; n < 96; n += 32)
          rk1_store(sb + OFF_RK1 + n * 32, ll_sum4(scr->cs + 960 + 96 * j + n, epoch), *reinterpret_cast<const uint32_t*>(b1 + 192 * j + 2 * n));
        fence_async_smem();
        __syncwarp();
        mbar_arrive_if0(lane, bars + 8 * SIDE2, 8);
        TL(18);
        const uint32_t eb = bars + 8 * (AF + 12 * ((lane >> 1) & 1) + 1 + (lane & 1));
        uint32_t pm = 15;
        do {
          mbar_wait_wd(__shfl_sync(0xffffffffu, eb, __ffs(pm) - 1));
          const uint32_t ok = mbar_test(eb) & (pm >> lane);
          if (ok) flag_release(scr->flag + (64 + 2 * i + (lane >> 1)) * 32, 0x100u << (8 * (lane & 1) + j));
          pm &= ~__ballot_sync(0xffffffffu, ok);
        } while (pm);
        mbar_wait_wd(bars + 8 * END);
        if (blockIdx.x == 0 && lane == 0) scr->epoch = epoch;
      } else {
        const int s = hw;
#pragma unroll 1
        for (int ph = 0; ph < 3; ph++) {
          const uint32_t ab = bars + 8 * (ph < 2 ? AO + 16 * ph + 8 * s : AF + 12 * s);
          const uint32_t bytes = ph < 2 ? 10240 : 8192;
          uint8_t* gb = scr->act + (ph * 32 + 2 * i + s) * 8 * 24576;
          uint32_t* fl = scr->flag + (ph * 32 + 2 * i + s) * 32;
          const int r = min(lane, 8);
          int cc = r + (r >= j), bit = cc, slot, wb, off = 0;
          if (ph == 0) {
            slot = r;
            wb = s ? DW + r + 1 : AO + 8;
          } else if (ph == 1) {
            slot = (0x0924u >> (2 * r)) & 3;
            wb = r < 3 ? DW + (s ? 15 : 9 + r) : DF + 8 * s + r - 2;
          } else {
            const int uu = (r * 11) >> 5, n = r - 3 * uu;
            cc = 2 * (n + (n >= p)) + q;
            bit = cc + 8 * uu;
            off = uu * 8192;
            slot = r & 3;
            wb = r < 4 ? DF + 8 * s + 7 : DG + 12 * s + r - 1;
          }
          const uint32_t fb = ab + 8 * r + (ph < 2 ? 8 : 24), wbar = bars + 8 * wb;
          const uint32_t dst = sb + (ph ? s * OFF_R1 : 0) + slot * bytes;
          const uint8_t* src = gb + cc * 24576 + off;
          uint32_t pm = ph < 2 ? 0x7fu : 0x1ffu, seen = 0;
          if (pm >> lane & 1) {
            mbar_expect(fb, bytes);
            mbar_arrive(fb, 7);
          }
          __syncwarp();
          mbar_wait(ab);
          if (elect_one()) flag_release(fl, 1u << j);
          __syncwarp();
          TL(44 + 2 * ph + s);
          do {
            const int next = __ffs(pm) - 1;
            if (!(seen >> next & 1)) {
              do seen = __ballot_sync(0xffffffffu, flag_read(fl, epoch) >> bit & 1);
              while (!(seen >> next & 1));
              asm volatile("fence.acquire.gpu;" ::: "memory");
              fence_async_global();
            }
            if (next == 0) TL(52 + 2 * ph + s);
            mbar_wait(__shfl_sync(0xffffffffu, wbar, next));
            const uint32_t ok = mbar_test(wbar) & ((pm & seen) >> lane);
            if (ok) bulk_load(dst, src, bytes, fb);
            pm &= ~__ballot_sync(0xffffffffu, ok);
          } while (pm);
        }
      }
    }
  } else {
    TC(tc4);
    uint32_t epoch;
    asm volatile("ld.relaxed.gpu.global.u32 %0, [%1];" : "=r"(epoch) : "l"(&scr->epoch) : "memory");
    epoch += 1;
    const int s = warp >> 2, w = warp & 3, tid = threadIdx.x & 127, c = lane & 3, g = lane >> 2;
    uint32_t sb_peer;
    asm volatile("mapa.shared::cluster.u32 %0, %1, %2;" : "=r"(sb_peer) : "r"(sb), "r"(q ^ 1));
    const int row0 = 128 * i + 64 * s + 16 * w;
    const uint32_t bs8 = bars + 64 * s, bs12 = bars + 96 * s;
    uint32_t pq[20], hp[20];
    {
      float acc[80];
      const Desc dx = mkdesc(s * 512, 0, 16, 1024, 1);
      const int srow = 16 * j + 2 * warp + (lane >> 4);
      float sm = 0.f, sq = 0.f;
      float4 u;
      auto load_res = [&]() {
        const uint32_t xa = sb + (64 * s + 16 * w + (lane & 15)) * 128;
#pragma unroll
        for (int ks = 0; ks < 5; ks++) {
          const int col = ks < 4 ? cF + 16 * ks : cR;
          ldsm4(xa + (col >> 6) * 16384 + (((((col & 63) >> 3) + (lane >> 4)) ^ (lane & 7)) << 4), hp + 4 * ks);
        }
      };
#pragma unroll
      for (int st = 0; st < 20; st++) {
        if ((st & 1) == 0 && st <= 4) mbar_wait(bars + 8 * (FX + (st >> 1)));
        mbar_wait(bars + 8 * (st < 16 ? RF + st % 5 : FE + st - 16), st < 16 ? (st / 5) & 1 : 0);
        const Desc da = dx + (st >> 1) * 1024 + (st & 1) * 4;
        const Desc db = mkdesc(0, st < 16 ? OFF_RING + (st % 5) * 12288 : (st - 16) * 12288, 4096, 1024, 1);
        wg_fence();
        wgmma_ss<160, 0, 1>(acc, da, db, st != 0);
        wgmma_ss<160, 0, 1>(acc, da + 2, db + 128, 1);
        wg_commit();
        TL0(64 + st);
        if (st == 0) { TL0(0); TS(38, tc4); TS(62, (uint32_t)tl_gt); }
        if (st == 15) asm volatile("barrier.cluster.wait.aligned;" ::: "memory");
        if (st == 1) asm volatile("setmaxnreg.inc.sync.aligned.u32 208;");
        if (st >= 3 && st <= 11 && (st & 1)) {
          const float uu[4] = {u.x, u.y, u.z, u.w};
#pragma unroll
          for (int e = 0; e < 4; e++) {
            const float a = bf_lo(__float_as_uint(uu[e])), b = bf_hi(__float_as_uint(uu[e]));
            sm += a + b;
            sq = fmaf(a, a, fmaf(b, b, sq));
          }
        }
        if (st >= 2 && st <= 10 && (st & 1) == 0) {
          if (st > 4) mbar_wait(bars + 8 * (FX + st - 2));
          if (st > 2) mbar_wait(bars + 8 * (FX + st - 1));
          u = lds128(sb + (st - 2 + ((lane >> 3) & 1)) * 16384 + srow * 128 + (lane & 7) * 16);
        }
        if (st == 11 || st == 12) {
#pragma unroll
          for (int o = st == 11 ? 1 : 4; o < (st == 11 ? 4 : 16); o <<= 1) {
            sm += __shfl_xor_sync(0xffffffffu, sm, o);
            sq += __shfl_xor_sync(0xffffffffu, sq, o);
          }
        }
        if (st == 12) {
          if ((lane & 15) == 0) ll_store(scr->ln1 + 128 * i + srow, sm, sq, epoch);
          TL0(39);
        }
        if (st == 13) mbar_arrive_if0(lane, bars + 8 * CG, 1);
        if (st == 14) mbar_arrive_if0(lane, bars + 8 * ST1, 1);
        if (st == 7 && p < 2) load_res();
        if (st == 8) mbar_arrive_if0(lane, bars + 8 * XF, 1);
        if (st == 16 && p >= 2) load_res();
        if (st > 0) {
          wg_wait<1>();
          if (st <= 16) mbar_arrive_if0(lane, bars + 8 * (RE + (st - 1) % 5), 1);
        }
      }
      TL0(12);
      float accq[40];
      auto q_step = [&](int t) {
        if (t >= 7) mbar_wait(bars + 8 * (FX + 3 + t));
        mbar_wait(bars + 8 * (RF + (t + 1) % 5), ((t + 16) / 5) & 1);
        const Desc da = dx + (t < 7 ? t + 3 : t - 3) * 1024, db = mkdesc(0, OFF_RING + ((t + 1) % 5) * 12288, 4096, 512, 2);
        wg_fence();
#pragma unroll
        for (int ks = 0; ks < 4; ks++) wgmma_ss<80, 0, 1>(accq, da + 2 * ks, db + 64 * ks, 1);
        wg_commit();
        TL0(84 + t);
      };
      mbar_wait(bars + 8 * SIDE);
      float a1[2], a2[2];
      uint32_t rk[2];
#pragma unroll
      for (int r = 0; r < 2; r++) {
        const float2 st = lds64(sb + OFF_LN1 + (64 * s + 16 * w + g + 8 * r) * 8);
        a1[r] = st.x;
        a2[r] = st.x * LOG2E;
        rk[r] = rk1_frag(st.y, 0.f, c);
      }
      wg_fence();
      wgmma_rs<160, 0>(acc, rk[0], rk[1], 0, 0, mkdesc(0, OFF_RK1, 0, 128, 0), 1);
      wg_commit();
      wgmma_rs<80, 0>(accq, rk[0], rk[1], 0, 0, mkdesc(0, OFF_RK1 + 2560, 0, 128, 0), 0);
      q_step(0);
      const int hi = lane >> 4;
      const uint32_t rowoff = sb + (64 * s + 16 * w + (lane & 15)) * 16;
      const uint32_t remoff = sb_peer + (64 * s + 16 * w) * 16 + lane * 4;
      auto put_remote = [&](const uint32_t* r, uint32_t a) {
#pragma unroll
        for (int e = 0; e < 4; e++)
          asm volatile("st.async.shared::cluster.mbarrier::complete_tx::bytes.b32 [%0], %1, [%2];"
                       ::"r"(a + (e >> 1) * 2048 + (e & 1) * 128), "r"(r[e]), "r"(sb_peer + OFF_BAR + 8 * RXK) : "memory");
      };
      const int mF = 2 * (p & 1) - q, g0 = 2 * mF + hi;
      const uint32_t ka = rowoff + g0 * 2048;
      wg_wait<1>();
      reg_fence(acc);
      mbar_arrive_if0(lane, bars + 8 * KD, 1);
      mbar_arrive_remote_if0(lane, sb_peer + OFF_BAR + 8 * PX);
      TL0(1);
      uint32_t r[4], r2[4];
      if (role == 0) {
        ln_pair<true>(acc + 64, a1, a2, r);
        ln_pair<true>(acc + 72, a1, a2, r2);
        mbar_wait_cluster(bars + 8 * PX);
        put_remote(r, remoff + (q ? 0 : 6 * 2048));
        put_remote(r2, remoff + (q ? 2 * 2048 : 8 * 2048));
      } else {
        ln_pair<false>(acc + 64, a1, a2, r);
        ln_pair<false>(acc + 72, a1, a2, r2);
        const uint32_t a = rowoff + (hi + (q ? 17 : 10)) * 2048;
        mbar_wait(bars + 8 * KD);
        stsm4(a, r[0], r[1], r[2], r[3]);
        stsm4(a + 4096, r2[0], r2[1], r2[2], r2[3]);
      }
      q_step(1);
#pragma unroll
      for (int n = 0; n < 4; n++) {
        const int P = n == 0 ? 0 : n == 1 ? 3 : n - 1;
        ln_pair<true>(acc + 8 * P, a1, a2, r);
        ln_pair<false>(acc + 32 + 8 * P, a1, a2, r2);
        if (n == 0) mbar_wait(bars + 8 * KD);
        if (n < 2 && mF == (n ? 2 : -1)) {
          mbar_wait_cluster(bars + 8 * PX);
          put_remote(r, remoff + (n ? 0 : 8 * 2048));
          put_remote(r2, remoff + (n ? 10 * 2048 : 19 * 2048));
        } else {
          stsm4(ka + P * 4096, r[0], r[1], r[2], r[3]);
          stsm4(ka + P * 4096 + (g0 + 2 * P > 4 ? 11 * 2048 : 10 * 2048), r2[0], r2[1], r2[2], r2[3]);
        }
        if (n == 0) {
          wg_wait<1>();
          mbar_arrive_if0(lane, bars + 8 * (RE + 1), 1);
          mbar_arrive_if0(lane, bars + 8 * ZK, 1);
        }
        if (n == 1) q_step(2);
        if (n == 2) {
          wg_wait<1>();
          mbar_arrive_if0(lane, bars + 8 * (RE + 2), 1);
        }
      }
      sts128(rowoff + 15 * 2048, ONES, ONES, ONES, ONES);
      TL0(2);
      mbar_wait_cluster(bars + 8 * RXK);
      fence_async_smem();
      named_bar<1, 256>();
      TL0(3);
      float kv[24];
      {
        const Desc da = mkdesc(s * 640, 0, 128, 2048, 0), db = da + 1280;
        wg_fence();
#pragma unroll
        for (int kk = 0; kk < 8; kk++) wgmma_ss<48, 1, 1>(kv, da + 16 * kk, db + 16 * kk, kk != 0);
        wg_commit();
      }
      wg_wait<1>();
      mbar_arrive_if0(lane, bars + 8 * (RE + 3), 1);
      q_step(3);
      {
        wg_wait<1>();
        reg_fence(kv);
        TL0(4);
#pragma unroll
        for (int hh = 0; hh < 2; hh++) {
          const int r = 16 * w + g + 8 * hh, eb = c - 4 * s - (r < 20 ? 0 : r < 40 ? 10 : 99);
          const uint32_t a = sb + OFF_KVP + (40 * s + r) * 80 + 8 * eb;
#pragma unroll
          for (int tt = 0; tt < 6; tt++)
            asm volatile("{.reg .pred p; setp.lt.u32 p, %3, 10; @p st.shared.v2.f32 [%0], {%1, %2};}"
                         ::"r"(a + 32 * tt), "f"(kv[4 * tt + 2 * hh]), "f"(kv[4 * tt + 2 * hh + 1]), "r"(eb + 4 * tt) : "memory");
          asm volatile("{.reg .pred p; setp.lt.u32 p, %2, 40; @p st.shared.f32 [%0], %1;}"
                       ::"r"(sb + OFF_KVP + 6400 + (40 * s + r) * 4), "f"(s ? kv[2 * hh] : kv[20 + 2 * hh]), "r"(r) : "memory");
        }
        fence_async_smem();
        __syncwarp();
      }
      mbar_arrive_if0(lane, bars + 8 * RKV, 1);
      TL0(9);
#pragma unroll
      for (int t = 4; t < 10; t++) {
        q_step(t);
        wg_wait<1>();
        mbar_arrive_if0(lane, bars + 8 * (RE + t % 5), 1);
      }
      wg_wait<0>();
      reg_fence(accq);
      mbar_arrive_if0(lane, bars + 8 * RE, 1);
      TL0(13);
#pragma unroll
      for (int P = 0; P < 5; P++) ln_pair<true>(accq + 8 * P, a1, a2, pq + 4 * P);
      reg_fence(pq);
      TL0(14);
    }
    const uint32_t rs = sb + s * OFF_R1;
    const uint8_t* gout = scr->act + ((2 * i + s) * 8 + j) * 24576 + 256 * w + 4 * lane;
    const Desc drs = mkdesc(s * (OFF_R1 / 16), 0, 1024, 128, 0);
    float accg[80];
    {
      {
        float o[48];
        wg_fence();
        mbar_wait(bars + 8 * (s ? OM : KVB));
        TL0(15);
#pragma unroll
        for (int ks = 0; ks < 5; ks++)
          wgmma_rs<96, 1>(o, pq[4 * ks], pq[4 * ks + 1], pq[4 * ks + 2], pq[4 * ks + 3], mkdesc(ks < 4 ? 16 * q : -64 * q, OFF_KVB + 256 * ks, 128, 1280, 0), ks != 0);
        wg_commit();
        mbar_arrive_if0(lane | s, bars + 8 * OM, 2);
        wg_wait<0>();
        reg_fence(o);
        float inv[2][4];
#pragma unroll
        for (int hh = 0; hh < 2; hh++)
#pragma unroll
          for (int h = 0; h < 4; h++) inv[hh][h] = rcp(o[40 + 4 * (h >> 1) + 2 * hh + (h & 1)] + 1e-6f);
        if (s) mbar_wait(bars + 8 * AO);
#pragma unroll
        for (int t = 0; t < 10; t++) {
#pragma unroll
          for (int hh = 0; hh < 2; hh++) {
            const float f = t == 2 ? (c < 2 ? inv[hh][0] : inv[hh][1]) : t == 7 ? (c < 2 ? inv[hh][2] : inv[hh][3]) : inv[hh][(8 * t) / 20];
            pq[2 * t + hh] = pack2(o[4 * t + 2 * hh] * f, o[4 * t + 2 * hh + 1] * f);
            stg32(gout + t * 1024 + hh * 128, pq[2 * t + hh]);
          }
        }
        __syncwarp();
        mbar_arrive_if0(lane, bs8 + 8 * AO, 2);
        TLW(16 + s);
      }
      float acc[40];
#pragma unroll
      for (int r = 0; r < 20; r++) { acc[2 * r] = bf_lo(hp[r]); acc[2 * r + 1] = bf_hi(hp[r]); }
      reg_fence(acc);
#pragma unroll
      for (int t = 0; t < 8; t++) {
        mbar_wait(bars + 8 * (FWO + t));
        if (t) mbar_wait(bs8 + 8 * (AO + t));
        TLW(160 + 8 * s + t);
        if (t == 1) TLW(20 + s);
        const Desc da = mkdesc(0, (t - 1) * PAGE, 1024, 128, 0);
        const Desc db = mkdesc(0, 10 * PAGE + (t < 2 ? t ^ 1 : t) * 15360, 5120, 512, 2);
        wg_fence();
#pragma unroll
        for (int ks = 0; ks < 5; ks++) {
          if (t == 0) wgmma_rs<80, 1>(acc, pq[4 * ks], pq[4 * ks + 1], pq[4 * ks + 2], pq[4 * ks + 3], db + 64 * ks, 1);
          else wgmma_ss<80, 0, 1>(acc, da + 128 * ks, db + 64 * ks, 1);
        }
        wg_commit();
        if (t > 1) {
          wg_wait<1>();
          mbar_arrive_if0(lane, bs8 + 8 * (DW + t - 1), 2);
        }
      }
      wg_wait<0>();
      reg_fence(acc);
      mbar_arrive_if0(lane, bs8 + 8 * (DW + 7), 2);
      TLW(22 + s);
#pragma unroll
      for (int r = 0; r < 20; r++) {
        hp[r] = pack2(acc[2 * r], acc[2 * r + 1]);
        stg32(gout + 32 * 8 * 24576 + (r >> 1) * 1024 + (r & 1) * 128, hp[r]);
      }
      __syncwarp();
      mbar_arrive_if0(lane, bs8 + 8 * AH, 2);
      TLW(24 + s);
    }
    float accf[96];
    uint4 hs[4];
    const uint4* hsp = scr->hstat + ((2 * i + s) * 8 + 2 * c) * 64 + 16 * w + g;
    uint32_t rk[2];
    float3 gk[2];
#pragma unroll
    for (int t = 0; t < 8; t++) {
      mbar_wait(bars + 8 * (FW1 + t));
      if (t) mbar_wait(bs8 + 8 * (AH + t));
      TLW(176 + 8 * s + t);
      if (t == 1) TLW(26 + s);
      const Desc da = drs + ((t + 2) % 3) * (PAGE / 16), db = mkdesc(0, (7 + 3 * (t % 5)) * PAGE, 8192, 1024, 1);
      wg_fence();
#pragma unroll
      for (int ks = 0; ks < 5; ks++) {
        const Desc dk = ks < 4 ? db + 128 * ks : mkdesc(0, (7 + 3 * (t % 5)) * PAGE + 24576, 2048, 1024, 1);
        if (t == 0) wgmma_rs<192, 1>(accf, hp[4 * ks], hp[4 * ks + 1], hp[4 * ks + 2], hp[4 * ks + 3], dk, ks != 0);
        else wgmma_ss<192, 0, 1>(accf, da + 128 * ks, dk, 1);
      }
      if (t == 7) wgmma_rs<192, 0>(accf, rk[0], rk[1], 0, 0, mkdesc(0, OFF_RK1, 0, 128, 0), 1);
      wg_commit();
      if (t == 5) {
        while (__any_sync(0xffffffffu, ((hs[0].y ^ epoch) | (hs[0].w ^ epoch) | (hs[1].y ^ epoch) | (hs[1].w ^ epoch) | (hs[2].y ^ epoch) |
                                        (hs[2].w ^ epoch) | (hs[3].y ^ epoch) | (hs[3].w ^ epoch)) != 0)) {
#pragma unroll
          for (int m = 0; m < 4; m++) hs[m] = ll_load(hsp + (m >> 1) * 64 + 8 * (m & 1));
        }
#pragma unroll
        for (int hh = 0; hh < 2; hh++) {
          float sm = __uint_as_float(hs[hh].x) + __uint_as_float(hs[2 + hh].x), sq = __uint_as_float(hs[hh].z) + __uint_as_float(hs[2 + hh].z);
#pragma unroll
          for (int o = 1; o < 4; o <<= 1) {
            sm += __shfl_xor_sync(0xffffffffu, sm, o);
            sq += __shfl_xor_sync(0xffffffffu, sq, o);
          }
          gk[hh].x = sm;
          gk[hh].y = sq;
        }
      }
      if (t == 6) {
        mbar_wait(bars + 8 * SIDE2);
#pragma unroll
        for (int hh = 0; hh < 2; hh++) {
          const float mean = gk[hh].x * (1.f / 640.f), var = fmaxf(fmaf(-mean, mean, gk[hh].y * (1.f / 640.f)), 0.f) + 1e-5f;
          const float a = rsqrtf(var);
          rk[hh] = rk1_frag(-mean, var * a, c);
          gk[hh] = make_float3(0.7978845608028654f * a, 0.7978845608028654f * 0.044715f * a * a * a, 0.5f * a);
        }
      }
      if (t == 0) {
        wg_wait<0>();
        mbar_arrive_if0(lane, bs8 + 8 * DF, 2);
        float sm[2] = {0.f, 0.f}, sq[2] = {0.f, 0.f};
#pragma unroll
        for (int m = 0; m < 10; m++) {
          const float2 b = lds64(sb + OFF_B2 + (8 * m + 2 * c) * 4);
#pragma unroll
          for (int hh = 0; hh < 2; hh++) {
            const float h0 = bf_lo(hp[2 * m + hh]), h1 = bf_hi(hp[2 * m + hh]);
            sm[hh] += h0 + h1;
            sq[hh] = fmaf(h0, h0, fmaf(h1, h1, sq[hh]));
            const float v0 = b.x + h0, v1 = b.y + h1;
            const int e = 4 * m + 2 * hh;
            if (m < 8) { accg[e] = v0; accg[e + 1] = v1; accg[32 + e] = 0.f; accg[33 + e] = 0.f; }
            else { accg[e + 32] = q ? 0.f : v0; accg[e + 33] = q ? 0.f : v1; accg[e + 40] = q ? v0 : 0.f; accg[e + 41] = q ? v1 : 0.f; }
          }
        }
        reg_fence(accg);
#pragma unroll
        for (int o = 1; o < 4; o <<= 1) {
#pragma unroll
          for (int hh = 0; hh < 2; hh++) {
            sm[hh] += __shfl_xor_sync(0xffffffffu, sm[hh], o);
            sq[hh] += __shfl_xor_sync(0xffffffffu, sq[hh], o);
          }
        }
        if (c < 2) ll_store(scr->hstat + ((2 * i + s) * 8 + j) * 64 + 16 * w + g + 8 * c, c ? sm[1] : sm[0], c ? sq[1] : sq[0], epoch);
      } else if (t > 1) {
        wg_wait<1>();
        mbar_arrive_if0(lane, bs8 + 8 * (DF + t - 1), 2);
      }
      if (t == 3) {
#pragma unroll
        for (int m = 0; m < 4; m++) hs[m] = ll_load(hsp + (m >> 1) * 64 + 8 * (m & 1));
      }
    }
    wg_wait<0>();
    reg_fence(accf);
    mbar_arrive_if0(lane, bs8 + 8 * (DF + 7), 2);
    TLW(28 + s);
    uint32_t fp[48];
#pragma unroll
    for (int t = 0; t < 12; t++) {
      if (t < 3) {
#pragma unroll
        for (int e = 16 * t; e < 16 * t + 16; e++) {
          fp[e] = pack2(gelu(accf[2 * e], gk[e & 1]), gelu(accf[2 * e + 1], gk[e & 1]));
          stg32(gout + 64 * 8 * 24576 + (e >> 1) * 1024 + (e & 1) * 128, fp[e]);
        }
        __syncwarp();
        mbar_arrive_if0(lane, bs12 + 8 * (AF + t), 2);
        if (t == 2) TLW(30 + s);
      }
      mbar_wait(bars + 8 * (FW2 + t));
      if (t >= 3) mbar_wait(bs12 + 8 * (AF + t));
      TLW(192 + 12 * s + t);
      if (t == 3) TLW(32 + s);
      const Desc da = drs + ((t + 1) & 3) * 512, db = mkdesc(0, OFF_W2 + ((0x321045 >> (4 * (t % 6))) & 7) * 24576, 8192, 1024, 1);
      wg_fence();
#pragma unroll
      for (int ks = 0; ks < 4; ks++) {
        if (t < 3) wgmma_rs<160, 1>(accg, fp[16 * t + 4 * ks], fp[16 * t + 4 * ks + 1], fp[16 * t + 4 * ks + 2], fp[16 * t + 4 * ks + 3], db + 128 * ks, 1);
        else wgmma_ss<160, 0, 1>(accg, da + 128 * ks, db + 128 * ks, 1);
      }
      wg_commit();
      if (t != 0 && t != 3) {
        wg_wait<1>();
        mbar_arrive_if0(lane, bs12 + 8 * (DG + t - 1), 2);
        if (t == 7) mbar_arrive_remote_if0(lane, sb_peer + OFF_BAR + 8 * PF);
      }
      if (t == 2) {
        wg_wait<0>();
        mbar_arrive_if0(lane, bs12 + 8 * (DG + 2), 2);
      }
    }
    mbar_wait_cluster(bars + 8 * PF);
    wg_wait<0>();
    reg_fence(accg);
    mbar_arrive_if0(lane, bs12 + 8 * (DG + 11), 2);
    TLW(34 + s);
    {
      const uint32_t buf = OFF_W2 + 5 * 24576 + s * PAGE + tid * 16;
#pragma unroll
      for (int e = 0; e < 8; e++) {
        const float a = accg[64 + e], b = accg[72 + e];
        accg[64 + e] = q ? a : b;
        accg[72 + e] = q ? b : a;
      }
#pragma unroll
      for (int m = 0; m < 5; m++) {
        const float* a = accg + 32 + 8 * m;
        asm volatile("st.async.shared::cluster.mbarrier::complete_tx::bytes.v4.b32 [%0], {%1,%2,%3,%4}, [%5];"
                     ::"r"(sb_peer + buf + m * 2048), "r"(pack2(a[0], a[1])), "r"(pack2(a[2], a[3])), "r"(pack2(a[4], a[5])),
                     "r"(pack2(a[6], a[7])), "r"(sb_peer + OFF_BAR + 8 * (RX + s)) : "memory");
      }
      TLW(58 + s);
      mbar_wait(bs12 + 8 * (DG + 11));
      mbar_wait_cluster(bars + 8 * (RX + s));
      TLW(60 + s);
      float4 rx[5];
#pragma unroll
      for (int m = 0; m < 5; m++) rx[m] = lds128(sb + buf + m * 2048);
      const uint32_t stg = rs + w * 2816;
      const uint32_t sa = stg + (lane & 15) * 176 + (lane >> 4) * 16;
#pragma unroll
      for (int ks = 0; ks < 5; ks++) {
        const uint32_t u[4] = {__float_as_uint(rx[ks].x), __float_as_uint(rx[ks].y), __float_as_uint(rx[ks].z), __float_as_uint(rx[ks].w)};
        const float* a = accg + (ks < 4 ? 8 * ks : 72);
        stsm4(sa + ks * 32, pack2(a[0] + bf_lo(u[0]), a[1] + bf_hi(u[0])), pack2(a[2] + bf_lo(u[1]), a[3] + bf_hi(u[1])),
              pack2(a[4] + bf_lo(u[2]), a[5] + bf_hi(u[2])), pack2(a[6] + bf_lo(u[3]), a[7] + bf_hi(u[3])));
      }
      __syncwarp();
#pragma unroll
      for (int m = 0; m < 4; m++) rx[m] = lds128(stg + (4 * m + (lane >> 3)) * 176 + (lane & 7) * 16);
      rx[4] = lds128(stg + (lane >> 1) * 176 + 128 + (lane & 1) * 16);
      __nv_bfloat16* outp = out + (row0 + (lane >> 3)) * 640 + cF + (lane & 7) * 8;
#pragma unroll
      for (int m = 0; m < 4; m++) *reinterpret_cast<float4*>(outp + m * 4 * 640) = rx[m];
      *reinterpret_cast<float4*>(out + (row0 + (lane >> 1)) * 640 + cR + (lane & 1) * 8) = rx[4];
    }
    mbar_arrive_if0(lane, bars + 8 * END, 1);
    TLW(36 + s);
  }
}

typedef CUresult (*EncodeFn)(CUtensorMap*, CUtensorMapDataType, cuuint32_t, void*, const cuuint64_t*, const cuuint64_t*,
                             const cuuint32_t*, const cuuint32_t*, CUtensorMapInterleave, CUtensorMapSwizzle,
                             CUtensorMapL2promotion, CUtensorMapFloatOOBfill);

void make_map(EncodeFn enc, CUtensorMap* tm, const void* base, int rows, int cols, int box_rows, int box_cols, int group, int natom,
              CUtensorMapSwizzle sw) {
  const cuuint64_t dims[3] = {(cuuint64_t)(natom ? group : cols), (cuuint64_t)rows, (cuuint64_t)(cols / group)};
  const cuuint64_t strides[2] = {(cuuint64_t)cols * 2, (cuuint64_t)group * 2};
  const cuuint32_t box[3] = {(cuuint32_t)box_cols, (cuuint32_t)box_rows, (cuuint32_t)natom}, es[3] = {1, 1, 1};
  enc(tm, CU_TENSOR_MAP_DATA_TYPE_BFLOAT16, natom ? 3 : 2, const_cast<void*>(base), dims, strides, box, es,
      CU_TENSOR_MAP_INTERLEAVE_NONE, sw, CU_TENSOR_MAP_L2_PROMOTION_L2_128B, CU_TENSOR_MAP_FLOAT_OOB_FILL_NONE);
}

}

extern "C" void kernel_launch(void* const* d_in, const int* in_sizes, int n_in, void* d_out, int out_size) {
  const __nv_bfloat16* x = (const __nv_bfloat16*)d_in[0];
  const __nv_bfloat16* wqkv = (const __nv_bfloat16*)d_in[1];
  const __nv_bfloat16* wo = (const __nv_bfloat16*)d_in[2];
  const __nv_bfloat16* w1 = (const __nv_bfloat16*)d_in[4];
  const __nv_bfloat16* b1 = (const __nv_bfloat16*)d_in[5];
  const __nv_bfloat16* w2 = (const __nv_bfloat16*)d_in[6];
  const __nv_bfloat16* b2 = (const __nv_bfloat16*)d_in[7];

  void* fn = nullptr;
  cudaDriverEntryPointQueryResult qr;
  cudaGetDriverEntryPoint("cuTensorMapEncodeTiled", &fn, cudaEnableDefault, &qr);
  EncodeFn enc = (EncodeFn)fn;
  const CUtensorMapSwizzle S128 = CU_TENSOR_MAP_SWIZZLE_128B, S64 = CU_TENSOR_MAP_SWIZZLE_64B;
  Maps maps;
  make_map(enc, &maps.m[M_X], x, 2048, 640, 128, 64, 64, 0, S128);
  make_map(enc, &maps.m[M_KVF], wqkv, 640, 1920, 32, 64, 640, 2, S128);
  make_map(enc, &maps.m[M_KVH], wqkv, 640, 1920, 32, 32, 64, 0, S128);
  make_map(enc, &maps.m[M_Q2], wqkv, 640, 1920, 64, 32, 32, 2, S64);
  make_map(enc, &maps.m[M_QR], wqkv, 640, 1920, 64, 16, 64, 0, S64);
  make_map(enc, &maps.m[M_WO2], wo, 640, 640, 80, 32, 32, 2, S64);
  make_map(enc, &maps.m[M_WOR], wo, 640, 640, 80, 16, 64, 0, S64);
  make_map(enc, &maps.m[M_W1], w1, 640, 1536, 64, 64, 64, 3, S128);
  make_map(enc, &maps.m[M_W1R], w1, 640, 1536, 16, 64, 64, 3, S128);
  make_map(enc, &maps.m[M_W2F], w2, 1536, 640, 64, 64, 64, 0, S128);
  make_map(enc, &maps.m[M_W2H], w2, 1536, 640, 64, 32, 64, 0, S128);
  cudaFuncSetAttribute(fused_block_kernel, cudaFuncAttributeMaxDynamicSharedMemorySize, SMEM_BYTES);
  void* scr = nullptr;
  cudaGetSymbolAddress(&scr, g_scratch);
  fused_block_kernel<<<128, 384, SMEM_BYTES>>>((Scratch*)scr, wqkv, wo, w1, w2, b2, b1, (__nv_bfloat16*)d_out, maps);
}
```

```cpp
#include <cuda_runtime.h>
#include <cuda_bf16.h>
#include <cuda.h>
#include <stdint.h>

namespace {

struct Desc { uint32_t base, off, hi; };
__device__ __forceinline__ Desc operator+(Desc d, uint32_t o) { return Desc{d.base, d.off + o, d.hi}; }
template <int TA, int TB> __device__ __forceinline__ void wgmma_ss_n48(float (&d)[24], Desc a, Desc b, int sc) {
  asm volatile("{.reg .pred p; .reg .b32 t, u; .reg .b64 da, db; setp.ne.b32 p, %30, 0; add.u32 t, %24, %25; mov.b64 da, {t, %26}; add.u32 u, %27, %28; mov.b64 db, {u, %29};"
    "wgmma.mma_async.sync.aligned.m64n48k16.f32.bf16.bf16 {%0,%1,%2,%3,%4,%5,%6,%7,%8,%9,%10,%11,%12,%13,%14,%15,%16,%17,%18,%19,%20,%21,%22,%23}, da, db, p, 1, 1, %31, %32;}"
    : "+f"(d[0]),"+f"(d[1]),"+f"(d[2]),"+f"(d[3]),"+f"(d[4]),"+f"(d[5]),"+f"(d[6]),"+f"(d[7]),"+f"(d[8]),"+f"(d[9]),"+f"(d[10]),"+f"(d[11]),"+f"(d[12]),"+f"(d[13]),"+f"(d[14]),"+f"(d[15]),"+f"(d[16]),"+f"(d[17]),"+f"(d[18]),"+f"(d[19]),"+f"(d[20]),"+f"(d[21]),"+f"(d[22]),"+f"(d[23])
    : "r"(a.base), "r"(a.off), "r"(a.hi), "r"(b.base), "r"(b.off), "r"(b.hi), "r"(sc), "n"(TA), "n"(TB));
}
template <int TA, int TB> __device__ __forceinline__ void wgmma_ss_n80(float (&d)[40], Desc a, Desc b, int sc) {
  asm volatile("{.reg .pred p; .reg .b32 t, u; .reg .b64 da, db; setp.ne.b32 p, %46, 0; add.u32 t, %40, %41; mov.b64 da, {t, %42}; add.u32 u, %43, %44; mov.b64 db, {u, %45};"
    "wgmma.mma_async.sync.aligned.m64n80k16.f32.bf16.bf16 {%0,%1,%2,%3,%4,%5,%6,%7,%8,%9,%10,%11,%12,%13,%14,%15,%16,%17,%18,%19,%20,%21,%22,%23,%24,%25,%26,%27,%28,%29,%30,%31,%32,%33,%34,%35,%36,%37,%38,%39}, da, db, p, 1, 1, %47, %48;}"
    : "+f"(d[0]),"+f"(d[1]),"+f"(d[2]),"+f"(d[3]),"+f"(d[4]),"+f"(d[5]),"+f"(d[6]),"+f"(d[7]),"+f"(d[8]),"+f"(d[9]),"+f"(d[10]),"+f"(d[11]),"+f"(d[12]),"+f"(d[13]),"+f"(d[14]),"+f"(d[15]),"+f"(d[16]),"+f"(d[17]),"+f"(d[18]),"+f"(d[19]),"+f"(d[20]),"+f"(d[21]),"+f"(d[22]),"+f"(d[23]),"+f"(d[24]),"+f"(d[25]),"+f"(d[26]),"+f"(d[27]),"+f"(d[28]),"+f"(d[29]),"+f"(d[30]),"+f"(d[31]),"+f"(d[32]),"+f"(d[33]),"+f"(d[34]),"+f"(d[35]),"+f"(d[36]),"+f"(d[37]),"+f"(d[38]),"+f"(d[39])
    : "r"(a.base), "r"(a.off), "r"(a.hi), "r"(b.base), "r"(b.off), "r"(b.hi), "r"(sc), "n"(TA), "n"(TB));
}
template <int TA, int TB> __device__ __forceinline__ void wgmma_ss_n160(float (&d)[80], Desc a, Desc b, int sc) {
  asm volatile("{.reg .pred p; .reg .b32 t, u; .reg .b64 da, db; setp.ne.b32 p, %86, 0; add.u32 t, %80, %81; mov.b64 da, {t, %82}; add.u32 u, %83, %84; mov.b64 db, {u, %85};"
    "wgmma.mma_async.sync.aligned.m64n160k16.f32.bf16.bf16 {%0,%1,%2,%3,%4,%5,%6,%7,%8,%9,%10,%11,%12,%13,%14,%15,%16,%17,%18,%19,%20,%21,%22,%23,%24,%25,%26,%27,%28,%29,%30,%31,%32,%33,%34,%35,%36,%37,%38,%39,%40,%41,%42,%43,%44,%45,%46,%47,%48,%49,%50,%51,%52,%53,%54,%55,%56,%57,%58,%59,%60,%61,%62,%63,%64,%65,%66,%67,%68,%69,%70,%71,%72,%73,%74,%75,%76,%77,%78,%79}, da, db, p, 1, 1, %87, %88;}"
    : "+f"(d[0]),"+f"(d[1]),"+f"(d[2]),"+f"(d[3]),"+f"(d[4]),"+f"(d[5]),"+f"(d[6]),"+f"(d[7]),"+f"(d[8]),"+f"(d[9]),"+f"(d[10]),"+f"(d[11]),"+f"(d[12]),"+f"(d[13]),"+f"(d[14]),"+f"(d[15]),"+f"(d[16]),"+f"(d[17]),"+f"(d[18]),"+f"(d[19]),"+f"(d[20]),"+f"(d[21]),"+f"(d[22]),"+f"(d[23]),"+f"(d[24]),"+f"(d[25]),"+f"(d[26]),"+f"(d[27]),"+f"(d[28]),"+f"(d[29]),"+f"(d[30]),"+f"(d[31]),"+f"(d[32]),"+f"(d[33]),"+f"(d[34]),"+f"(d[35]),"+f"(d[36]),"+f"(d[37]),"+f"(d[38]),"+f"(d[39]),"+f"(d[40]),"+f"(d[41]),"+f"(d[42]),"+f"(d[43]),"+f"(d[44]),"+f"(d[45]),"+f"(d[46]),"+f"(d[47]),"+f"(d[48]),"+f"(d[49]),"+f"(d[50]),"+f"(d[51]),"+f"(d[52]),"+f"(d[53]),"+f"(d[54]),"+f"(d[55]),"+f"(d[56]),"+f"(d[57]),"+f"(d[58]),"+f"(d[59]),"+f"(d[60]),"+f"(d[61]),"+f"(d[62]),"+f"(d[63]),"+f"(d[64]),"+f"(d[65]),"+f"(d[66]),"+f"(d[67]),"+f"(d[68]),"+f"(d[69]),"+f"(d[70]),"+f"(d[71]),"+f"(d[72]),"+f"(d[73]),"+f"(d[74]),"+f"(d[75]),"+f"(d[76]),"+f"(d[77]),"+f"(d[78]),"+f"(d[79])
    : "r"(a.base), "r"(a.off), "r"(a.hi), "r"(b.base), "r"(b.off), "r"(b.hi), "r"(sc), "n"(TA), "n"(TB));
}
template <int TA, int TB> __device__ __forceinline__ void wgmma_ss_n192(float (&d)[96], Desc a, Desc b, int sc) {
  asm volatile("{.reg .pred p; .reg .b32 t, u; .reg .b64 da, db; setp.ne.b32 p, %102, 0; add.u32 t, %96, %97; mov.b64 da, {t, %98}; add.u32 u, %99, %100; mov.b64 db, {u, %101};"
    "wgmma.mma_async.sync.aligned.m64n192k16.f32.bf16.bf16 {%0,%1,%2,%3,%4,%5,%6,%7,%8,%9,%10,%11,%12,%13,%14,%15,%16,%17,%18,%19,%20,%21,%22,%23,%24,%25,%26,%27,%28,%29,%30,%31,%32,%33,%34,%35,%36,%37,%38,%39,%40,%41,%42,%43,%44,%45,%46,%47,%48,%49,%50,%51,%52,%53,%54,%55,%56,%57,%58,%59,%60,%61,%62,%63,%64,%65,%66,%67,%68,%69,%70,%71,%72,%73,%74,%75,%76,%77,%78,%79,%80,%81,%82,%83,%84,%85,%86,%87,%88,%89,%90,%91,%92,%93,%94,%95}, da, db, p, 1, 1, %103, %104;}"
    : "+f"(d[0]),"+f"(d[1]),"+f"(d[2]),"+f"(d[3]),"+f"(d[4]),"+f"(d[5]),"+f"(d[6]),"+f"(d[7]),"+f"(d[8]),"+f"(d[9]),"+f"(d[10]),"+f"(d[11]),"+f"(d[12]),"+f"(d[13]),"+f"(d[14]),"+f"(d[15]),"+f"(d[16]),"+f"(d[17]),"+f"(d[18]),"+f"(d[19]),"+f"(d[20]),"+f"(d[21]),"+f"(d[22]),"+f"(d[23]),"+f"(d[24]),"+f"(d[25]),"+f"(d[26]),"+f"(d[27]),"+f"(d[28]),"+f"(d[29]),"+f"(d[30]),"+f"(d[31]),"+f"(d[32]),"+f"(d[33]),"+f"(d[34]),"+f"(d[35]),"+f"(d[36]),"+f"(d[37]),"+f"(d[38]),"+f"(d[39]),"+f"(d[40]),"+f"(d[41]),"+f"(d[42]),"+f"(d[43]),"+f"(d[44]),"+f"(d[45]),"+f"(d[46]),"+f"(d[47]),"+f"(d[48]),"+f"(d[49]),"+f"(d[50]),"+f"(d[51]),"+f"(d[52]),"+f"(d[53]),"+f"(d[54]),"+f"(d[55]),"+f"(d[56]),"+f"(d[57]),"+f"(d[58]),"+f"(d[59]),"+f"(d[60]),"+f"(d[61]),"+f"(d[62]),"+f"(d[63]),"+f"(d[64]),"+f"(d[65]),"+f"(d[66]),"+f"(d[67]),"+f"(d[68]),"+f"(d[69]),"+f"(d[70]),"+f"(d[71]),"+f"(d[72]),"+f"(d[73]),"+f"(d[74]),"+f"(d[75]),"+f"(d[76]),"+f"(d[77]),"+f"(d[78]),"+f"(d[79]),"+f"(d[80]),"+f"(d[81]),"+f"(d[82]),"+f"(d[83]),"+f"(d[84]),"+f"(d[85]),"+f"(d[86]),"+f"(d[87]),"+f"(d[88]),"+f"(d[89]),"+f"(d[90]),"+f"(d[91]),"+f"(d[92]),"+f"(d[93]),"+f"(d[94]),"+f"(d[95])
    : "r"(a.base), "r"(a.off), "r"(a.hi), "r"(b.base), "r"(b.off), "r"(b.hi), "r"(sc), "n"(TA), "n"(TB));
}
template <int TB> __device__ __forceinline__ void wgmma_rs_n80(float (&d)[40], uint32_t a0, uint32_t a1, uint32_t a2, uint32_t a3, Desc b, int sc) {
  asm volatile("{.reg .pred p; .reg .b32 u; .reg .b64 db; setp.ne.b32 p, %47, 0; add.u32 u, %44, %45; mov.b64 db, {u, %46};"
    "wgmma.mma_async.sync.aligned.m64n80k16.f32.bf16.bf16 {%0,%1,%2,%3,%4,%5,%6,%7,%8,%9,%10,%11,%12,%13,%14,%15,%16,%17,%18,%19,%20,%21,%22,%23,%24,%25,%26,%27,%28,%29,%30,%31,%32,%33,%34,%35,%36,%37,%38,%39}, {%40,%41,%42,%43}, db, p, 1, 1, %48;}"
    : "+f"(d[0]),"+f"(d[1]),"+f"(d[2]),"+f"(d[3]),"+f"(d[4]),"+f"(d[5]),"+f"(d[6]),"+f"(d[7]),"+f"(d[8]),"+f"(d[9]),"+f"(d[10]),"+f"(d[11]),"+f"(d[12]),"+f"(d[13]),"+f"(d[14]),"+f"(d[15]),"+f"(d[16]),"+f"(d[17]),"+f"(d[18]),"+f"(d[19]),"+f"(d[20]),"+f"(d[21]),"+f"(d[22]),"+f"(d[23]),"+f"(d[24]),"+f"(d[25]),"+f"(d[26]),"+f"(d[27]),"+f"(d[28]),"+f"(d[29]),"+f"(d[30]),"+f"(d[31]),"+f"(d[32]),"+f"(d[33]),"+f"(d[34]),"+f"(d[35]),"+f"(d[36]),"+f"(d[37]),"+f"(d[38]),"+f"(d[39])
    : "r"(a0), "r"(a1), "r"(a2), "r"(a3), "r"(b.base), "r"(b.off), "r"(b.hi), "r"(sc), "n"(TB));
}
template <int TB> __device__ __forceinline__ void wgmma_rs_n96(float (&d)[48], uint32_t a0, uint32_t a1, uint32_t a2, uint32_t a3, Desc b, int sc) {
  asm volatile("{.reg .pred p; .reg .b32 u; .reg .b64 db; setp.ne.b32 p, %55, 0; add.u32 u, %52, %53; mov.b64 db, {u, %54};"
    "wgmma.mma_async.sync.aligned.m64n96k16.f32.bf16.bf16 {%0,%1,%2,%3,%4,%5,%6,%7,%8,%9,%10,%11,%12,%13,%14,%15,%16,%17,%18,%19,%20,%21,%22,%23,%24,%25,%26,%27,%28,%29,%30,%31,%32,%33,%34,%35,%36,%37,%38,%39,%40,%41,%42,%43,%44,%45,%46,%47}, {%48,%49,%50,%51}, db, p, 1, 1, %56;}"
    : "+f"(d[0]),"+f"(d[1]),"+f"(d[2]),"+f"(d[3]),"+f"(d[4]),"+f"(d[5]),"+f"(d[6]),"+f"(d[7]),"+f"(d[8]),"+f"(d[9]),"+f"(d[10]),"+f"(d[11]),"+f"(d[12]),"+f"(d[13]),"+f"(d[14]),"+f"(d[15]),"+f"(d[16]),"+f"(d[17]),"+f"(d[18]),"+f"(d[19]),"+f"(d[20]),"+f"(d[21]),"+f"(d[22]),"+f"(d[23]),"+f"(d[24]),"+f"(d[25]),"+f"(d[26]),"+f"(d[27]),"+f"(d[28]),"+f"(d[29]),"+f"(d[30]),"+f"(d[31]),"+f"(d[32]),"+f"(d[33]),"+f"(d[34]),"+f"(d[35]),"+f"(d[36]),"+f"(d[37]),"+f"(d[38]),"+f"(d[39]),"+f"(d[40]),"+f"(d[41]),"+f"(d[42]),"+f"(d[43]),"+f"(d[44]),"+f"(d[45]),"+f"(d[46]),"+f"(d[47])
    : "r"(a0), "r"(a1), "r"(a2), "r"(a3), "r"(b.base), "r"(b.off), "r"(b.hi), "r"(sc), "n"(TB));
}
template <int TB> __device__ __forceinline__ void wgmma_rs_n160(float (&d)[80], uint32_t a0, uint32_t a1, uint32_t a2, uint32_t a3, Desc b, int sc) {
  asm volatile("{.reg .pred p; .reg .b32 u; .reg .b64 db; setp.ne.b32 p, %87, 0; add.u32 u, %84, %85; mov.b64 db, {u, %86};"
    "wgmma.mma_async.sync.aligned.m64n160k16.f32.bf16.bf16 {%0,%1,%2,%3,%4,%5,%6,%7,%8,%9,%10,%11,%12,%13,%14,%15,%16,%17,%18,%19,%20,%21,%22,%23,%24,%25,%26,%27,%28,%29,%30,%31,%32,%33,%34,%35,%36,%37,%38,%39,%40,%41,%42,%43,%44,%45,%46,%47,%48,%49,%50,%51,%52,%53,%54,%55,%56,%57,%58,%59,%60,%61,%62,%63,%64,%65,%66,%67,%68,%69,%70,%71,%72,%73,%74,%75,%76,%77,%78,%79}, {%80,%81,%82,%83}, db, p, 1, 1, %88;}"
    : "+f"(d[0]),"+f"(d[1]),"+f"(d[2]),"+f"(d[3]),"+f"(d[4]),"+f"(d[5]),"+f"(d[6]),"+f"(d[7]),"+f"(d[8]),"+f"(d[9]),"+f"(d[10]),"+f"(d[11]),"+f"(d[12]),"+f"(d[13]),"+f"(d[14]),"+f"(d[15]),"+f"(d[16]),"+f"(d[17]),"+f"(d[18]),"+f"(d[19]),"+f"(d[20]),"+f"(d[21]),"+f"(d[22]),"+f"(d[23]),"+f"(d[24]),"+f"(d[25]),"+f"(d[26]),"+f"(d[27]),"+f"(d[28]),"+f"(d[29]),"+f"(d[30]),"+f"(d[31]),"+f"(d[32]),"+f"(d[33]),"+f"(d[34]),"+f"(d[35]),"+f"(d[36]),"+f"(d[37]),"+f"(d[38]),"+f"(d[39]),"+f"(d[40]),"+f"(d[41]),"+f"(d[42]),"+f"(d[43]),"+f"(d[44]),"+f"(d[45]),"+f"(d[46]),"+f"(d[47]),"+f"(d[48]),"+f"(d[49]),"+f"(d[50]),"+f"(d[51]),"+f"(d[52]),"+f"(d[53]),"+f"(d[54]),"+f"(d[55]),"+f"(d[56]),"+f"(d[57]),"+f"(d[58]),"+f"(d[59]),"+f"(d[60]),"+f"(d[61]),"+f"(d[62]),"+f"(d[63]),"+f"(d[64]),"+f"(d[65]),"+f"(d[66]),"+f"(d[67]),"+f"(d[68]),"+f"(d[69]),"+f"(d[70]),"+f"(d[71]),"+f"(d[72]),"+f"(d[73]),"+f"(d[74]),"+f"(d[75]),"+f"(d[76]),"+f"(d[77]),"+f"(d[78]),"+f"(d[79])
    : "r"(a0), "r"(a1), "r"(a2), "r"(a3), "r"(b.base), "r"(b.off), "r"(b.hi), "r"(sc), "n"(TB));
}
template <int TB> __device__ __forceinline__ void wgmma_rs_n192(float (&d)[96], uint32_t a0, uint32_t a1, uint32_t a2, uint32_t a3, Desc b, int sc) {
  asm volatile("{.reg .pred p; .reg .b32 u; .reg .b64 db; setp.ne.b32 p, %103, 0; add.u32 u, %100, %101; mov.b64 db, {u, %102};"
    "wgmma.mma_async.sync.aligned.m64n192k16.f32.bf16.bf16 {%0,%1,%2,%3,%4,%5,%6,%7,%8,%9,%10,%11,%12,%13,%14,%15,%16,%17,%18,%19,%20,%21,%22,%23,%24,%25,%26,%27,%28,%29,%30,%31,%32,%33,%34,%35,%36,%37,%38,%39,%40,%41,%42,%43,%44,%45,%46,%47,%48,%49,%50,%51,%52,%53,%54,%55,%56,%57,%58,%59,%60,%61,%62,%63,%64,%65,%66,%67,%68,%69,%70,%71,%72,%73,%74,%75,%76,%77,%78,%79,%80,%81,%82,%83,%84,%85,%86,%87,%88,%89,%90,%91,%92,%93,%94,%95}, {%96,%97,%98,%99}, db, p, 1, 1, %104;}"
    : "+f"(d[0]),"+f"(d[1]),"+f"(d[2]),"+f"(d[3]),"+f"(d[4]),"+f"(d[5]),"+f"(d[6]),"+f"(d[7]),"+f"(d[8]),"+f"(d[9]),"+f"(d[10]),"+f"(d[11]),"+f"(d[12]),"+f"(d[13]),"+f"(d[14]),"+f"(d[15]),"+f"(d[16]),"+f"(d[17]),"+f"(d[18]),"+f"(d[19]),"+f"(d[20]),"+f"(d[21]),"+f"(d[22]),"+f"(d[23]),"+f"(d[24]),"+f"(d[25]),"+f"(d[26]),"+f"(d[27]),"+f"(d[28]),"+f"(d[29]),"+f"(d[30]),"+f"(d[31]),"+f"(d[32]),"+f"(d[33]),"+f"(d[34]),"+f"(d[35]),"+f"(d[36]),"+f"(d[37]),"+f"(d[38]),"+f"(d[39]),"+f"(d[40]),"+f"(d[41]),"+f"(d[42]),"+f"(d[43]),"+f"(d[44]),"+f"(d[45]),"+f"(d[46]),"+f"(d[47]),"+f"(d[48]),"+f"(d[49]),"+f"(d[50]),"+f"(d[51]),"+f"(d[52]),"+f"(d[53]),"+f"(d[54]),"+f"(d[55]),"+f"(d[56]),"+f"(d[57]),"+f"(d[58]),"+f"(d[59]),"+f"(d[60]),"+f"(d[61]),"+f"(d[62]),"+f"(d[63]),"+f"(d[64]),"+f"(d[65]),"+f"(d[66]),"+f"(d[67]),"+f"(d[68]),"+f"(d[69]),"+f"(d[70]),"+f"(d[71]),"+f"(d[72]),"+f"(d[73]),"+f"(d[74]),"+f"(d[75]),"+f"(d[76]),"+f"(d[77]),"+f"(d[78]),"+f"(d[79]),"+f"(d[80]),"+f"(d[81]),"+f"(d[82]),"+f"(d[83]),"+f"(d[84]),"+f"(d[85]),"+f"(d[86]),"+f"(d[87]),"+f"(d[88]),"+f"(d[89]),"+f"(d[90]),"+f"(d[91]),"+f"(d[92]),"+f"(d[93]),"+f"(d[94]),"+f"(d[95])
    : "r"(a0), "r"(a1), "r"(a2), "r"(a3), "r"(b.base), "r"(b.off), "r"(b.hi), "r"(sc), "n"(TB));
}
template <int N, int TA, int TB> __device__ __forceinline__ void wgmma_ss(float (&d)[N / 2], Desc a, Desc b, int sc) {
  if constexpr (N == 48) wgmma_ss_n48<TA, TB>(d, a, b, sc);
  else if constexpr (N == 80) wgmma_ss_n80<TA, TB>(d, a, b, sc);
  else if constexpr (N == 160) wgmma_ss_n160<TA, TB>(d, a, b, sc);
  else if constexpr (N == 192) wgmma_ss_n192<TA, TB>(d, a, b, sc);
}
template <int N, int TB> __device__ __forceinline__ void wgmma_rs(float (&d)[N / 2], uint32_t a0, uint32_t a1, uint32_t a2, uint32_t a3, Desc b, int sc) {
  if constexpr (N == 80) wgmma_rs_n80<TB>(d, a0, a1, a2, a3, b, sc);
  else if constexpr (N == 96) wgmma_rs_n96<TB>(d, a0, a1, a2, a3, b, sc);
  else if constexpr (N == 160) wgmma_rs_n160<TB>(d, a0, a1, a2, a3, b, sc);
  else if constexpr (N == 192) wgmma_rs_n192<TB>(d, a0, a1, a2, a3, b, sc);
}

constexpr uint32_t SMEM_BASE = 1024;
constexpr uint32_t PAGE = 10240;
constexpr uint32_t OFF_RING = 16 * PAGE;
constexpr uint32_t OFF_KVB = 50176;
constexpr uint32_t OFF_KVP = 43008;
constexpr uint32_t OFF_R1 = 35840;
constexpr uint32_t OFF_MISC = 22 * PAGE;
constexpr uint32_t OFF_W2 = OFF_MISC - 6 * 24576;
constexpr uint32_t OFF_BAR = OFF_MISC;
constexpr uint32_t OFF_LN1 = OFF_MISC + 1920;
constexpr uint32_t OFF_RK1 = OFF_MISC + 2944;
constexpr uint32_t OFF_B2 = OFF_MISC + 1600;
constexpr uint32_t OFF_SCR = OFF_MISC + 6784;
constexpr uint32_t SMEM_BYTES = OFF_MISC + 7040;

enum : int {
  RF = 0, FX = 5, FE = 18, RX = 22, RXK = 24,
  RE = 25, PX = 30, PF = 31, SIDE = 32, ZK = 33, RKV = 34, ST1 = 35, XF = 36, KD = 37, CG = 38,
  FWO = 40, FW1 = 48, FW2 = 56,
  AO = 70, AH = 86, AF = 102,
  DW = 126, DF = 142, DG = 158,
  SIDE2 = 185, KVB = 186, END = 187, OM = 188
};

struct __align__(128) Scratch {
  uint8_t act[3 * 32 * 8 * 24576];
  uint4 ln1[2048];
  uint4 cs[4 * 1728];
  uint4 hstat[32 * 8 * 64];
  float kv[8 * 1696];
  uint32_t flag[(3 * 32 + 16) * 32];
  uint32_t epoch;
};
__device__ Scratch g_scratch;

struct Maps { CUtensorMap m[11]; };
enum : int { M_X, M_KVF, M_KVH, M_Q2, M_QR, M_WO2, M_WOR, M_W1, M_W1R, M_W2F, M_W2H };

#define TL(id)
#define TLW(id)
#define TL0(id)
#define TL1(id)
#define TC(v)
#define TS(id, v)

constexpr int SPIN_LIMIT = 1 << 19;

__device__ __forceinline__ bool elect_one() {
  uint32_t p;
  asm volatile("{.reg .pred P; elect.sync _|P, 0xffffffff; selp.u32 %0,1,0,P;}" : "=r"(p));
  return p;
}
__device__ __forceinline__ void mbar_wait(uint32_t bar, uint32_t parity = 0) {
  asm volatile("{.reg .pred p;\nW: mbarrier.try_wait.parity.shared::cta.b64 p, [%0], %1;\n@!p bra W;}" ::"r"(bar), "r"(parity) : "memory");
}
__device__ __forceinline__ void mbar_wait_cluster(uint32_t bar) {
  asm volatile("{.reg .pred p;\nW: mbarrier.try_wait.parity.acquire.cluster.shared::cta.b64 p, [%0], 0;\n@!p bra W;}" ::"r"(bar) : "memory");
}
__device__ __forceinline__ void mbar_wait_wd(uint32_t bar) {
  asm volatile("{.reg .pred p; .reg .u32 n; mov.u32 n, 0;\n"
               "W: mbarrier.try_wait.parity.shared::cta.b64 p, [%0], 0;\n"
               "@p bra D; add.u32 n, n, 1; setp.gt.u32 p, n, %1; @p trap; bra W;\n"
               "D: }" ::"r"(bar), "n"(SPIN_LIMIT) : "memory");
}
__device__ __forceinline__ uint32_t mbar_test(uint32_t bar) {
  uint32_t ok;
  asm volatile("{.reg .pred p; mbarrier.test_wait.parity.shared::cta.b64 p, [%1], 0; selp.u32 %0, 1, 0, p;}" : "=r"(ok) : "r"(bar) : "memory");
  return ok;
}
__device__ __forceinline__ void mbar_arrive(uint32_t bar, uint32_t n) {
  asm volatile("mbarrier.arrive.shared::cta.b64 _, [%0], %1;" ::"r"(bar), "r"(n) : "memory");
}
__device__ __forceinline__ void mbar_arrive_if0(int z, uint32_t bar, uint32_t n) {
  asm volatile("{.reg .pred p; setp.eq.s32 p, %2, 0; @p mbarrier.arrive.shared::cta.b64 _, [%0], %1;}" ::"r"(bar), "r"(n), "r"(z) : "memory");
}
__device__ __forceinline__ void mbar_arrive_remote_if0(int z, uint32_t bar) {
  asm volatile("{.reg .pred p; setp.eq.s32 p, %1, 0; @p mbarrier.arrive.shared::cluster.b64 _, [%0];}" ::"r"(bar), "r"(z) : "memory");
}
__device__ __forceinline__ void mbar_expect(uint32_t bar, uint32_t bytes) {
  asm volatile("mbarrier.arrive.expect_tx.shared::cta.b64 _, [%0], %1;" ::"r"(bar), "r"(bytes) : "memory");
}
__device__ __forceinline__ void tma2d(uint32_t dst, const CUtensorMap* tm, uint32_t bar, int c0, int c1) {
  asm volatile("cp.async.bulk.tensor.2d.shared::cluster.global.mbarrier::complete_tx::bytes [%0],[%1,{%3,%4}],[%2];"
               ::"r"(dst), "l"(tm), "r"(bar), "r"(c0), "r"(c1) : "memory");
}
__device__ __forceinline__ void tma3d(uint32_t dst, const CUtensorMap* tm, uint32_t bar, int c0, int c1, int c2) {
  asm volatile("cp.async.bulk.tensor.3d.shared::cluster.global.mbarrier::complete_tx::bytes [%0],[%1,{%3,%4,%5}],[%2];"
               ::"r"(dst), "l"(tm), "r"(bar), "r"(c0), "r"(c1), "r"(c2) : "memory");
}
__device__ __forceinline__ void bulk_load(uint32_t dst, const void* src, uint32_t bytes, uint32_t bar) {
  asm volatile("cp.async.bulk.shared::cluster.global.mbarrier::complete_tx::bytes [%0],[%1],%2,[%3];"
               ::"r"(dst), "l"(src), "r"(bytes), "r"(bar) : "memory");
}
__device__ __forceinline__ void l2_prefetch(const void* src, uint32_t bytes) {
  asm volatile("cp.async.bulk.prefetch.L2.global [%0], %1;" ::"l"(src), "r"(bytes) : "memory");
}
__device__ __forceinline__ void fence_async_smem() { asm volatile("fence.proxy.async.shared::cta;" ::: "memory"); }
__device__ __forceinline__ void fence_async_global() { asm volatile("fence.proxy.async.global;" ::: "memory"); }
__device__ __forceinline__ void flag_release(uint32_t* p, uint32_t bits) {
  asm volatile("fence.release.gpu;" ::: "memory");
  asm volatile("red.relaxed.gpu.global.xor.b32 [%0], %1;" ::"l"(p), "r"(bits) : "memory");
}
__device__ __forceinline__ uint32_t flag_read(const uint32_t* p, uint32_t epoch) {
  uint32_t v;
  asm volatile("ld.relaxed.gpu.global.u32 %0, [%1];" : "=r"(v) : "l"(p) : "memory");
  return v ^ ((epoch & 1) - 1);
}
__device__ __forceinline__ void flag_wait(const uint32_t* p, uint32_t want, uint32_t epoch) {
  int it = 0;
  while ((flag_read(p, epoch) & want) != want && ++it < SPIN_LIMIT) {}
  asm volatile("fence.acquire.gpu;" ::: "memory");
}
__device__ __forceinline__ void stg32(const void* p, uint32_t v) { asm volatile("st.global.u32 [%0], %1;" ::"l"(p), "r"(v) : "memory"); }
__device__ __forceinline__ void wg_fence() { asm volatile("wgmma.fence.sync.aligned;" ::: "memory"); }
__device__ __forceinline__ void wg_commit() { asm volatile("wgmma.commit_group.sync.aligned;" ::: "memory"); }
template <int N> __device__ __forceinline__ void wg_wait() { asm volatile("wgmma.wait_group.sync.aligned %0;" ::"n"(N) : "memory"); }
template <int N> __device__ __forceinline__ void reg_fence(float (&a)[N]) {
#pragma unroll
  for (int i = 0; i < N; i++) asm volatile("" : "+f"(a[i])::"memory");
}
template <int ID, int N> __device__ __forceinline__ void named_bar() { asm volatile("bar.sync %0, %1;" ::"n"(ID), "n"(N) : "memory"); }
template <int N> __device__ __forceinline__ void reg_fence(uint32_t (&a)[N]) {
#pragma unroll
  for (int i = 0; i < N; i++) asm volatile("" : "+r"(a[i])::"memory");
}
__device__ __forceinline__ Desc mkdesc(uint32_t dyn, uint32_t off, uint32_t lbo, uint32_t sbo, uint32_t swz) {
  return Desc{dyn, ((off + SMEM_BASE) >> 4) + ((lbo >> 4) << 16), (sbo >> 4) | (swz << 30)};
}
__device__ __forceinline__ uint32_t pack2(float lo, float hi) {
  uint32_t r;
  asm("cvt.rn.bf16x2.f32 %0, %1, %2;" : "=r"(r) : "f"(hi), "f"(lo));
  return r;
}
__device__ __forceinline__ float bf_lo(uint32_t v) { return __uint_as_float(v << 16); }
__device__ __forceinline__ float bf_hi(uint32_t v) { return __uint_as_float(v & 0xffff0000u); }
__device__ __forceinline__ void stsm4(uint32_t addr, uint32_t a, uint32_t b, uint32_t c, uint32_t d) {
  asm volatile("stmatrix.sync.aligned.m8n8.x4.shared.b16 [%0], {%1,%2,%3,%4};" ::"r"(addr), "r"(a), "r"(b), "r"(c), "r"(d) : "memory");
}
__device__ __forceinline__ void ldsm4(uint32_t addr, uint32_t* r) {
  asm volatile("ldmatrix.sync.aligned.m8n8.x4.shared.b16 {%0,%1,%2,%3}, [%4];" : "=r"(r[0]), "=r"(r[1]), "=r"(r[2]), "=r"(r[3]) : "r"(addr) : "memory");
}
__device__ __forceinline__ float2 lds64(uint32_t a) {
  float2 v;
  asm volatile("ld.shared.v2.f32 {%0,%1}, [%2];" : "=f"(v.x), "=f"(v.y) : "r"(a) : "memory");
  return v;
}
__device__ __forceinline__ float4 lds128(uint32_t a) {
  float4 v;
  asm volatile("ld.shared.v4.f32 {%0,%1,%2,%3}, [%4];" : "=f"(v.x), "=f"(v.y), "=f"(v.z), "=f"(v.w) : "r"(a) : "memory");
  return v;
}
__device__ __forceinline__ void sts64(uint32_t a, uint32_t x, uint32_t y) {
  asm volatile("st.shared.v2.u32 [%0], {%1,%2};" ::"r"(a), "r"(x), "r"(y) : "memory");
}
__device__ __forceinline__ void sts128(uint32_t a, uint32_t x, uint32_t y, uint32_t z, uint32_t w) {
  asm volatile("st.shared.v4.u32 [%0], {%1,%2,%3,%4};" ::"r"(a), "r"(x), "r"(y), "r"(z), "r"(w) : "memory");
}
__device__ __forceinline__ float ex2(float x) {
  float r;
  asm("ex2.approx.ftz.f32 %0, %1;" : "=f"(r) : "f"(x));
  return r;
}
__device__ __forceinline__ float rcp(float x) {
  float r;
  asm("rcp.approx.ftz.f32 %0, %1;" : "=f"(r) : "f"(x));
  return r;
}
constexpr float LOG2E = 1.4426950408889634f;
__device__ __forceinline__ float phi(float z, float a, float a2) {
  float r = ex2(z * a2) + 1e-6f;
  asm("{.reg .pred p; setp.gt.f32 p, %1, 0f00000000; @p fma.rn.f32 %0, %1, %2, 0f3F800008;}" : "+f"(r) : "f"(z), "f"(a));
  return r;
}
__device__ __forceinline__ float gelu(float z, const float3& k) {
  float th;
  asm("tanh.approx.f32 %0, %1;" : "=f"(th) : "f"(z * fmaf(z * z, k.y, k.x)));
  const float hy = z * k.z;
  return fmaf(hy, th, hy);
}
__device__ __forceinline__ uint32_t rk1_frag(float m, float d, int c) {
  const uint32_t hi = pack2(m, d), lo = pack2(m - bf_lo(hi), d - bf_hi(hi));
  return __byte_perm(c & 2 ? 0u : hi, c == 3 ? 0u : lo, 0x107632541010ull >> (16 * c) & 0xffff);
}
__device__ __forceinline__ void rk1_store(uint32_t addr, float2 cs, uint32_t bb) {
  const uint32_t hi = pack2(cs.x, cs.y), lo = pack2(cs.x - bf_lo(hi), cs.y - bf_hi(hi));
  sts128(addr, __byte_perm(hi, lo, 0x5410), __byte_perm(hi, bb, 0x5410), bb & 0xffffu, 0);
  sts128(addr + 16, __byte_perm(hi, lo, 0x7632), __byte_perm(hi, bb, 0x7632), bb >> 16, 0);
}
constexpr uint32_t ONES = 0x3F803F80u;
__device__ __forceinline__ void ll_store(uint4* p, float a, float b, uint32_t tag) {
  asm volatile("st.relaxed.gpu.global.v4.u32 [%0], {%1,%2,%3,%2};" ::"l"(p), "r"(__float_as_uint(a)), "r"(tag), "r"(__float_as_uint(b)) : "memory");
}
__device__ __forceinline__ uint4 ll_load(const void* p) {
  uint4 v;
  asm volatile("ld.relaxed.gpu.global.v4.u32 {%0,%1,%2,%3}, [%4];" : "=r"(v.x), "=r"(v.y), "=r"(v.z), "=r"(v.w) : "l"(p) : "memory");
  return v;
}
template <int N>
__device__ __forceinline__ void ll_wait(uint4 (&v)[N], const uint4* p, int stride, uint32_t tag) {
  uint32_t bad;
  int it = 0;
  do {
    bad = 0;
#pragma unroll
    for (int m = 0; m < N; m++) v[m] = ll_load(p + m * stride);
#pragma unroll
    for (int m = 0; m < N; m++) bad |= (v[m].y ^ tag) | (v[m].w ^ tag);
  } while (__any_sync(0xffffffffu, bad) && ++it < SPIN_LIMIT);
}
__device__ __forceinline__ void ll_wait2(uint4 (&v)[8], const uint4* p, uint32_t tag) {
  uint32_t bad;
  int it = 0;
  do {
    bad = 0;
#pragma unroll
    for (int m = 0; m < 8; m++) v[m] = ll_load(p + (m >> 1) * 1728 + (m & 1));
#pragma unroll
    for (int m = 0; m < 8; m++) bad |= (v[m].y ^ tag) | (v[m].w ^ tag);
  } while (__any_sync(0xffffffffu, bad) && ++it < SPIN_LIMIT);
}
__device__ __forceinline__ float2 ll_sum4(const uint4* p, uint32_t tag) {
  uint4 v[4];
  ll_wait(v, p, 1728, tag);
  return make_float2((__uint_as_float(v[0].x) + __uint_as_float(v[1].x)) + (__uint_as_float(v[2].x) + __uint_as_float(v[3].x)),
                     (__uint_as_float(v[0].z) + __uint_as_float(v[1].z)) + (__uint_as_float(v[2].z) + __uint_as_float(v[3].z)));
}
__device__ __noinline__ float2 colsum(const __nv_bfloat16* wm, int ld, int h0, int h1) {
  const int lane = threadIdx.x & 31, r4 = lane >> 3;
  float d[8];
#pragma unroll
  for (int e = 0; e < 8; e++) d[e] = 0.f;
#pragma unroll 1
  for (int h = h0; h < h1; h++) {
    const __nv_bfloat16* wp = wm + (4 * h + r4) * ld + 8 * (lane & 7);
    uint4 v[14];
#pragma unroll
    for (int m = 0; m < 14; m++) {
      v[m] = make_uint4(0, 0, 0, 0);
      if (m < 13 || h == 0)
        asm volatile("ld.global.nc.v4.u32 {%0,%1,%2,%3}, [%4];" : "=r"(v[m].x), "=r"(v[m].y), "=r"(v[m].z), "=r"(v[m].w) : "l"(wp));
      wp += 12 * ld;
    }
#pragma unroll
    for (int m = 0; m < 14; m++) {
      d[0] += bf_lo(v[m].x); d[1] += bf_hi(v[m].x); d[2] += bf_lo(v[m].y); d[3] += bf_hi(v[m].y);
      d[4] += bf_lo(v[m].z); d[5] += bf_hi(v[m].z); d[6] += bf_lo(v[m].w); d[7] += bf_hi(v[m].w);
    }
  }
#pragma unroll 1
  for (int o = 8; o < 32; o <<= 1) {
#pragma unroll
    for (int e = 0; e < 8; e++) d[e] += __shfl_xor_sync(0xffffffffu, d[e], o);
  }
  if (r4 & 2) { d[0] = d[4]; d[1] = d[5]; d[2] = d[6]; d[3] = d[7]; }
  return r4 & 1 ? make_float2(d[2], d[3]) : make_float2(d[0], d[1]);
}
template <bool PHI>
__device__ __forceinline__ void ln_pair(const float* z, const float (&a)[2], const float (&a2)[2], uint32_t* o) {
#pragma unroll
  for (int e = 0; e < 4; e++) {
    const int hh = e & 1;
    o[e] = PHI ? pack2(phi(z[2 * e], a[hh], a2[hh]), phi(z[2 * e + 1], a[hh], a2[hh])) : pack2(z[2 * e] * a[hh], z[2 * e + 1] * a[hh]);
  }
}

__global__ void __cluster_dims__(2, 1, 1) __launch_bounds__(384, 1)
fused_block_kernel(Scratch* __restrict__ scr, const __nv_bfloat16* __restrict__ wqkv, const __nv_bfloat16* __restrict__ wo,
                   const __nv_bfloat16* __restrict__ w1, const __nv_bfloat16* __restrict__ w2, const __nv_bfloat16* __restrict__ b2,
                   const __nv_bfloat16* __restrict__ b1, __nv_bfloat16* __restrict__ out,
                   const __grid_constant__ Maps maps) {
  extern __shared__ __align__(1024) uint8_t smem_raw[];
  const uint32_t sb = (uint32_t)__cvta_generic_to_shared(smem_raw);
  const uint32_t bars = sb + OFF_BAR;
  const int warp = __shfl_sync(0xffffffffu, threadIdx.x >> 5, 0);
  const int lane = threadIdx.x & 31;
  if (warp < 3 && elect_one()) asm volatile("prefetch.tensormap [%0];" ::"l"(&maps.m[warp]) : "memory");

  const int cl = blockIdx.x >> 1, q = blockIdx.x & 1;
  const int u7 = ((cl - 36) * 37) >> 8;
  const int oct = cl < 4 ? 0 : cl < 36 ? 1 + 2 * ((cl - 4) & 7) : 2 + 2 * (cl - 36 - 7 * u7);
  const int u4 = cl < 4 ? cl : cl < 36 ? (cl - 4) >> 3 : u7;
  const int i = 2 * (oct & 7) + (u4 >> 1), p = 2 * (oct >> 3) + (u4 & 1);
  const int j = 2 * p + q;
  auto col_f = [](int jj) { return 160 * (jj >> 1) + 16 * (jj & 2) + 64 * (jj & 1); };
  auto col_r = [](int jj) { return 160 * (jj >> 1) + 128 - 64 * (jj & 2) + 16 * (jj & 1); };
  const int cF = col_f(j), cR = col_r(j), role = q ^ (p & 1);

  auto load_kv = [&](int s) {
    const uint32_t dst = sb + (s < 16 ? OFF_RING + (s % 5) * 12288 : (s - 16) * 12288), bar = bars + 8 * (s < 16 ? RF + s % 5 : FE + s - 16);
    tma3d(dst, &maps.m[M_KVF], bar, cF, 32 * s, 1);
    tma2d(dst + 8192, &maps.m[M_KVH], bar, 640 + 640 * role + cR - 16 * q, 32 * s);
    mbar_expect(bar, 10240);
  };
  auto load_x = [&](int c, int b, int slot) {
    tma2d(sb + slot * 16384, &maps.m[M_X], bars + 8 * (FX + b), 64 * c, 128 * i);
    mbar_expect(bars + 8 * (FX + b), 16384);
  };
  auto bar_init = [&](int n, uint32_t cnt) { asm volatile("mbarrier.init.shared::cta.b64 [%0], %1;" ::"r"(bars + 8 * n), "r"(cnt) : "memory"); };

  if (warp < 8 && elect_one()) {
    if (warp == 3) {
      bar_init(RF, 1);
      bar_init(RF + 1, 1);
      bar_init(FX, 1);
      load_x(0, 0, 0);
      load_kv(0);
      load_kv(1);
    }
#pragma unroll
    for (int n = 0; n < 5; n++)
      if (warp > (n == 0 ? 1 : n == 1 ? 0 : -1)) bar_init(5 * warp + n, warp < 5 ? 1 : 8);
    asm volatile("fence.mbarrier_init.release.cluster;" ::: "memory");
  }
  __syncwarp();

  if (warp >= 8) {
    TC(tc0);
    asm volatile("setmaxnreg.dec.sync.aligned.u32 88;");
    TC(tc1);
    if (warp == 8) {
      named_bar<0, 288>();
      TC(tc2);
      asm volatile("barrier.cluster.arrive.relaxed.aligned;" ::: "memory");
      if (elect_one()) {
        load_x(1, 1, 1);
        load_kv(2);
        load_kv(3);
        load_x(2, 2, 2);
        load_kv(4);
        load_x(3, 3, 3);
      }
      __syncwarp();
      TC(tc3);
      asm volatile("barrier.cluster.wait.aligned;" ::: "memory");
      TL(40);
      TS(41, tc0); TS(42, tc1); TS(43, tc2); TS(19, tc3);
      if (elect_one()) {
        auto prefetch_piece = [&](const __nv_bfloat16* wm, uint32_t total, uint32_t off, uint32_t bytes) {
          l2_prefetch(reinterpret_cast<const uint8_t*>(wm) + blockIdx.x * total + off, bytes);
        };
#pragma unroll
        for (int s = 5; s < 16; s++) {
          mbar_wait(bars + 8 * (RE + s % 5), (s / 5 - 1) & 1);
          load_kv(s);
          if (s < 11) load_x(s - 1, s - 1, s - 1);
          if (s == 12) mbar_wait(bars + 8 * XF);
          if (s >= 12) load_kv(s + 4);
          if (s < 13) asm volatile("prefetch.tensormap [%0];" ::"l"(&maps.m[s - 2]) : "memory");
          if (s >= 11) prefetch_piece(wo, 6400, (s - 11) * 1280, 1280);
          TL1(96 + s);
        }
#pragma unroll
        for (int t = 0; t < 10; t++) {
          const int slot = (t + 1) % 5, k0 = 64 * (t < 7 ? t + 3 : t - 7);
          const uint32_t dst = sb + OFF_RING + slot * 12288, bar = bars + 8 * (RF + slot);
          mbar_wait(bars + 8 * (RE + slot), ((t + 11) / 5) & 1);
          tma3d(dst, &maps.m[M_Q2], bar, 0, k0, 5 * p + 3 * q);
          tma2d(dst + 8192, &maps.m[M_QR], bar, 80 * j + 64 - 64 * q, k0);
          mbar_expect(bar, 10240);
          if (t >= 6 && t < 9) load_x(t - 6, t + 4, t - 2);
          if (t < 8) prefetch_piece(w1, 15360, t * 1920, 1920);
          TL1(116 + t);
        }
#pragma unroll 1
        for (int n = 0; n < 32; n += 4) {
          const int t = (0x41765320u >> n) & 7, k0 = 80 * (t == 0 ? j : t - (t <= j));
          const uint32_t dst = sb + 10 * PAGE + (t < 2 ? t ^ 1 : t) * 15360, bar = bars + 8 * (FWO + t);
          mbar_wait(bars + 8 * (RE + ((0x00432221u >> n) & 15)), n >= 24);
          if (n >= 8) mbar_wait(bars + 8 * (FWO + ((0x41765320u >> (n - 8)) & 7)));
          tma3d(dst, &maps.m[M_WO2], bar, 0, k0, cF >> 5);
          tma2d(dst + 10240, &maps.m[M_WOR], bar, cR, k0);
          mbar_expect(bar, 12800);
          TL1(128 + n / 4);
        }
#pragma unroll 1
        for (int t = 0; t < 8; t++) {
          const uint32_t wb = bars + 8 * (t == 0 ? FWO + 1 : t < 5 ? DW + 2 * t - 1 : DF + t - 5);
          const int jj = t == 0 ? j : t - (t <= j);
          const uint32_t dst = sb + (7 + 3 * (t < 5 ? t : t - 5)) * PAGE, bar = bars + 8 * (FW1 + t);
          mbar_wait(wb);
          if (t) {
            mbar_wait(wb + 64);
            mbar_wait(bars + 8 * (t == 1 ? AH : t < 4 ? FW1 + t - 1 : t == 4 ? AH + 2 : DF + t - 4));
          }
          tma3d(dst, &maps.m[M_W1], bar, 0, col_f(jj), 3 * j);
          tma3d(dst + 24576, &maps.m[M_W1R], bar, 0, col_r(jj), 3 * j);
          mbar_expect(bar, 30720);
          if (t >= 3) prefetch_piece(w2, 15360, (t - 3) * 3072, 3072);
          TL1(136 + t);
        }
#pragma unroll 1
        for (int t = 0; t < 12; t++) {
          const int t6 = t < 6 ? t : t - 6;
          const uint32_t wb = bars + 8 * (t < 6 ? DF + ((0x776544 >> (4 * t)) & 7) : DG + t6);
          const int uu = (0xA95024 >> (2 * t)) & 3, n = (0x924900 >> (2 * t)) & 3;
          const int k0 = 192 * (t < 3 ? j : 2 * (n + (n >= p)) + q) + 64 * uu;
          const uint32_t dst = sb + OFF_W2 + ((0x321045 >> (4 * t6)) & 7) * 24576, bar = bars + 8 * (FW2 + t);
          mbar_wait(wb);
          mbar_wait(wb + (t < 6 ? 64 : 96));
          tma2d(dst, &maps.m[M_W2F], bar, cF, k0);
          tma2d(dst + 8192, &maps.m[M_W2F], bar, cF + 64 - 128 * q, k0);
          tma2d(dst + 16384, &maps.m[M_W2H], bar, cR - 16 * q, k0);
          mbar_expect(bar, 20480);
          TL1(144 + t);
        }
      }
    } else {
      const int unit = i * 8 + j, hw = warp - 9, part = unit & 3, cg = unit >> 2;
      asm volatile("barrier.cluster.arrive.relaxed.aligned;" ::: "memory");
      if (part >= 2) {
        asm volatile("barrier.cluster.wait.aligned;" ::: "memory");
        mbar_wait_wd(bars + 8 * (FX + 2 * part - 4));
      }
      uint32_t epoch;
      asm volatile("ld.relaxed.gpu.global.u32 %0, [%1];" : "=r"(epoch) : "l"(&scr->epoch) : "memory");
      epoch += 1;
      if (hw == 0 && lane < 28 && i < 15) *reinterpret_cast<float4*>(scr->kv + j * 1696 + i * 112 + lane * 4) = make_float4(0.f, 0.f, 0.f, 0.f);
      if (hw == 0) TL(248);
      const int ht = hw * 32 + lane, cpair = part * 1728 + 32 * cg + 4 * (lane & 7) + (lane >> 3);
      if (cg < 30) {
        float2 csum = colsum(wqkv + part * 160 * 1920 + 64 * cg, 1920, hw, hw + 1);
        const uint32_t red = sb + OFF_SCR + lane * 8;
#pragma unroll 1
        for (int h = 0; h < 2; h++) {
          if (hw == h) sts64(red, __float_as_uint(csum.x), __float_as_uint(csum.y));
          named_bar<2, 96>();
          if (hw == h + 1) {
            const float2 a = lds64(red);
            csum.x += a.x;
            csum.y += a.y;
          }
        }
        if (hw == 2) ll_store(scr->cs + cpair, csum.x, csum.y, epoch);
      }
      if (hw == 2) TL(249);
      if (part < 2) asm volatile("barrier.cluster.wait.aligned;" ::: "memory");
      if (elect_one()) {
#pragma unroll 1
        for (int n = FWO + 50 * hw; n < FWO + 50 * hw + 50; n += 10) {
#pragma unroll
          for (int e = 0; e < 10; e++) bar_init(n + e, n < AO ? 1 : 8);
        }
        mbar_expect(bars + 8 * (RX + hw), hw == 2 ? 8192 : 10240);
        if (hw == 0) flag_release(scr->flag + (96 + j) * 32, 1u << i);
      }
      __syncwarp();
      if (hw == 2) {
        TL(8);
#pragma unroll 1
        for (int n = lane; n < 40; n += 32) {
          const uint32_t b = *reinterpret_cast<const uint32_t*>(b2 + (n < 32 ? cF + 2 * n : cR + 2 * n - 64));
          sts64(sb + OFF_B2 + n * 8, b << 16, b & 0xffff0000u);
        }
        __syncwarp();
        mbar_wait_wd(bars + 8 * ST1);
        uint4 v[4];
        ll_wait(v, scr->ln1 + 128 * i + lane, 32, epoch);
#pragma unroll
        for (int m = 0; m < 4; m++) {
          const float nm = __uint_as_float(v[m].x) * (-1.f / 640.f);
          const float rstd = rsqrtf(fmaxf(fmaf(-nm, nm, __uint_as_float(v[m].z) * (1.f / 640.f)), 0.f) + 1e-5f);
          sts64(sb + OFF_LN1 + (lane + 32 * m) * 8, __float_as_uint(rstd), __float_as_uint(nm));
        }
      } else {
        const int n = 4 * min(ht, 59);
        int col;
        if (n < 160) col = n + (n < 64 ? 640 + cF : n < 128 ? 1216 + cF : 512 + 640 * role + cR - 16 * q);
        else col = 80 * j + n - 160 + (q ? (n < 224 ? 16 : -64) : 0);
        mbar_wait(bars + 8 * CG);
        uint4 v[8];
        ll_wait2(v, scr->cs + (col >> 1), epoch);
#pragma unroll
        for (int e = 0; e < 2; e++)
          rk1_store(sb + OFF_RK1 + n * 16 + 32 * e,
                    make_float2((__uint_as_float(v[e].x) + __uint_as_float(v[2 + e].x)) + (__uint_as_float(v[4 + e].x) + __uint_as_float(v[6 + e].x)),
                                (__uint_as_float(v[e].z) + __uint_as_float(v[2 + e].z)) + (__uint_as_float(v[4 + e].z) + __uint_as_float(v[6 + e].z))), 0);
        fence_async_smem();
      }
      __syncwarp();
      mbar_arrive_if0(lane, bars + 8 * SIDE, hw == 2 ? 2 : 3);
      if (hw != 1) TL(11 - hw / 2);
      {
        if (hw == 2) {
          flag_wait(scr->flag + (96 + j) * 32, 0xffffu, epoch);
          fence_async_global();
          mbar_wait_wd(bars + 8 * RKV);
          if (elect_one()) {
            asm volatile("cp.reduce.async.bulk.global.shared::cta.bulk_group.add.f32 [%0], [%1], 6720;" ::"l"(scr->kv + j * 1696), "r"(sb + OFF_KVP) : "memory");
            asm volatile("cp.async.bulk.commit_group;" ::: "memory");
            asm volatile("cp.async.bulk.wait_group 0;" ::: "memory");
            flag_release(scr->flag + (104 + j) * 32, 1u << i);
          }
          TL(5);
        } else {
          mbar_wait_wd(bars + 8 * ZK);
#pragma unroll 1
          for (int m = 0; m < 15; m += 3) {
#pragma unroll
            for (int e = 0; e < 3; e++) sts128(sb + OFF_KVB + ((m + e) * 64 + ht) * 16, 0, 0, 0, 0);
          }
        }
        const int d0 = ht < 80 ? (ht * 205) >> 10 : ht - 80, pt = ht - 5 * d0;
        uint32_t da[5];
#pragma unroll
        for (int m = 0; m < 5; m++) {
          const int d = d0 + 16 * m, head = (d * 205) >> 12, n = 20 * head + 4 * pt;
          da[m] = sb + OFF_KVB + d * 16 + (ht < 80 ? (n >> 3) * 1280 + (n & 7) * 2 : (10 + (head >> 1)) * 1280 + (head & 1));
        }
        reg_fence(da);
        named_bar<2, 96>();
        flag_wait(scr->flag + (104 + j) * 32, 0xffffu, epoch);
        if (hw == 0) TL(6);
        if (ht < 80) {
          uint4 v[5];
#pragma unroll
          for (int m = 0; m < 5; m++) v[m] = ll_load(scr->kv + j * 1696 + (ht + 80 * m) * 4);
#pragma unroll
          for (int m = 0; m < 5; m++)
            sts64(da[m], pack2(__uint_as_float(v[m].x), __uint_as_float(v[m].y)), pack2(__uint_as_float(v[m].z), __uint_as_float(v[m].w)));
        } else {
          float z[5];
#pragma unroll
          for (int m = 0; m < 5; m++) asm volatile("ld.relaxed.gpu.global.f32 %0, [%1];" : "=f"(z[m]) : "l"(scr->kv + j * 1696 + 1520 + ht + 16 * m) : "memory");
#pragma unroll
          for (int m = 0; m < 5; m++) {
            const uint32_t zz = pack2(z[m], 0.f) << (16 * (da[m] & 1));
            sts128(da[m] & ~1u, zz, zz, zz, zz);
          }
        }
        fence_async_smem();
        __syncwarp();
        mbar_arrive_if0(lane, bars + 8 * KVB, hw == 2 ? 2 : 3);
        if (hw == 0) TL(7);
      }

      if (hw == 2) {
        if (cg < 24) {
          const float2 d = colsum(w1 + part * 160 * 1536 + 64 * cg, 1536, 0, 3);
          ll_store(scr->cs + 960 + cpair, d.x, d.y, epoch);
        }
        mbar_wait_wd(bars + 8 * (DW + 15));
#pragma unroll 1
        for (int n = lane; n < 96; n += 32)
          rk1_store(sb + OFF_RK1 + n * 32, ll_sum4(scr->cs + 960 + 96 * j + n, epoch), *reinterpret_cast<const uint32_t*>(b1 + 192 * j + 2 * n));
        fence_async_smem();
        __syncwarp();
        mbar_arrive_if0(lane, bars + 8 * SIDE2, 8);
        TL(18);
        const uint32_t eb = bars + 8 * (AF + 12 * ((lane >> 1) & 1) + 1 + (lane & 1));
        uint32_t pm = 15;
        do {
          mbar_wait_wd(__shfl_sync(0xffffffffu, eb, __ffs(pm) - 1));
          const uint32_t ok = mbar_test(eb) & (pm >> lane);
          if (ok) flag_release(scr->flag + (64 + 2 * i + (lane >> 1)) * 32, 0x100u << (8 * (lane & 1) + j));
          pm &= ~__ballot_sync(0xffffffffu, ok);
        } while (pm);
        mbar_wait_wd(bars + 8 * END);
        if (blockIdx.x == 0 && lane == 0) scr->epoch = epoch;
      } else {
        const int s = hw;
#pragma unroll 1
        for (int ph = 0; ph < 3; ph++) {
          const uint32_t ab = bars + 8 * (ph < 2 ? AO + 16 * ph + 8 * s : AF + 12 * s);
          const uint32_t bytes = ph < 2 ? 10240 : 8192;
          uint8_t* gb = scr->act + (ph * 32 + 2 * i + s) * 8 * 24576;
          uint32_t* fl = scr->flag + (ph * 32 + 2 * i + s) * 32;
          const int r = min(lane, 8);
          int cc = r + (r >= j), bit = cc, slot, wb, off = 0;
          if (ph == 0) {
            slot = r;
            wb = s ? DW + r + 1 : AO + 8;
          } else if (ph == 1) {
            slot = (0x0924u >> (2 * r)) & 3;
            wb = r < 3 ? DW + (s ? 15 : 9 + r) : DF + 8 * s + r - 2;
          } else {
            const int uu = (r * 11) >> 5, n = r - 3 * uu;
            cc = 2 * (n + (n >= p)) + q;
            bit = cc + 8 * uu;
            off = uu * 8192;
            slot = r & 3;
            wb = r < 4 ? DF + 8 * s + 7 : DG + 12 * s + r - 1;
          }
          const uint32_t fb = ab + 8 * r + (ph < 2 ? 8 : 24), wbar = bars + 8 * wb;
          const uint32_t dst = sb + (ph ? s * OFF_R1 : 0) + slot * bytes;
          const uint8_t* src = gb + cc * 24576 + off;
          uint32_t pm = ph < 2 ? 0x7fu : 0x1ffu, seen = 0;
          if (pm >> lane & 1) {
            mbar_expect(fb, bytes);
            mbar_arrive(fb, 7);
          }
          __syncwarp();
          mbar_wait(ab);
          if (elect_one()) flag_release(fl, 1u << j);
          __syncwarp();
          TL(44 + 2 * ph + s);
          do {
            const int next = __ffs(pm) - 1;
            if (!(seen >> next & 1)) {
              do seen = __ballot_sync(0xffffffffu, flag_read(fl, epoch) >> bit & 1);
              while (!(seen >> next & 1));
              asm volatile("fence.acquire.gpu;" ::: "memory");
              fence_async_global();
            }
            if (next == 0) TL(52 + 2 * ph + s);
            mbar_wait(__shfl_sync(0xffffffffu, wbar, next));
            const uint32_t ok = mbar_test(wbar) & ((pm & seen) >> lane);
            if (ok) bulk_load(dst, src, bytes, fb);
            pm &= ~__ballot_sync(0xffffffffu, ok);
          } while (pm);
        }
      }
    }
  } else {
    named_bar<0, 288>();
    asm volatile("barrier.cluster.arrive.relaxed.aligned;" ::: "memory");
    TC(tc4);
    uint32_t epoch;
    asm volatile("ld.relaxed.gpu.global.u32 %0, [%1];" : "=r"(epoch) : "l"(&scr->epoch) : "memory");
    epoch += 1;
    const int s = warp >> 2, w = warp & 3, tid = threadIdx.x & 127, c = lane & 3, g = lane >> 2;
    uint32_t sb_peer;
    asm volatile("mapa.shared::cluster.u32 %0, %1, %2;" : "=r"(sb_peer) : "r"(sb), "r"(q ^ 1));
    const int row0 = 128 * i + 64 * s + 16 * w;
    const uint32_t bs8 = bars + 64 * s, bs12 = bars + 96 * s;
    uint32_t pq[20], hp[20];
    {
      float acc[80];
      const Desc dx = mkdesc(s * 512, 0, 16, 1024, 1);
      const int srow = 16 * j + 2 * warp + (lane >> 4);
      float sm = 0.f, sq = 0.f;
      float4 u;
      auto load_res = [&]() {
        const uint32_t xa = sb + (64 * s + 16 * w + (lane & 15)) * 128;
#pragma unroll
        for (int ks = 0; ks < 5; ks++) {
          const int col = ks < 4 ? cF + 16 * ks : cR;
          ldsm4(xa + (col >> 6) * 16384 + (((((col & 63) >> 3) + (lane >> 4)) ^ (lane & 7)) << 4), hp + 4 * ks);
        }
      };
#pragma unroll
      for (int st = 0; st < 20; st++) {
        if ((st & 1) == 0 && st <= 4) mbar_wait(bars + 8 * (FX + (st >> 1)));
        mbar_wait(bars + 8 * (st < 16 ? RF + st % 5 : FE + st - 16), st < 16 ? (st / 5) & 1 : 0);
        const Desc da = dx + (st >> 1) * 1024 + (st & 1) * 4;
        const Desc db = mkdesc(0, st < 16 ? OFF_RING + (st % 5) * 12288 : (st - 16) * 12288, 4096, 1024, 1);
        wg_fence();
        wgmma_ss<160, 0, 1>(acc, da, db, st != 0);
        wgmma_ss<160, 0, 1>(acc, da + 2, db + 128, 1);
        wg_commit();
        TL0(64 + st);
        if (st == 0) { TL0(0); TS(38, tc4); TS(62, (uint32_t)tl_gt); }
        if (st == 1) asm volatile("setmaxnreg.inc.sync.aligned.u32 208;");
        if (st == 15) asm volatile("barrier.cluster.wait.aligned;" ::: "memory");
        if (st >= 3 && st <= 11 && (st & 1)) {
          const float uu[4] = {u.x, u.y, u.z, u.w};
#pragma unroll
          for (int e = 0; e < 4; e++) {
            const float a = bf_lo(__float_as_uint(uu[e])), b = bf_hi(__float_as_uint(uu[e]));
            sm += a + b;
            sq = fmaf(a, a, fmaf(b, b, sq));
          }
        }
        if (st >= 2 && st <= 10 && (st & 1) == 0) {
          if (st > 4) mbar_wait(bars + 8 * (FX + st - 2));
          if (st > 2) mbar_wait(bars + 8 * (FX + st - 1));
          u = lds128(sb + (st - 2 + ((lane >> 3) & 1)) * 16384 + srow * 128 + (lane & 7) * 16);
        }
        if (st == 11 || st == 12) {
#pragma unroll
          for (int o = st == 11 ? 1 : 4; o < (st == 11 ? 4 : 16); o <<= 1) {
            sm += __shfl_xor_sync(0xffffffffu, sm, o);
            sq += __shfl_xor_sync(0xffffffffu, sq, o);
          }
        }
        if (st == 12) {
          if ((lane & 15) == 0) ll_store(scr->ln1 + 128 * i + srow, sm, sq, epoch);
          TL0(39);
        }
        if (st == 13) mbar_arrive_if0(lane, bars + 8 * CG, 1);
        if (st == 14) mbar_arrive_if0(lane, bars + 8 * ST1, 1);
        if (st == 7 && p < 2) load_res();
        if (st == 8) mbar_arrive_if0(lane, bars + 8 * XF, 1);
        if (st == 16 && p >= 2) load_res();
        if (st > 0) {
          wg_wait<1>();
          if (st <= 16) mbar_arrive_if0(lane, bars + 8 * (RE + (st - 1) % 5), 1);
        }
      }
      TL0(12);
      float accq[40];
      auto q_step = [&](int t) {
        if (t >= 7) mbar_wait(bars + 8 * (FX + 3 + t));
        mbar_wait(bars + 8 * (RF + (t + 1) % 5), ((t + 16) / 5) & 1);
        const Desc da = dx + (t < 7 ? t + 3 : t - 3) * 1024, db = mkdesc(0, OFF_RING + ((t + 1) % 5) * 12288, 4096, 512, 2);
        wg_fence();
#pragma unroll
        for (int ks = 0; ks < 4; ks++) wgmma_ss<80, 0, 1>(accq, da + 2 * ks, db + 64 * ks, 1);
        wg_commit();
        TL0(84 + t);
      };
      mbar_wait(bars + 8 * SIDE);
      float a1[2], a2[2];
      uint32_t rk[2];
#pragma unroll
      for (int r = 0; r < 2; r++) {
        const float2 st = lds64(sb + OFF_LN1 + (64 * s + 16 * w + g + 8 * r) * 8);
        a1[r] = st.x;
        a2[r] = st.x * LOG2E;
        rk[r] = rk1_frag(st.y, 0.f, c);
      }
      wg_fence();
      wgmma_rs<160, 0>(acc, rk[0], rk[1], 0, 0, mkdesc(0, OFF_RK1, 0, 128, 0), 1);
      wg_commit();
      wgmma_rs<80, 0>(accq, rk[0], rk[1], 0, 0, mkdesc(0, OFF_RK1 + 2560, 0, 128, 0), 0);
      q_step(0);
      const int hi = lane >> 4;
      const uint32_t rowoff = sb + (64 * s + 16 * w + (lane & 15)) * 16;
      const uint32_t remoff = sb_peer + (64 * s + 16 * w) * 16 + lane * 4;
      auto put_remote = [&](const uint32_t* r, uint32_t a) {
#pragma unroll
        for (int e = 0; e < 4; e++)
          asm volatile("st.async.shared::cluster.mbarrier::complete_tx::bytes.b32 [%0], %1, [%2];"
                       ::"r"(a + (e >> 1) * 2048 + (e & 1) * 128), "r"(r[e]), "r"(sb_peer + OFF_BAR + 8 * RXK) : "memory");
      };
      const int mF = 2 * (p & 1) - q, g0 = 2 * mF + hi;
      const uint32_t ka = rowoff + g0 * 2048;
      wg_wait<1>();
      reg_fence(acc);
      mbar_arrive_if0(lane, bars + 8 * KD, 1);
      mbar_arrive_remote_if0(lane, sb_peer + OFF_BAR + 8 * PX);
      TL0(1);
      uint32_t r[4], r2[4];
      if (role == 0) {
        ln_pair<true>(acc + 64, a1, a2, r);
        ln_pair<true>(acc + 72, a1, a2, r2);
        mbar_wait_cluster(bars + 8 * PX);
        put_remote(r, remoff + (q ? 0 : 6 * 2048));
        put_remote(r2, remoff + (q ? 2 * 2048 : 8 * 2048));
      } else {
        ln_pair<false>(acc + 64, a1, a2, r);
        ln_pair<false>(acc + 72, a1, a2, r2);
        const uint32_t a = rowoff + (hi + (q ? 17 : 10)) * 2048;
        mbar_wait(bars + 8 * KD);
        stsm4(a, r[0], r[1], r[2], r[3]);
        stsm4(a + 4096, r2[0], r2[1], r2[2], r2[3]);
      }
      q_step(1);
#pragma unroll
      for (int n = 0; n < 4; n++) {
        const int P = n == 0 ? 0 : n == 1 ? 3 : n - 1;
        ln_pair<true>(acc + 8 * P, a1, a2, r);
        ln_pair<false>(acc + 32 + 8 * P, a1, a2, r2);
        if (n == 0) mbar_wait(bars + 8 * KD);
        if (n < 2 && mF == (n ? 2 : -1)) {
          mbar_wait_cluster(bars + 8 * PX);
          put_remote(r, remoff + (n ? 0 : 8 * 2048));
          put_remote(r2, remoff + (n ? 10 * 2048 : 19 * 2048));
        } else {
          stsm4(ka + P * 4096, r[0], r[1], r[2], r[3]);
          stsm4(ka + P * 4096 + (g0 + 2 * P > 4 ? 11 * 2048 : 10 * 2048), r2[0], r2[1], r2[2], r2[3]);
        }
        if (n == 0) {
          wg_wait<1>();
          mbar_arrive_if0(lane, bars + 8 * (RE + 1), 1);
          mbar_arrive_if0(lane, bars + 8 * ZK, 1);
        }
        if (n == 1) q_step(2);
        if (n == 2) {
          wg_wait<1>();
          mbar_arrive_if0(lane, bars + 8 * (RE + 2), 1);
        }
      }
      sts128(rowoff + 15 * 2048, ONES, ONES, ONES, ONES);
      TL0(2);
      mbar_wait_cluster(bars + 8 * RXK);
      fence_async_smem();
      named_bar<1, 256>();
      TL0(3);
      float kv[24];
      {
        const Desc da = mkdesc(s * 640, 0, 128, 2048, 0), db = da + 1280;
        wg_fence();
#pragma unroll
        for (int kk = 0; kk < 8; kk++) wgmma_ss<48, 1, 1>(kv, da + 16 * kk, db + 16 * kk, kk != 0);
        wg_commit();
      }
      wg_wait<1>();
      mbar_arrive_if0(lane, bars + 8 * (RE + 3), 1);
      q_step(3);
      {
        wg_wait<1>();
        reg_fence(kv);
        TL0(4);
#pragma unroll
        for (int hh = 0; hh < 2; hh++) {
          const int r = 16 * w + g + 8 * hh, eb = c - 4 * s - (r < 20 ? 0 : r < 40 ? 10 : 99);
          const uint32_t a = sb + OFF_KVP + (40 * s + r) * 80 + 8 * eb;
#pragma unroll
          for (int tt = 0; tt < 6; tt++)
            asm volatile("{.reg .pred p; setp.lt.u32 p, %3, 10; @p st.shared.v2.f32 [%0], {%1, %2};}"
                         ::"r"(a + 32 * tt), "f"(kv[4 * tt + 2 * hh]), "f"(kv[4 * tt + 2 * hh + 1]), "r"(eb + 4 * tt) : "memory");
          asm volatile("{.reg .pred p; setp.lt.u32 p, %2, 40; @p st.shared.f32 [%0], %1;}"
                       ::"r"(sb + OFF_KVP + 6400 + (40 * s + r) * 4), "f"(s ? kv[2 * hh] : kv[20 + 2 * hh]), "r"(r) : "memory");
        }
        fence_async_smem();
        __syncwarp();
      }
      mbar_arrive_if0(lane, bars + 8 * RKV, 1);
      TL0(9);
#pragma unroll
      for (int t = 4; t < 10; t++) {
        q_step(t);
        wg_wait<1>();
        mbar_arrive_if0(lane, bars + 8 * (RE + t % 5), 1);
      }
      wg_wait<0>();
      reg_fence(accq);
      mbar_arrive_if0(lane, bars + 8 * RE, 1);
      TL0(13);
#pragma unroll
      for (int P = 0; P < 5; P++) ln_pair<true>(accq + 8 * P, a1, a2, pq + 4 * P);
      reg_fence(pq);
      TL0(14);
    }
    const uint32_t rs = sb + s * OFF_R1;
    const uint8_t* gout = scr->act + ((2 * i + s) * 8 + j) * 24576 + 256 * w + 4 * lane;
    const Desc drs = mkdesc(s * (OFF_R1 / 16), 0, 1024, 128, 0);
    float accg[80];
    {
      {
        float o[48];
        wg_fence();
        mbar_wait(bars + 8 * (s ? OM : KVB));
        TL0(15);
#pragma unroll
        for (int ks = 0; ks < 5; ks++)
          wgmma_rs<96, 1>(o, pq[4 * ks], pq[4 * ks + 1], pq[4 * ks + 2], pq[4 * ks + 3], mkdesc(ks < 4 ? 16 * q : -64 * q, OFF_KVB + 256 * ks, 128, 1280, 0), ks != 0);
        wg_commit();
        mbar_arrive_if0(lane | s, bars + 8 * OM, 2);
        wg_wait<0>();
        reg_fence(o);
        float inv[2][4];
#pragma unroll
        for (int hh = 0; hh < 2; hh++)
#pragma unroll
          for (int h = 0; h < 4; h++) inv[hh][h] = rcp(o[40 + 4 * (h >> 1) + 2 * hh + (h & 1)] + 1e-6f);
        if (s) mbar_wait(bars + 8 * AO);
#pragma unroll
        for (int t = 0; t < 10; t++) {
#pragma unroll
          for (int hh = 0; hh < 2; hh++) {
            const float f = t == 2 ? (c < 2 ? inv[hh][0] : inv[hh][1]) : t == 7 ? (c < 2 ? inv[hh][2] : inv[hh][3]) : inv[hh][(8 * t) / 20];
            pq[2 * t + hh] = pack2(o[4 * t + 2 * hh] * f, o[4 * t + 2 * hh + 1] * f);
            stg32(gout + t * 1024 + hh * 128, pq[2 * t + hh]);
          }
        }
        __syncwarp();
        mbar_arrive_if0(lane, bs8 + 8 * AO, 2);
        TLW(16 + s);
      }
      float acc[40];
#pragma unroll
      for (int r = 0; r < 20; r++) { acc[2 * r] = bf_lo(hp[r]); acc[2 * r + 1] = bf_hi(hp[r]); }
      reg_fence(acc);
#pragma unroll
      for (int t = 0; t < 8; t++) {
        mbar_wait(bars + 8 * (FWO + t));
        if (t) mbar_wait(bs8 + 8 * (AO + t));
        TLW(160 + 8 * s + t);
        if (t == 1) TLW(20 + s);
        const Desc da = mkdesc(0, (t - 1) * PAGE, 1024, 128, 0);
        const Desc db = mkdesc(0, 10 * PAGE + (t < 2 ? t ^ 1 : t) * 15360, 5120, 512, 2);
        wg_fence();
#pragma unroll
        for (int ks = 0; ks < 5; ks++) {
          if (t == 0) wgmma_rs<80, 1>(acc, pq[4 * ks], pq[4 * ks + 1], pq[4 * ks + 2], pq[4 * ks + 3], db + 64 * ks, 1);
          else wgmma_ss<80, 0, 1>(acc, da + 128 * ks, db + 64 * ks, 1);
        }
        wg_commit();
        if (t > 1) {
          wg_wait<1>();
          mbar_arrive_if0(lane, bs8 + 8 * (DW + t - 1), 2);
        }
      }
      wg_wait<0>();
      reg_fence(acc);
      mbar_arrive_if0(lane, bs8 + 8 * (DW + 7), 2);
      TLW(22 + s);
#pragma unroll
      for (int r = 0; r < 20; r++) {
        hp[r] = pack2(acc[2 * r], acc[2 * r + 1]);
        stg32(gout + 32 * 8 * 24576 + (r >> 1) * 1024 + (r & 1) * 128, hp[r]);
      }
      __syncwarp();
      mbar_arrive_if0(lane, bs8 + 8 * AH, 2);
      TLW(24 + s);
    }
    float accf[96];
    uint4 hs[4];
    const uint4* hsp = scr->hstat + ((2 * i + s) * 8 + 2 * c) * 64 + 16 * w + g;
    uint32_t rk[2];
    float3 gk[2];
#pragma unroll
    for (int t = 0; t < 8; t++) {
      mbar_wait(bars + 8 * (FW1 + t));
      if (t) mbar_wait(bs8 + 8 * (AH + t));
      TLW(176 + 8 * s + t);
      if (t == 1) TLW(26 + s);
      const Desc da = drs + ((t + 2) % 3) * (PAGE / 16), db = mkdesc(0, (7 + 3 * (t % 5)) * PAGE, 8192, 1024, 1);
      wg_fence();
#pragma unroll
      for (int ks = 0; ks < 5; ks++) {
        const Desc dk = ks < 4 ? db + 128 * ks : mkdesc(0, (7 + 3 * (t % 5)) * PAGE + 24576, 2048, 1024, 1);
        if (t == 0) wgmma_rs<192, 1>(accf, hp[4 * ks], hp[4 * ks + 1], hp[4 * ks + 2], hp[4 * ks + 3], dk, ks != 0);
        else wgmma_ss<192, 0, 1>(accf, da + 128 * ks, dk, 1);
      }
      if (t == 7) wgmma_rs<192, 0>(accf, rk[0], rk[1], 0, 0, mkdesc(0, OFF_RK1, 0, 128, 0), 1);
      wg_commit();
      if (t == 5) {
        while (__any_sync(0xffffffffu, ((hs[0].y ^ epoch) | (hs[0].w ^ epoch) | (hs[1].y ^ epoch) | (hs[1].w ^ epoch) | (hs[2].y ^ epoch) |
                                        (hs[2].w ^ epoch) | (hs[3].y ^ epoch) | (hs[3].w ^ epoch)) != 0)) {
#pragma unroll
          for (int m = 0; m < 4; m++) hs[m] = ll_load(hsp + (m >> 1) * 64 + 8 * (m & 1));
        }
#pragma unroll
        for (int hh = 0; hh < 2; hh++) {
          float sm = __uint_as_float(hs[hh].x) + __uint_as_float(hs[2 + hh].x), sq = __uint_as_float(hs[hh].z) + __uint_as_float(hs[2 + hh].z);
#pragma unroll
          for (int o = 1; o < 4; o <<= 1) {
            sm += __shfl_xor_sync(0xffffffffu, sm, o);
            sq += __shfl_xor_sync(0xffffffffu, sq, o);
          }
          gk[hh].x = sm;
          gk[hh].y = sq;
        }
      }
      if (t == 6) {
        mbar_wait(bars + 8 * SIDE2);
#pragma unroll
        for (int hh = 0; hh < 2; hh++) {
          const float mean = gk[hh].x * (1.f / 640.f), var = fmaxf(fmaf(-mean, mean, gk[hh].y * (1.f / 640.f)), 0.f) + 1e-5f;
          const float a = rsqrtf(var);
          rk[hh] = rk1_frag(-mean, var * a, c);
          gk[hh] = make_float3(0.7978845608028654f * a, 0.7978845608028654f * 0.044715f * a * a * a, 0.5f * a);
        }
      }
      if (t == 0) {
        wg_wait<0>();
        mbar_arrive_if0(lane, bs8 + 8 * DF, 2);
        float sm[2] = {0.f, 0.f}, sq[2] = {0.f, 0.f};
#pragma unroll
        for (int m = 0; m < 10; m++) {
          const float2 b = lds64(sb + OFF_B2 + (8 * m + 2 * c) * 4);
#pragma unroll
          for (int hh = 0; hh < 2; hh++) {
            const float h0 = bf_lo(hp[2 * m + hh]), h1 = bf_hi(hp[2 * m + hh]);
            sm[hh] += h0 + h1;
            sq[hh] = fmaf(h0, h0, fmaf(h1, h1, sq[hh]));
            const float v0 = b.x + h0, v1 = b.y + h1;
            const int e = 4 * m + 2 * hh;
            if (m < 8) { accg[e] = v0; accg[e + 1] = v1; accg[32 + e] = 0.f; accg[33 + e] = 0.f; }
            else { accg[e + 32] = q ? 0.f : v0; accg[e + 33] = q ? 0.f : v1; accg[e + 40] = q ? v0 : 0.f; accg[e + 41] = q ? v1 : 0.f; }
          }
        }
        reg_fence(accg);
#pragma unroll
        for (int o = 1; o < 4; o <<= 1) {
#pragma unroll
          for (int hh = 0; hh < 2; hh++) {
            sm[hh] += __shfl_xor_sync(0xffffffffu, sm[hh], o);
            sq[hh] += __shfl_xor_sync(0xffffffffu, sq[hh], o);
          }
        }
        if (c < 2) ll_store(scr->hstat + ((2 * i + s) * 8 + j) * 64 + 16 * w + g + 8 * c, c ? sm[1] : sm[0], c ? sq[1] : sq[0], epoch);
      } else if (t > 1) {
        wg_wait<1>();
        mbar_arrive_if0(lane, bs8 + 8 * (DF + t - 1), 2);
      }
      if (t == 3) {
#pragma unroll
        for (int m = 0; m < 4; m++) hs[m] = ll_load(hsp + (m >> 1) * 64 + 8 * (m & 1));
      }
    }
    wg_wait<0>();
    reg_fence(accf);
    mbar_arrive_if0(lane, bs8 + 8 * (DF + 7), 2);
    TLW(28 + s);
    uint32_t fp[48];
#pragma unroll
    for (int t = 0; t < 12; t++) {
      if (t < 3) {
#pragma unroll
        for (int e = 16 * t; e < 16 * t + 16; e++) {
          fp[e] = pack2(gelu(accf[2 * e], gk[e & 1]), gelu(accf[2 * e + 1], gk[e & 1]));
          stg32(gout + 64 * 8 * 24576 + (e >> 1) * 1024 + (e & 1) * 128, fp[e]);
        }
        __syncwarp();
        mbar_arrive_if0(lane, bs12 + 8 * (AF + t), 2);
        if (t == 2) TLW(30 + s);
      }
      mbar_wait(bars + 8 * (FW2 + t));
      if (t >= 3) mbar_wait(bs12 + 8 * (AF + t));
      TLW(192 + 12 * s + t);
      if (t == 3) TLW(32 + s);
      const Desc da = drs + ((t + 1) & 3) * 512, db = mkdesc(0, OFF_W2 + ((0x321045 >> (4 * (t % 6))) & 7) * 24576, 8192, 1024, 1);
      wg_fence();
#pragma unroll
      for (int ks = 0; ks < 4; ks++) {
        if (t < 3) wgmma_rs<160, 1>(accg, fp[16 * t + 4 * ks], fp[16 * t + 4 * ks + 1], fp[16 * t + 4 * ks + 2], fp[16 * t + 4 * ks + 3], db + 128 * ks, 1);
        else wgmma_ss<160, 0, 1>(accg, da + 128 * ks, db + 128 * ks, 1);
      }
      wg_commit();
      if (t != 0 && t != 3) {
        wg_wait<1>();
        mbar_arrive_if0(lane, bs12 + 8 * (DG + t - 1), 2);
        if (t == 7) mbar_arrive_remote_if0(lane, sb_peer + OFF_BAR + 8 * PF);
      }
      if (t == 2) {
        wg_wait<0>();
        mbar_arrive_if0(lane, bs12 + 8 * (DG + 2), 2);
      }
    }
    mbar_wait_cluster(bars + 8 * PF);
    wg_wait<0>();
    reg_fence(accg);
    mbar_arrive_if0(lane, bs12 + 8 * (DG + 11), 2);
    TLW(34 + s);
    {
      const uint32_t buf = OFF_W2 + 5 * 24576 + s * PAGE + tid * 16;
#pragma unroll
      for (int e = 0; e < 8; e++) {
        const float a = accg[64 + e], b = accg[72 + e];
        accg[64 + e] = q ? a : b;
        accg[72 + e] = q ? b : a;
      }
#pragma unroll
      for (int m = 0; m < 5; m++) {
        const float* a = accg + 32 + 8 * m;
        asm volatile("st.async.shared::cluster.mbarrier::complete_tx::bytes.v4.b32 [%0], {%1,%2,%3,%4}, [%5];"
                     ::"r"(sb_peer + buf + m * 2048), "r"(pack2(a[0], a[1])), "r"(pack2(a[2], a[3])), "r"(pack2(a[4], a[5])),
                     "r"(pack2(a[6], a[7])), "r"(sb_peer + OFF_BAR + 8 * (RX + s)) : "memory");
      }
      TLW(58 + s);
      mbar_wait(bs12 + 8 * (DG + 11));
      mbar_wait_cluster(bars + 8 * (RX + s));
      TLW(60 + s);
      float4 rx[5];
#pragma unroll
      for (int m = 0; m < 5; m++) rx[m] = lds128(sb + buf + m * 2048);
      const uint32_t stg = rs + w * 2816;
      const uint32_t sa = stg + (lane & 15) * 176 + (lane >> 4) * 16;
#pragma unroll
      for (int ks = 0; ks < 5; ks++) {
        const uint32_t u[4] = {__float_as_uint(rx[ks].x), __float_as_uint(rx[ks].y), __float_as_uint(rx[ks].z), __float_as_uint(rx[ks].w)};
        const float* a = accg + (ks < 4 ? 8 * ks : 72);
        stsm4(sa + ks * 32, pack2(a[0] + bf_lo(u[0]), a[1] + bf_hi(u[0])), pack2(a[2] + bf_lo(u[1]), a[3] + bf_hi(u[1])),
              pack2(a[4] + bf_lo(u[2]), a[5] + bf_hi(u[2])), pack2(a[6] + bf_lo(u[3]), a[7] + bf_hi(u[3])));
      }
      __syncwarp();
#pragma unroll
      for (int m = 0; m < 4; m++) rx[m] = lds128(stg + (4 * m + (lane >> 3)) * 176 + (lane & 7) * 16);
      rx[4] = lds128(stg + (lane >> 1) * 176 + 128 + (lane & 1) * 16);
      __nv_bfloat16* outp = out + (row0 + (lane >> 3)) * 640 + cF + (lane & 7) * 8;
#pragma unroll
      for (int m = 0; m < 4; m++) *reinterpret_cast<float4*>(outp + m * 4 * 640) = rx[m];
      *reinterpret_cast<float4*>(out + (row0 + (lane >> 1)) * 640 + cR + (lane & 1) * 8) = rx[4];
    }
    mbar_arrive_if0(lane, bars + 8 * END, 1);
    TLW(36 + s);
  }
}

typedef CUresult (*EncodeFn)(CUtensorMap*, CUtensorMapDataType, cuuint32_t, void*, const cuuint64_t*, const cuuint64_t*,
                             const cuuint32_t*, const cuuint32_t*, CUtensorMapInterleave, CUtensorMapSwizzle,
                             CUtensorMapL2promotion, CUtensorMapFloatOOBfill);

void make_map(EncodeFn enc, CUtensorMap* tm, const void* base, int rows, int cols, int box_rows, int box_cols, int group, int natom,
              CUtensorMapSwizzle sw) {
  const cuuint64_t dims[3] = {(cuuint64_t)(natom ? group : cols), (cuuint64_t)rows, (cuuint64_t)(cols / group)};
  const cuuint64_t strides[2] = {(cuuint64_t)cols * 2, (cuuint64_t)group * 2};
  const cuuint32_t box[3] = {(cuuint32_t)box_cols, (cuuint32_t)box_rows, (cuuint32_t)natom}, es[3] = {1, 1, 1};
  enc(tm, CU_TENSOR_MAP_DATA_TYPE_BFLOAT16, natom ? 3 : 2, const_cast<void*>(base), dims, strides, box, es,
      CU_TENSOR_MAP_INTERLEAVE_NONE, sw, CU_TENSOR_MAP_L2_PROMOTION_L2_128B, CU_TENSOR_MAP_FLOAT_OOB_FILL_NONE);
}

}

extern "C" void kernel_launch(void* const* d_in, const int* in_sizes, int n_in, void* d_out, int out_size) {
  const __nv_bfloat16* x = (const __nv_bfloat16*)d_in[0];
  const __nv_bfloat16* wqkv = (const __nv_bfloat16*)d_in[1];
  const __nv_bfloat16* wo = (const __nv_bfloat16*)d_in[2];
  const __nv_bfloat16* w1 = (const __nv_bfloat16*)d_in[4];
  const __nv_bfloat16* b1 = (const __nv_bfloat16*)d_in[5];
  const __nv_bfloat16* w2 = (const __nv_bfloat16*)d_in[6];
  const __nv_bfloat16* b2 = (const __nv_bfloat16*)d_in[7];

  void* fn = nullptr;
  cudaDriverEntryPointQueryResult qr;
  cudaGetDriverEntryPoint("cuTensorMapEncodeTiled", &fn, cudaEnableDefault, &qr);
  EncodeFn enc = (EncodeFn)fn;
  const CUtensorMapSwizzle S128 = CU_TENSOR_MAP_SWIZZLE_128B, S64 = CU_TENSOR_MAP_SWIZZLE_64B;
  Maps maps;
  make_map(enc, &maps.m[M_X], x, 2048, 640, 128, 64, 64, 0, S128);
  make_map(enc, &maps.m[M_KVF], wqkv, 640, 1920, 32, 64, 640, 2, S128);
  make_map(enc, &maps.m[M_KVH], wqkv, 640, 1920, 32, 32, 64, 0, S128);
  make_map(enc, &maps.m[M_Q2], wqkv, 640, 1920, 64, 32, 32, 2, S64);
  make_map(enc, &maps.m[M_QR], wqkv, 640, 1920, 64, 16, 64, 0, S64);
  make_map(enc, &maps.m[M_WO2], wo, 640, 640, 80, 32, 32, 2, S64);
  make_map(enc, &maps.m[M_WOR], wo, 640, 640, 80, 16, 64, 0, S64);
  make_map(enc, &maps.m[M_W1], w1, 640, 1536, 64, 64, 64, 3, S128);
  make_map(enc, &maps.m[M_W1R], w1, 640, 1536, 16, 64, 64, 3, S128);
  make_map(enc, &maps.m[M_W2F], w2, 1536, 640, 64, 64, 64, 0, S128);
  make_map(enc, &maps.m[M_W2H], w2, 1536, 640, 64, 32, 64, 0, S128);
  cudaFuncSetAttribute(fused_block_kernel, cudaFuncAttributeMaxDynamicSharedMemorySize, SMEM_BYTES);
  void* scr = nullptr;
  cudaGetSymbolAddress(&scr, g_scratch);
  fused_block_kernel<<<128, 384, SMEM_BYTES>>>((Scratch*)scr, wqkv, wo, w1, w2, b2, b1, (__nv_bfloat16*)d_out, maps);
}
```

```cpp
#include <cuda_runtime.h>
#include <cuda_bf16.h>
#include <cuda.h>
#include <stdint.h>

namespace {

struct Desc { uint32_t base, off, hi; };
__device__ __forceinline__ Desc operator+(Desc d, uint32_t o) { return Desc{d.base, d.off + o, d.hi}; }
template <int TA, int TB> __device__ __forceinline__ void wgmma_ss_n48(float (&d)[24], Desc a, Desc b, int sc) {
  asm volatile("{.reg .pred p; .reg .b32 t, u; .reg .b64 da, db; setp.ne.b32 p, %30, 0; add.u32 t, %24, %25; mov.b64 da, {t, %26}; add.u32 u, %27, %28; mov.b64 db, {u, %29};"
    "wgmma.mma_async.sync.aligned.m64n48k16.f32.bf16.bf16 {%0,%1,%2,%3,%4,%5,%6,%7,%8,%9,%10,%11,%12,%13,%14,%15,%16,%17,%18,%19,%20,%21,%22,%23}, da, db, p, 1, 1, %31, %32;}"
    : "+f"(d[0]),"+f"(d[1]),"+f"(d[2]),"+f"(d[3]),"+f"(d[4]),"+f"(d[5]),"+f"(d[6]),"+f"(d[7]),"+f"(d[8]),"+f"(d[9]),"+f"(d[10]),"+f"(d[11]),"+f"(d[12]),"+f"(d[13]),"+f"(d[14]),"+f"(d[15]),"+f"(d[16]),"+f"(d[17]),"+f"(d[18]),"+f"(d[19]),"+f"(d[20]),"+f"(d[21]),"+f"(d[22]),"+f"(d[23])
    : "r"(a.base), "r"(a.off), "r"(a.hi), "r"(b.base), "r"(b.off), "r"(b.hi), "r"(sc), "n"(TA), "n"(TB));
}
template <int TA, int TB> __device__ __forceinline__ void wgmma_ss_n80(float (&d)[40], Desc a, Desc b, int sc) {
  asm volatile("{.reg .pred p; .reg .b32 t, u; .reg .b64 da, db; setp.ne.b32 p, %46, 0; add.u32 t, %40, %41; mov.b64 da, {t, %42}; add.u32 u, %43, %44; mov.b64 db, {u, %45};"
    "wgmma.mma_async.sync.aligned.m64n80k16.f32.bf16.bf16 {%0,%1,%2,%3,%4,%5,%6,%7,%8,%9,%10,%11,%12,%13,%14,%15,%16,%17,%18,%19,%20,%21,%22,%23,%24,%25,%26,%27,%28,%29,%30,%31,%32,%33,%34,%35,%36,%37,%38,%39}, da, db, p, 1, 1, %47, %48;}"
    : "+f"(d[0]),"+f"(d[1]),"+f"(d[2]),"+f"(d[3]),"+f"(d[4]),"+f"(d[5]),"+f"(d[6]),"+f"(d[7]),"+f"(d[8]),"+f"(d[9]),"+f"(d[10]),"+f"(d[11]),"+f"(d[12]),"+f"(d[13]),"+f"(d[14]),"+f"(d[15]),"+f"(d[16]),"+f"(d[17]),"+f"(d[18]),"+f"(d[19]),"+f"(d[20]),"+f"(d[21]),"+f"(d[22]),"+f"(d[23]),"+f"(d[24]),"+f"(d[25]),"+f"(d[26]),"+f"(d[27]),"+f"(d[28]),"+f"(d[29]),"+f"(d[30]),"+f"(d[31]),"+f"(d[32]),"+f"(d[33]),"+f"(d[34]),"+f"(d[35]),"+f"(d[36]),"+f"(d[37]),"+f"(d[38]),"+f"(d[39])
    : "r"(a.base), "r"(a.off), "r"(a.hi), "r"(b.base), "r"(b.off), "r"(b.hi), "r"(sc), "n"(TA), "n"(TB));
}
template <int TA, int TB> __device__ __forceinline__ void wgmma_ss_n160(float (&d)[80], Desc a, Desc b, int sc) {
  asm volatile("{.reg .pred p; .reg .b32 t, u; .reg .b64 da, db; setp.ne.b32 p, %86, 0; add.u32 t, %80, %81; mov.b64 da, {t, %82}; add.u32 u, %83, %84; mov.b64 db, {u, %85};"
    "wgmma.mma_async.sync.aligned.m64n160k16.f32.bf16.bf16 {%0,%1,%2,%3,%4,%5,%6,%7,%8,%9,%10,%11,%12,%13,%14,%15,%16,%17,%18,%19,%20,%21,%22,%23,%24,%25,%26,%27,%28,%29,%30,%31,%32,%33,%34,%35,%36,%37,%38,%39,%40,%41,%42,%43,%44,%45,%46,%47,%48,%49,%50,%51,%52,%53,%54,%55,%56,%57,%58,%59,%60,%61,%62,%63,%64,%65,%66,%67,%68,%69,%70,%71,%72,%73,%74,%75,%76,%77,%78,%79}, da, db, p, 1, 1, %87, %88;}"
    : "+f"(d[0]),"+f"(d[1]),"+f"(d[2]),"+f"(d[3]),"+f"(d[4]),"+f"(d[5]),"+f"(d[6]),"+f"(d[7]),"+f"(d[8]),"+f"(d[9]),"+f"(d[10]),"+f"(d[11]),"+f"(d[12]),"+f"(d[13]),"+f"(d[14]),"+f"(d[15]),"+f"(d[16]),"+f"(d[17]),"+f"(d[18]),"+f"(d[19]),"+f"(d[20]),"+f"(d[21]),"+f"(d[22]),"+f"(d[23]),"+f"(d[24]),"+f"(d[25]),"+f"(d[26]),"+f"(d[27]),"+f"(d[28]),"+f"(d[29]),"+f"(d[30]),"+f"(d[31]),"+f"(d[32]),"+f"(d[33]),"+f"(d[34]),"+f"(d[35]),"+f"(d[36]),"+f"(d[37]),"+f"(d[38]),"+f"(d[39]),"+f"(d[40]),"+f"(d[41]),"+f"(d[42]),"+f"(d[43]),"+f"(d[44]),"+f"(d[45]),"+f"(d[46]),"+f"(d[47]),"+f"(d[48]),"+f"(d[49]),"+f"(d[50]),"+f"(d[51]),"+f"(d[52]),"+f"(d[53]),"+f"(d[54]),"+f"(d[55]),"+f"(d[56]),"+f"(d[57]),"+f"(d[58]),"+f"(d[59]),"+f"(d[60]),"+f"(d[61]),"+f"(d[62]),"+f"(d[63]),"+f"(d[64]),"+f"(d[65]),"+f"(d[66]),"+f"(d[67]),"+f"(d[68]),"+f"(d[69]),"+f"(d[70]),"+f"(d[71]),"+f"(d[72]),"+f"(d[73]),"+f"(d[74]),"+f"(d[75]),"+f"(d[76]),"+f"(d[77]),"+f"(d[78]),"+f"(d[79])
    : "r"(a.base), "r"(a.off), "r"(a.hi), "r"(b.base), "r"(b.off), "r"(b.hi), "r"(sc), "n"(TA), "n"(TB));
}
template <int TA, int TB> __device__ __forceinline__ void wgmma_ss_n192(float (&d)[96], Desc a, Desc b, int sc) {
  asm volatile("{.reg .pred p; .reg .b32 t, u; .reg .b64 da, db; setp.ne.b32 p, %102, 0; add.u32 t, %96, %97; mov.b64 da, {t, %98}; add.u32 u, %99, %100; mov.b64 db, {u, %101};"
    "wgmma.mma_async.sync.aligned.m64n192k16.f32.bf16.bf16 {%0,%1,%2,%3,%4,%5,%6,%7,%8,%9,%10,%11,%12,%13,%14,%15,%16,%17,%18,%19,%20,%21,%22,%23,%24,%25,%26,%27,%28,%29,%30,%31,%32,%33,%34,%35,%36,%37,%38,%39,%40,%41,%42,%43,%44,%45,%46,%47,%48,%49,%50,%51,%52,%53,%54,%55,%56,%57,%58,%59,%60,%61,%62,%63,%64,%65,%66,%67,%68,%69,%70,%71,%72,%73,%74,%75,%76,%77,%78,%79,%80,%81,%82,%83,%84,%85,%86,%87,%88,%89,%90,%91,%92,%93,%94,%95}, da, db, p, 1, 1, %103, %104;}"
    : "+f"(d[0]),"+f"(d[1]),"+f"(d[2]),"+f"(d[3]),"+f"(d[4]),"+f"(d[5]),"+f"(d[6]),"+f"(d[7]),"+f"(d[8]),"+f"(d[9]),"+f"(d[10]),"+f"(d[11]),"+f"(d[12]),"+f"(d[13]),"+f"(d[14]),"+f"(d[15]),"+f"(d[16]),"+f"(d[17]),"+f"(d[18]),"+f"(d[19]),"+f"(d[20]),"+f"(d[21]),"+f"(d[22]),"+f"(d[23]),"+f"(d[24]),"+f"(d[25]),"+f"(d[26]),"+f"(d[27]),"+f"(d[28]),"+f"(d[29]),"+f"(d[30]),"+f"(d[31]),"+f"(d[32]),"+f"(d[33]),"+f"(d[34]),"+f"(d[35]),"+f"(d[36]),"+f"(d[37]),"+f"(d[38]),"+f"(d[39]),"+f"(d[40]),"+f"(d[41]),"+f"(d[42]),"+f"(d[43]),"+f"(d[44]),"+f"(d[45]),"+f"(d[46]),"+f"(d[47]),"+f"(d[48]),"+f"(d[49]),"+f"(d[50]),"+f"(d[51]),"+f"(d[52]),"+f"(d[53]),"+f"(d[54]),"+f"(d[55]),"+f"(d[56]),"+f"(d[57]),"+f"(d[58]),"+f"(d[59]),"+f"(d[60]),"+f"(d[61]),"+f"(d[62]),"+f"(d[63]),"+f"(d[64]),"+f"(d[65]),"+f"(d[66]),"+f"(d[67]),"+f"(d[68]),"+f"(d[69]),"+f"(d[70]),"+f"(d[71]),"+f"(d[72]),"+f"(d[73]),"+f"(d[74]),"+f"(d[75]),"+f"(d[76]),"+f"(d[77]),"+f"(d[78]),"+f"(d[79]),"+f"(d[80]),"+f"(d[81]),"+f"(d[82]),"+f"(d[83]),"+f"(d[84]),"+f"(d[85]),"+f"(d[86]),"+f"(d[87]),"+f"(d[88]),"+f"(d[89]),"+f"(d[90]),"+f"(d[91]),"+f"(d[92]),"+f"(d[93]),"+f"(d[94]),"+f"(d[95])
    : "r"(a.base), "r"(a.off), "r"(a.hi), "r"(b.base), "r"(b.off), "r"(b.hi), "r"(sc), "n"(TA), "n"(TB));
}
template <int TB> __device__ __forceinline__ void wgmma_rs_n80(float (&d)[40], uint32_t a0, uint32_t a1, uint32_t a2, uint32_t a3, Desc b, int sc) {
  asm volatile("{.reg .pred p; .reg .b32 u; .reg .b64 db; setp.ne.b32 p, %47, 0; add.u32 u, %44, %45; mov.b64 db, {u, %46};"
    "wgmma.mma_async.sync.aligned.m64n80k16.f32.bf16.bf16 {%0,%1,%2,%3,%4,%5,%6,%7,%8,%9,%10,%11,%12,%13,%14,%15,%16,%17,%18,%19,%20,%21,%22,%23,%24,%25,%26,%27,%28,%29,%30,%31,%32,%33,%34,%35,%36,%37,%38,%39}, {%40,%41,%42,%43}, db, p, 1, 1, %48;}"
    : "+f"(d[0]),"+f"(d[1]),"+f"(d[2]),"+f"(d[3]),"+f"(d[4]),"+f"(d[5]),"+f"(d[6]),"+f"(d[7]),"+f"(d[8]),"+f"(d[9]),"+f"(d[10]),"+f"(d[11]),"+f"(d[12]),"+f"(d[13]),"+f"(d[14]),"+f"(d[15]),"+f"(d[16]),"+f"(d[17]),"+f"(d[18]),"+f"(d[19]),"+f"(d[20]),"+f"(d[21]),"+f"(d[22]),"+f"(d[23]),"+f"(d[24]),"+f"(d[25]),"+f"(d[26]),"+f"(d[27]),"+f"(d[28]),"+f"(d[29]),"+f"(d[30]),"+f"(d[31]),"+f"(d[32]),"+f"(d[33]),"+f"(d[34]),"+f"(d[35]),"+f"(d[36]),"+f"(d[37]),"+f"(d[38]),"+f"(d[39])
    : "r"(a0), "r"(a1), "r"(a2), "r"(a3), "r"(b.base), "r"(b.off), "r"(b.hi), "r"(sc), "n"(TB));
}
template <int TB> __device__ __forceinline__ void wgmma_rs_n96(float (&d)[48], uint32_t a0, uint32_t a1, uint32_t a2, uint32_t a3, Desc b, int sc) {
  asm volatile("{.reg .pred p; .reg .b32 u; .reg .b64 db; setp.ne.b32 p, %55, 0; add.u32 u, %52, %53; mov.b64 db, {u, %54};"
    "wgmma.mma_async.sync.aligned.m64n96k16.f32.bf16.bf16 {%0,%1,%2,%3,%4,%5,%6,%7,%8,%9,%10,%11,%12,%13,%14,%15,%16,%17,%18,%19,%20,%21,%22,%23,%24,%25,%26,%27,%28,%29,%30,%31,%32,%33,%34,%35,%36,%37,%38,%39,%40,%41,%42,%43,%44,%45,%46,%47}, {%48,%49,%50,%51}, db, p, 1, 1, %56;}"
    : "+f"(d[0]),"+f"(d[1]),"+f"(d[2]),"+f"(d[3]),"+f"(d[4]),"+f"(d[5]),"+f"(d[6]),"+f"(d[7]),"+f"(d[8]),"+f"(d[9]),"+f"(d[10]),"+f"(d[11]),"+f"(d[12]),"+f"(d[13]),"+f"(d[14]),"+f"(d[15]),"+f"(d[16]),"+f"(d[17]),"+f"(d[18]),"+f"(d[19]),"+f"(d[20]),"+f"(d[21]),"+f"(d[22]),"+f"(d[23]),"+f"(d[24]),"+f"(d[25]),"+f"(d[26]),"+f"(d[27]),"+f"(d[28]),"+f"(d[29]),"+f"(d[30]),"+f"(d[31]),"+f"(d[32]),"+f"(d[33]),"+f"(d[34]),"+f"(d[35]),"+f"(d[36]),"+f"(d[37]),"+f"(d[38]),"+f"(d[39]),"+f"(d[40]),"+f"(d[41]),"+f"(d[42]),"+f"(d[43]),"+f"(d[44]),"+f"(d[45]),"+f"(d[46]),"+f"(d[47])
    : "r"(a0), "r"(a1), "r"(a2), "r"(a3), "r"(b.base), "r"(b.off), "r"(b.hi), "r"(sc), "n"(TB));
}
template <int TB> __device__ __forceinline__ void wgmma_rs_n160(float (&d)[80], uint32_t a0, uint32_t a1, uint32_t a2, uint32_t a3, Desc b, int sc) {
  asm volatile("{.reg .pred p; .reg .b32 u; .reg .b64 db; setp.ne.b32 p, %87, 0; add.u32 u, %84, %85; mov.b64 db, {u, %86};"
    "wgmma.mma_async.sync.aligned.m64n160k16.f32.bf16.bf16 {%0,%1,%2,%3,%4,%5,%6,%7,%8,%9,%10,%11,%12,%13,%14,%15,%16,%17,%18,%19,%20,%21,%22,%23,%24,%25,%26,%27,%28,%29,%30,%31,%32,%33,%34,%35,%36,%37,%38,%39,%40,%41,%42,%43,%44,%45,%46,%47,%48,%49,%50,%51,%52,%53,%54,%55,%56,%57,%58,%59,%60,%61,%62,%63,%64,%65,%66,%67,%68,%69,%70,%71,%72,%73,%74,%75,%76,%77,%78,%79}, {%80,%81,%82,%83}, db, p, 1, 1, %88;}"
    : "+f"(d[0]),"+f"(d[1]),"+f"(d[2]),"+f"(d[3]),"+f"(d[4]),"+f"(d[5]),"+f"(d[6]),"+f"(d[7]),"+f"(d[8]),"+f"(d[9]),"+f"(d[10]),"+f"(d[11]),"+f"(d[12]),"+f"(d[13]),"+f"(d[14]),"+f"(d[15]),"+f"(d[16]),"+f"(d[17]),"+f"(d[18]),"+f"(d[19]),"+f"(d[20]),"+f"(d[21]),"+f"(d[22]),"+f"(d[23]),"+f"(d[24]),"+f"(d[25]),"+f"(d[26]),"+f"(d[27]),"+f"(d[28]),"+f"(d[29]),"+f"(d[30]),"+f"(d[31]),"+f"(d[32]),"+f"(d[33]),"+f"(d[34]),"+f"(d[35]),"+f"(d[36]),"+f"(d[37]),"+f"(d[38]),"+f"(d[39]),"+f"(d[40]),"+f"(d[41]),"+f"(d[42]),"+f"(d[43]),"+f"(d[44]),"+f"(d[45]),"+f"(d[46]),"+f"(d[47]),"+f"(d[48]),"+f"(d[49]),"+f"(d[50]),"+f"(d[51]),"+f"(d[52]),"+f"(d[53]),"+f"(d[54]),"+f"(d[55]),"+f"(d[56]),"+f"(d[57]),"+f"(d[58]),"+f"(d[59]),"+f"(d[60]),"+f"(d[61]),"+f"(d[62]),"+f"(d[63]),"+f"(d[64]),"+f"(d[65]),"+f"(d[66]),"+f"(d[67]),"+f"(d[68]),"+f"(d[69]),"+f"(d[70]),"+f"(d[71]),"+f"(d[72]),"+f"(d[73]),"+f"(d[74]),"+f"(d[75]),"+f"(d[76]),"+f"(d[77]),"+f"(d[78]),"+f"(d[79])
    : "r"(a0), "r"(a1), "r"(a2), "r"(a3), "r"(b.base), "r"(b.off), "r"(b.hi), "r"(sc), "n"(TB));
}
template <int TB> __device__ __forceinline__ void wgmma_rs_n192(float (&d)[96], uint32_t a0, uint32_t a1, uint32_t a2, uint32_t a3, Desc b, int sc) {
  asm volatile("{.reg .pred p; .reg .b32 u; .reg .b64 db; setp.ne.b32 p, %103, 0; add.u32 u, %100, %101; mov.b64 db, {u, %102};"
    "wgmma.mma_async.sync.aligned.m64n192k16.f32.bf16.bf16 {%0,%1,%2,%3,%4,%5,%6,%7,%8,%9,%10,%11,%12,%13,%14,%15,%16,%17,%18,%19,%20,%21,%22,%23,%24,%25,%26,%27,%28,%29,%30,%31,%32,%33,%34,%35,%36,%37,%38,%39,%40,%41,%42,%43,%44,%45,%46,%47,%48,%49,%50,%51,%52,%53,%54,%55,%56,%57,%58,%59,%60,%61,%62,%63,%64,%65,%66,%67,%68,%69,%70,%71,%72,%73,%74,%75,%76,%77,%78,%79,%80,%81,%82,%83,%84,%85,%86,%87,%88,%89,%90,%91,%92,%93,%94,%95}, {%96,%97,%98,%99}, db, p, 1, 1, %104;}"
    : "+f"(d[0]),"+f"(d[1]),"+f"(d[2]),"+f"(d[3]),"+f"(d[4]),"+f"(d[5]),"+f"(d[6]),"+f"(d[7]),"+f"(d[8]),"+f"(d[9]),"+f"(d[10]),"+f"(d[11]),"+f"(d[12]),"+f"(d[13]),"+f"(d[14]),"+f"(d[15]),"+f"(d[16]),"+f"(d[17]),"+f"(d[18]),"+f"(d[19]),"+f"(d[20]),"+f"(d[21]),"+f"(d[22]),"+f"(d[23]),"+f"(d[24]),"+f"(d[25]),"+f"(d[26]),"+f"(d[27]),"+f"(d[28]),"+f"(d[29]),"+f"(d[30]),"+f"(d[31]),"+f"(d[32]),"+f"(d[33]),"+f"(d[34]),"+f"(d[35]),"+f"(d[36]),"+f"(d[37]),"+f"(d[38]),"+f"(d[39]),"+f"(d[40]),"+f"(d[41]),"+f"(d[42]),"+f"(d[43]),"+f"(d[44]),"+f"(d[45]),"+f"(d[46]),"+f"(d[47]),"+f"(d[48]),"+f"(d[49]),"+f"(d[50]),"+f"(d[51]),"+f"(d[52]),"+f"(d[53]),"+f"(d[54]),"+f"(d[55]),"+f"(d[56]),"+f"(d[57]),"+f"(d[58]),"+f"(d[59]),"+f"(d[60]),"+f"(d[61]),"+f"(d[62]),"+f"(d[63]),"+f"(d[64]),"+f"(d[65]),"+f"(d[66]),"+f"(d[67]),"+f"(d[68]),"+f"(d[69]),"+f"(d[70]),"+f"(d[71]),"+f"(d[72]),"+f"(d[73]),"+f"(d[74]),"+f"(d[75]),"+f"(d[76]),"+f"(d[77]),"+f"(d[78]),"+f"(d[79]),"+f"(d[80]),"+f"(d[81]),"+f"(d[82]),"+f"(d[83]),"+f"(d[84]),"+f"(d[85]),"+f"(d[86]),"+f"(d[87]),"+f"(d[88]),"+f"(d[89]),"+f"(d[90]),"+f"(d[91]),"+f"(d[92]),"+f"(d[93]),"+f"(d[94]),"+f"(d[95])
    : "r"(a0), "r"(a1), "r"(a2), "r"(a3), "r"(b.base), "r"(b.off), "r"(b.hi), "r"(sc), "n"(TB));
}
template <int N, int TA, int TB> __device__ __forceinline__ void wgmma_ss(float (&d)[N / 2], Desc a, Desc b, int sc) {
  if constexpr (N == 48) wgmma_ss_n48<TA, TB>(d, a, b, sc);
  else if constexpr (N == 80) wgmma_ss_n80<TA, TB>(d, a, b, sc);
  else if constexpr (N == 160) wgmma_ss_n160<TA, TB>(d, a, b, sc);
  else if constexpr (N == 192) wgmma_ss_n192<TA, TB>(d, a, b, sc);
}
template <int N, int TB> __device__ __forceinline__ void wgmma_rs(float (&d)[N / 2], uint32_t a0, uint32_t a1, uint32_t a2, uint32_t a3, Desc b, int sc) {
  if constexpr (N == 80) wgmma_rs_n80<TB>(d, a0, a1, a2, a3, b, sc);
  else if constexpr (N == 96) wgmma_rs_n96<TB>(d, a0, a1, a2, a3, b, sc);
  else if constexpr (N == 160) wgmma_rs_n160<TB>(d, a0, a1, a2, a3, b, sc);
  else if constexpr (N == 192) wgmma_rs_n192<TB>(d, a0, a1, a2, a3, b, sc);
}

constexpr uint32_t SMEM_BASE = 1024;
constexpr uint32_t PAGE = 10240;
constexpr uint32_t OFF_RING = 16 * PAGE;
constexpr uint32_t OFF_KVB = 50176;
constexpr uint32_t OFF_KVP = 43008;
constexpr uint32_t OFF_R1 = 35840;
constexpr uint32_t OFF_MISC = 22 * PAGE;
constexpr uint32_t OFF_W2 = OFF_MISC - 6 * 24576;
constexpr uint32_t OFF_BAR = OFF_MISC;
constexpr uint32_t OFF_LN1 = OFF_MISC + 1920;
constexpr uint32_t OFF_RK1 = OFF_MISC + 2944;
constexpr uint32_t OFF_B2 = OFF_MISC + 1600;
constexpr uint32_t OFF_SCR = OFF_MISC + 6784;
constexpr uint32_t SMEM_BYTES = OFF_MISC + 7040;

enum : int {
  RF = 0, FX = 6, FE = 19, RX = 23, RXK = 25,
  RE = 30, PX = 35, PF = 36, SIDE = 37, ZK = 38, RKV = 39, ST1 = 40, XF = 41, KD = 42, CG = 43, KVB = 44, OM = 45, G2 = 46,
  FWO = 50, FW1 = 58, FW2 = 66,
  AO = 80, AH = 96, AF = 112,
  DW = 136, DF = 152, DG = 168,
  SIDE2 = 192, END = 193
};
#define PACE 4

struct __align__(128) Scratch {
  uint8_t act[3 * 32 * 8 * 24576];
  uint4 ln1[2048];
  uint4 cs[4 * 1728];
  uint4 hstat[32 * 8 * 64];
  float kv[8 * 1696];
  uint32_t flag[(3 * 32 + 16) * 32];
  uint32_t epoch;
};
__device__ Scratch g_scratch;

struct Maps { CUtensorMap m[11]; };
enum : int { M_X, M_KVF, M_KVH, M_Q2, M_QR, M_WO2, M_WOR, M_W1, M_W1R, M_W2F, M_W2H };

#define TL(id)
#define TLW(id)
#define TL0(id)
#define TL1(id)
#define TC(v)
#define TS(id, v)

constexpr int SPIN_LIMIT = 1 << 19;

__device__ __forceinline__ bool elect_one() {
  uint32_t p;
  asm volatile("{.reg .pred P; elect.sync _|P, 0xffffffff; selp.u32 %0,1,0,P;}" : "=r"(p));
  return p;
}
__device__ __forceinline__ void mbar_wait(uint32_t bar, uint32_t parity = 0) {
  asm volatile("{.reg .pred p;\nW: mbarrier.try_wait.parity.shared::cta.b64 p, [%0], %1;\n@!p bra W;}" ::"r"(bar), "r"(parity) : "memory");
}
__device__ __forceinline__ void mbar_wait_cluster(uint32_t bar) {
  asm volatile("{.reg .pred p;\nW: mbarrier.try_wait.parity.acquire.cluster.shared::cta.b64 p, [%0], 0;\n@!p bra W;}" ::"r"(bar) : "memory");
}
__device__ __forceinline__ void mbar_wait_wd(uint32_t bar) {
  asm volatile("{.reg .pred p; .reg .u32 n; mov.u32 n, 0;\n"
               "W: mbarrier.try_wait.parity.shared::cta.b64 p, [%0], 0;\n"
               "@p bra D; add.u32 n, n, 1; setp.gt.u32 p, n, %1; @p trap; bra W;\n"
               "D: }" ::"r"(bar), "n"(SPIN_LIMIT) : "memory");
}
__device__ __forceinline__ uint32_t mbar_test(uint32_t bar) {
  uint32_t ok;
  asm volatile("{.reg .pred p; mbarrier.test_wait.parity.shared::cta.b64 p, [%1], 0; selp.u32 %0, 1, 0, p;}" : "=r"(ok) : "r"(bar) : "memory");
  return ok;
}
__device__ __forceinline__ void mbar_arrive(uint32_t bar, uint32_t n) {
  asm volatile("mbarrier.arrive.shared::cta.b64 _, [%0], %1;" ::"r"(bar), "r"(n) : "memory");
}
__device__ __forceinline__ void mbar_arrive_if0(int z, uint32_t bar, uint32_t n) {
  asm volatile("{.reg .pred p; setp.eq.s32 p, %2, 0; @p mbarrier.arrive.shared::cta.b64 _, [%0], %1;}" ::"r"(bar), "r"(n), "r"(z) : "memory");
}
__device__ __forceinline__ void mbar_arrive_remote_if0(int z, uint32_t bar) {
  asm volatile("{.reg .pred p; setp.eq.s32 p, %1, 0; @p mbarrier.arrive.shared::cluster.b64 _, [%0];}" ::"r"(bar), "r"(z) : "memory");
}
__device__ __forceinline__ void mbar_expect(uint32_t bar, uint32_t bytes) {
  asm volatile("mbarrier.arrive.expect_tx.shared::cta.b64 _, [%0], %1;" ::"r"(bar), "r"(bytes) : "memory");
}
__device__ __forceinline__ void tma2d(uint32_t dst, const CUtensorMap* tm, uint32_t bar, int c0, int c1) {
  asm volatile("cp.async.bulk.tensor.2d.shared::cluster.global.mbarrier::complete_tx::bytes [%0],[%1,{%3,%4}],[%2];"
               ::"r"(dst), "l"(tm), "r"(bar), "r"(c0), "r"(c1) : "memory");
}
__device__ __forceinline__ void tma3d(uint32_t dst, const CUtensorMap* tm, uint32_t bar, int c0, int c1, int c2) {
  asm volatile("cp.async.bulk.tensor.3d.shared::cluster.global.mbarrier::complete_tx::bytes [%0],[%1,{%3,%4,%5}],[%2];"
               ::"r"(dst), "l"(tm), "r"(bar), "r"(c0), "r"(c1), "r"(c2) : "memory");
}
__device__ __forceinline__ void bulk_load(uint32_t dst, const void* src, uint32_t bytes, uint32_t bar) {
  asm volatile("cp.async.bulk.shared::cluster.global.mbarrier::complete_tx::bytes [%0],[%1],%2,[%3];"
               ::"r"(dst), "l"(src), "r"(bytes), "r"(bar) : "memory");
}
__device__ __forceinline__ void l2_prefetch(const void* src, uint32_t bytes) {
  asm volatile("cp.async.bulk.prefetch.L2.global [%0], %1;" ::"l"(src), "r"(bytes) : "memory");
}
__device__ __forceinline__ void fence_async_smem() { asm volatile("fence.proxy.async.shared::cta;" ::: "memory"); }
__device__ __forceinline__ void fence_async_global() { asm volatile("fence.proxy.async.global;" ::: "memory"); }
__device__ __forceinline__ void flag_release(uint32_t* p, uint32_t bits) {
  asm volatile("fence.release.gpu;" ::: "memory");
  asm volatile("red.relaxed.gpu.global.xor.b32 [%0], %1;" ::"l"(p), "r"(bits) : "memory");
}
__device__ __forceinline__ uint32_t flag_read(const uint32_t* p, uint32_t epoch) {
  uint32_t v;
  asm volatile("ld.relaxed.gpu.global.u32 %0, [%1];" : "=r"(v) : "l"(p) : "memory");
  return v ^ ((epoch & 1) - 1);
}
__device__ __forceinline__ void flag_wait(const uint32_t* p, uint32_t want, uint32_t epoch) {
  int it = 0;
  while ((flag_read(p, epoch) & want) != want && ++it < SPIN_LIMIT) {}
  asm volatile("fence.acquire.gpu;" ::: "memory");
}
__device__ __forceinline__ void stg32(const void* p, uint32_t v) { asm volatile("st.global.u32 [%0], %1;" ::"l"(p), "r"(v) : "memory"); }
__device__ __forceinline__ void wg_fence() { asm volatile("wgmma.fence.sync.aligned;" ::: "memory"); }
__device__ __forceinline__ void wg_commit() { asm volatile("wgmma.commit_group.sync.aligned;" ::: "memory"); }
template <int N> __device__ __forceinline__ void wg_wait() { asm volatile("wgmma.wait_group.sync.aligned %0;" ::"n"(N) : "memory"); }
template <int N> __device__ __forceinline__ void reg_fence(float (&a)[N]) {
#pragma unroll
  for (int i = 0; i < N; i++) asm volatile("" : "+f"(a[i])::"memory");
}
template <int ID, int N> __device__ __forceinline__ void named_bar() { asm volatile("bar.sync %0, %1;" ::"n"(ID), "n"(N) : "memory"); }
template <int N> __device__ __forceinline__ void reg_fence(uint32_t (&a)[N]) {
#pragma unroll
  for (int i = 0; i < N; i++) asm volatile("" : "+r"(a[i])::"memory");
}
__device__ __forceinline__ Desc mkdesc(uint32_t dyn, uint32_t off, uint32_t lbo, uint32_t sbo, uint32_t swz) {
  return Desc{dyn, ((off + SMEM_BASE) >> 4) + ((lbo >> 4) << 16), (sbo >> 4) | (swz << 30)};
}
__device__ __forceinline__ uint32_t pack2(float lo, float hi) {
  uint32_t r;
  asm("cvt.rn.bf16x2.f32 %0, %1, %2;" : "=r"(r) : "f"(hi), "f"(lo));
  return r;
}
__device__ __forceinline__ float bf_lo(uint32_t v) { return __uint_as_float(v << 16); }
__device__ __forceinline__ float bf_hi(uint32_t v) { return __uint_as_float(v & 0xffff0000u); }
__device__ __forceinline__ void stsm4(uint32_t addr, uint32_t a, uint32_t b, uint32_t c, uint32_t d) {
  asm volatile("stmatrix.sync.aligned.m8n8.x4.shared.b16 [%0], {%1,%2,%3,%4};" ::"r"(addr), "r"(a), "r"(b), "r"(c), "r"(d) : "memory");
}
__device__ __forceinline__ void ldsm4(uint32_t addr, uint32_t* r) {
  asm volatile("ldmatrix.sync.aligned.m8n8.x4.shared.b16 {%0,%1,%2,%3}, [%4];" : "=r"(r[0]), "=r"(r[1]), "=r"(r[2]), "=r"(r[3]) : "r"(addr) : "memory");
}
__device__ __forceinline__ float2 lds64(uint32_t a) {
  float2 v;
  asm volatile("ld.shared.v2.f32 {%0,%1}, [%2];" : "=f"(v.x), "=f"(v.y) : "r"(a) : "memory");
  return v;
}
__device__ __forceinline__ float4 lds128(uint32_t a) {
  float4 v;
  asm volatile("ld.shared.v4.f32 {%0,%1,%2,%3}, [%4];" : "=f"(v.x), "=f"(v.y), "=f"(v.z), "=f"(v.w) : "r"(a) : "memory");
  return v;
}
__device__ __forceinline__ void sts64(uint32_t a, uint32_t x, uint32_t y) {
  asm volatile("st.shared.v2.u32 [%0], {%1,%2};" ::"r"(a), "r"(x), "r"(y) : "memory");
}
__device__ __forceinline__ void sts128(uint32_t a, uint32_t x, uint32_t y, uint32_t z, uint32_t w) {
  asm volatile("st.shared.v4.u32 [%0], {%1,%2,%3,%4};" ::"r"(a), "r"(x), "r"(y), "r"(z), "r"(w) : "memory");
}
__device__ __forceinline__ float ex2(float x) {
  float r;
  asm("ex2.approx.ftz.f32 %0, %1;" : "=f"(r) : "f"(x));
  return r;
}
__device__ __forceinline__ float rcp(float x) {
  float r;
  asm("rcp.approx.ftz.f32 %0, %1;" : "=f"(r) : "f"(x));
  return r;
}
constexpr float LOG2E = 1.4426950408889634f;
__device__ __forceinline__ float phi(float z, float a, float a2) {
  float r = ex2(z * a2) + 1e-6f;
  asm("{.reg .pred p; setp.gt.f32 p, %1, 0f00000000; @p fma.rn.f32 %0, %1, %2, 0f3F800008;}" : "+f"(r) : "f"(z), "f"(a));
  return r;
}
__device__ __forceinline__ float gelu(float z, const float3& k) {
  float th;
  asm("tanh.approx.f32 %0, %1;" : "=f"(th) : "f"(z * fmaf(z * z, k.y, k.x)));
  const float hy = z * k.z;
  return fmaf(hy, th, hy);
}
__device__ __forceinline__ uint32_t rk1_frag(float m, float d, int c) {
  const uint32_t hi = pack2(m, d), lo = pack2(m - bf_lo(hi), d - bf_hi(hi));
  return __byte_perm(c & 2 ? 0u : hi, c == 3 ? 0u : lo, 0x107632541010ull >> (16 * c) & 0xffff);
}
__device__ __forceinline__ void rk1_store(uint32_t addr, float2 cs, uint32_t bb) {
  const uint32_t hi = pack2(cs.x, cs.y), lo = pack2(cs.x - bf_lo(hi), cs.y - bf_hi(hi));
  sts128(addr, __byte_perm(hi, lo, 0x5410), __byte_perm(hi, bb, 0x5410), bb & 0xffffu, 0);
  sts128(addr + 16, __byte_perm(hi, lo, 0x7632), __byte_perm(hi, bb, 0x7632), bb >> 16, 0);
}
constexpr uint32_t ONES = 0x3F803F80u;
__device__ __forceinline__ void ll_store(uint4* p, float a, float b, uint32_t tag) {
  asm volatile("st.relaxed.gpu.global.v4.u32 [%0], {%1,%2,%3,%2};" ::"l"(p), "r"(__float_as_uint(a)), "r"(tag), "r"(__float_as_uint(b)) : "memory");
}
__device__ __forceinline__ uint4 ll_load(const void* p) {
  uint4 v;
  asm volatile("ld.relaxed.gpu.global.v4.u32 {%0,%1,%2,%3}, [%4];" : "=r"(v.x), "=r"(v.y), "=r"(v.z), "=r"(v.w) : "l"(p) : "memory");
  return v;
}
template <int N>
__device__ __forceinline__ void ll_wait(uint4 (&v)[N], const uint4* p, int stride, uint32_t tag) {
  uint32_t bad;
  int it = 0;
  do {
    bad = 0;
#pragma unroll
    for (int m = 0; m < N; m++) v[m] = ll_load(p + m * stride);
#pragma unroll
    for (int m = 0; m < N; m++) bad |= (v[m].y ^ tag) | (v[m].w ^ tag);
  } while (__any_sync(0xffffffffu, bad) && ++it < SPIN_LIMIT);
}
__device__ __forceinline__ void ll_wait2(uint4 (&v)[8], const uint4* p, uint32_t tag) {
  uint32_t bad;
  int it = 0;
  do {
    bad = 0;
#pragma unroll
    for (int m = 0; m < 8; m++) v[m] = ll_load(p + (m >> 1) * 1728 + (m & 1));
#pragma unroll
    for (int m = 0; m < 8; m++) bad |= (v[m].y ^ tag) | (v[m].w ^ tag);
  } while (__any_sync(0xffffffffu, bad) && ++it < SPIN_LIMIT);
}
__device__ __forceinline__ float2 ll_sum4(const uint4* p, uint32_t tag) {
  uint4 v[4];
  ll_wait(v, p, 1728, tag);
  return make_float2((__uint_as_float(v[0].x) + __uint_as_float(v[1].x)) + (__uint_as_float(v[2].x) + __uint_as_float(v[3].x)),
                     (__uint_as_float(v[0].z) + __uint_as_float(v[1].z)) + (__uint_as_float(v[2].z) + __uint_as_float(v[3].z)));
}
__device__ __noinline__ float2 colsum(const __nv_bfloat16* wm, int ld, int h0, int h1) {
  const int lane = threadIdx.x & 31, r4 = lane >> 3;
  float d[8];
#pragma unroll
  for (int e = 0; e < 8; e++) d[e] = 0.f;
#pragma unroll 1
  for (int h = h0; h < h1; h++) {
    const __nv_bfloat16* wp = wm + (4 * h + r4) * ld + 8 * (lane & 7);
    uint4 v[14];
#pragma unroll
    for (int m = 0; m < 14; m++) {
      v[m] = make_uint4(0, 0, 0, 0);
      if (m < 13 || h == 0)
        asm volatile("ld.global.nc.v4.u32 {%0,%1,%2,%3}, [%4];" : "=r"(v[m].x), "=r"(v[m].y), "=r"(v[m].z), "=r"(v[m].w) : "l"(wp));
      wp += 12 * ld;
    }
#pragma unroll
    for (int m = 0; m < 14; m++) {
      d[0] += bf_lo(v[m].x); d[1] += bf_hi(v[m].x); d[2] += bf_lo(v[m].y); d[3] += bf_hi(v[m].y);
      d[4] += bf_lo(v[m].z); d[5] += bf_hi(v[m].z); d[6] += bf_lo(v[m].w); d[7] += bf_hi(v[m].w);
    }
  }
#pragma unroll 1
  for (int o = 8; o < 32; o <<= 1) {
#pragma unroll
    for (int e = 0; e < 8; e++) d[e] += __shfl_xor_sync(0xffffffffu, d[e], o);
  }
  if (r4 & 2) { d[0] = d[4]; d[1] = d[5]; d[2] = d[6]; d[3] = d[7]; }
  return r4 & 1 ? make_float2(d[2], d[3]) : make_float2(d[0], d[1]);
}
template <bool PHI>
__device__ __forceinline__ void ln_pair(const float* z, const float (&a)[2], const float (&a2)[2], uint32_t* o) {
#pragma unroll
  for (int e = 0; e < 4; e++) {
    const int hh = e & 1;
    o[e] = PHI ? pack2(phi(z[2 * e], a[hh], a2[hh]), phi(z[2 * e + 1], a[hh], a2[hh])) : pack2(z[2 * e] * a[hh], z[2 * e + 1] * a[hh]);
  }
}

__global__ void __cluster_dims__(2, 1, 1) __launch_bounds__(384, 1)
fused_block_kernel(Scratch* __restrict__ scr, const __nv_bfloat16* __restrict__ wqkv, const __nv_bfloat16* __restrict__ wo,
                   const __nv_bfloat16* __restrict__ w1, const __nv_bfloat16* __restrict__ w2, const __nv_bfloat16* __restrict__ b2,
                   const __nv_bfloat16* __restrict__ b1, __nv_bfloat16* __restrict__ out,
                   const __grid_constant__ Maps maps) {
  extern __shared__ __align__(1024) uint8_t smem_raw[];
  const uint32_t sb = (uint32_t)__cvta_generic_to_shared(smem_raw);
  const uint32_t bars = sb + OFF_BAR;
  const int warp = __shfl_sync(0xffffffffu, threadIdx.x >> 5, 0);
  const int lane = threadIdx.x & 31;
  if (warp < 3 && elect_one()) asm volatile("prefetch.tensormap [%0];" ::"l"(&maps.m[warp]) : "memory");

  const int cl = blockIdx.x >> 1, q = blockIdx.x & 1;
  const int u7 = ((cl - 36) * 37) >> 8;
  const int oct = cl < 4 ? 0 : cl < 36 ? 1 + 2 * ((cl - 4) & 7) : 2 + 2 * (cl - 36 - 7 * u7);
  const int u4 = cl < 4 ? cl : cl < 36 ? (cl - 4) >> 3 : u7;
  const int i = 2 * (oct & 7) + (u4 >> 1), p = 2 * (oct >> 3) + (u4 & 1);
  const int j = 2 * p + q;
  auto col_f = [](int jj) { return 160 * (jj >> 1) + 16 * (jj & 2) + 64 * (jj & 1); };
  auto col_r = [](int jj) { return 160 * (jj >> 1) + 128 - 64 * (jj & 2) + 16 * (jj & 1); };
  const int cF = col_f(j), cR = col_r(j), role = q ^ (p & 1);

  auto load_kv = [&](int s) {
    const uint32_t dst = sb + (s < 16 ? OFF_RING + (s % 5) * 12288 : (s - 16) * 12288), bar = bars + 8 * (s < 16 ? RF + s % 5 : FE + s - 16);
    tma3d(dst, &maps.m[M_KVF], bar, cF, 32 * s, 1);
    tma2d(dst + 8192, &maps.m[M_KVH], bar, 640 + 640 * role + cR - 16 * q, 32 * s);
    mbar_expect(bar, 10240);
  };
  auto load_x = [&](int c, int b, int slot) {
    tma2d(sb + slot * 16384, &maps.m[M_X], bars + 8 * (FX + b), 64 * c, 128 * i);
    mbar_expect(bars + 8 * (FX + b), 16384);
  };
  auto bar_init = [&](int n, uint32_t cnt) { asm volatile("mbarrier.init.shared::cta.b64 [%0], %1;" ::"r"(bars + 8 * n), "r"(cnt) : "memory"); };

  if (warp < 8 && elect_one()) {
    if (warp == 3) {
      bar_init(RF, 1);
      bar_init(RF + 1, 1);
      bar_init(FX, 1);
      load_x(0, 0, 0);
      load_kv(0);
      load_kv(1);
    }
#pragma unroll
    for (int n = 0; n < 6; n++)
      if (warp > (n == 0 ? 1 : n == 1 ? 0 : -1)) bar_init(6 * warp + n, warp < 5 ? 1 : 8);
    asm volatile("fence.mbarrier_init.release.cluster;" ::: "memory");
  }
  __syncwarp();

  if (warp >= 8) {
    TC(tc0);
    asm volatile("setmaxnreg.dec.sync.aligned.u32 88;");
    TC(tc1);
    if (warp == 8) {
      named_bar<0, 288>();
      TC(tc2);
      asm volatile("barrier.cluster.arrive.relaxed.aligned;" ::: "memory");
      if (elect_one()) {
        load_x(1, 1, 1);
        load_kv(2);
        load_kv(3);
        load_x(2, 2, 2);
        load_kv(4);
        load_x(3, 3, 3);
      }
      __syncwarp();
      TC(tc3);
      asm volatile("barrier.cluster.wait.aligned;" ::: "memory");
      TL(40);
      TS(41, tc0); TS(42, tc1); TS(43, tc2); TS(19, tc3);
      if (elect_one()) {
        auto prefetch_piece = [&](const __nv_bfloat16* wm, uint32_t total, uint32_t off, uint32_t bytes) {
          l2_prefetch(reinterpret_cast<const uint8_t*>(wm) + blockIdx.x * total + off, bytes);
        };
#pragma unroll
        for (int s = 5; s < 16; s++) {
          mbar_wait(bars + 8 * (RE + s % 5), (s / 5 - 1) & 1);
          load_kv(s);
          if (s < 11) load_x(s - 1, s - 1, s - 1);
          if (s == 12) mbar_wait(bars + 8 * XF);
          if (s >= 12) load_kv(s + 4);
          if (s < 13) asm volatile("prefetch.tensormap [%0];" ::"l"(&maps.m[s - 2]) : "memory");
          if (s >= 11) prefetch_piece(wo, 6400, (s - 11) * 1280, 1280);
          TL1(96 + s);
        }
#pragma unroll
        for (int t = 0; t < 10; t++) {
          const int slot = (t + 1) % 5, k0 = 64 * (t < 7 ? t + 3 : t - 7);
          const uint32_t dst = sb + OFF_RING + slot * 12288, bar = bars + 8 * (RF + slot);
          mbar_wait(bars + 8 * (RE + slot), ((t + 11) / 5) & 1);
          tma3d(dst, &maps.m[M_Q2], bar, 0, k0, 5 * p + 3 * q);
          tma2d(dst + 8192, &maps.m[M_QR], bar, 80 * j + 64 - 64 * q, k0);
          mbar_expect(bar, 10240);
          if (t >= 6 && t < 9) load_x(t - 6, t + 4, t - 2);
          if (t < 8) prefetch_piece(w1, 15360, t * 1920, 1920);
          TL1(116 + t);
        }
        mbar_wait(bars + 8 * G2);
#pragma unroll 1
        for (int n = 0; n < 32; n += 4) {
          const int t = (0x41765320u >> n) & 7, k0 = 80 * (t == 0 ? j : t - (t <= j));
          const uint32_t dst = sb + 10 * PAGE + (t < 2 ? t ^ 1 : t) * 15360, bar = bars + 8 * (FWO + t);
          mbar_wait(bars + 8 * (RE + ((0x00432221u >> n) & 15)), n >= 24);
          if (n >= 8) mbar_wait(bars + 8 * (FWO + ((0x41765320u >> (n - 8)) & 7)));
          tma3d(dst, &maps.m[M_WO2], bar, 0, k0, cF >> 5);
          tma2d(dst + 10240, &maps.m[M_WOR], bar, cR, k0);
          mbar_expect(bar, 12800);
          TL1(128 + n / 4);
        }
#pragma unroll 1
        for (int t = 0; t < 8; t++) {
          const uint32_t wb = bars + 8 * (t == 0 ? FWO + 1 : t < 5 ? DW + 2 * t - 1 : DF + t - 5);
          const int jj = t == 0 ? j : t - (t <= j);
          const uint32_t dst = sb + (7 + 3 * (t < 5 ? t : t - 5)) * PAGE, bar = bars + 8 * (FW1 + t);
          mbar_wait(wb);
          if (t) {
            mbar_wait(wb + 64);
            mbar_wait(bars + 8 * (t == 1 ? AH : t < 4 ? FW1 + t - 1 : t == 4 ? AH + 2 : DF + t - 4));
          }
          tma3d(dst, &maps.m[M_W1], bar, 0, col_f(jj), 3 * j);
          tma3d(dst + 24576, &maps.m[M_W1R], bar, 0, col_r(jj), 3 * j);
          mbar_expect(bar, 30720);
          if (t >= 3) prefetch_piece(w2, 15360, (t - 3) * 3072, 3072);
          TL1(136 + t);
        }
#pragma unroll 1
        for (int t = 0; t < 12; t++) {
          const int t6 = t < 6 ? t : t - 6;
          const uint32_t wb = bars + 8 * (t < 6 ? DF + ((0x776544 >> (4 * t)) & 7) : DG + t6);
          const int uu = (0xA95024 >> (2 * t)) & 3, n = (0x924900 >> (2 * t)) & 3;
          const int k0 = 192 * (t < 3 ? j : 2 * (n + (n >= p)) + q) + 64 * uu;
          const uint32_t dst = sb + OFF_W2 + ((0x321045 >> (4 * t6)) & 7) * 24576, bar = bars + 8 * (FW2 + t);
          mbar_wait(wb);
          mbar_wait(wb + (t < 6 ? 64 : 96));
          tma2d(dst, &maps.m[M_W2F], bar, cF, k0);
          tma2d(dst + 8192, &maps.m[M_W2F], bar, cF + 64 - 128 * q, k0);
          tma2d(dst + 16384, &maps.m[M_W2H], bar, cR - 16 * q, k0);
          mbar_expect(bar, 20480);
          TL1(144 + t);
        }
      }
    } else {
      const int unit = i * 8 + j, hw = warp - 9, part = unit & 3, cg = unit >> 2;
      asm volatile("barrier.cluster.arrive.relaxed.aligned;" ::: "memory");
      if (part >= PACE) {
        asm volatile("barrier.cluster.wait.aligned;" ::: "memory");
        mbar_wait_wd(bars + 8 * FX);
      }
      uint32_t epoch;
      asm volatile("ld.relaxed.gpu.global.u32 %0, [%1];" : "=r"(epoch) : "l"(&scr->epoch) : "memory");
      epoch += 1;
      if (hw == 0 && lane < 28 && i < 15) *reinterpret_cast<float4*>(scr->kv + j * 1696 + i * 112 + lane * 4) = make_float4(0.f, 0.f, 0.f, 0.f);
      if (hw == 0) TL(248);
      const int ht = hw * 32 + lane, cpair = part * 1728 + 32 * cg + 4 * (lane & 7) + (lane >> 3);
      if (cg < 30) {
        float2 csum = colsum(wqkv + part * 160 * 1920 + 64 * cg, 1920, hw, hw + 1);
        const uint32_t red = sb + OFF_SCR + lane * 8;
#pragma unroll 1
        for (int h = 0; h < 2; h++) {
          if (hw == h) sts64(red, __float_as_uint(csum.x), __float_as_uint(csum.y));
          named_bar<2, 96>();
          if (hw == h + 1) {
            const float2 a = lds64(red);
            csum.x += a.x;
            csum.y += a.y;
          }
        }
        if (hw == 2) ll_store(scr->cs + cpair, csum.x, csum.y, epoch);
      }
      if (hw == 2) TL(249);
      if (part < PACE) asm volatile("barrier.cluster.wait.aligned;" ::: "memory");
      if (elect_one()) {
        mbar_expect(bars + 8 * (RX + hw), hw == 2 ? 8192 : 10240);
        if (hw == 0) flag_release(scr->flag + (96 + j) * 32, 1u << i);
      }
      __syncwarp();
      if (hw == 2) {
        TL(8);
#pragma unroll 1
        for (int n = lane; n < 40; n += 32) {
          const uint32_t b = *reinterpret_cast<const uint32_t*>(b2 + (n < 32 ? cF + 2 * n : cR + 2 * n - 64));
          sts64(sb + OFF_B2 + n * 8, b << 16, b & 0xffff0000u);
        }
        __syncwarp();
        mbar_wait_wd(bars + 8 * ST1);
        uint4 v[4];
        ll_wait(v, scr->ln1 + 128 * i + lane, 32, epoch);
#pragma unroll
        for (int m = 0; m < 4; m++) {
          const float nm = __uint_as_float(v[m].x) * (-1.f / 640.f);
          const float rstd = rsqrtf(fmaxf(fmaf(-nm, nm, __uint_as_float(v[m].z) * (1.f / 640.f)), 0.f) + 1e-5f);
          sts64(sb + OFF_LN1 + (lane + 32 * m) * 8, __float_as_uint(rstd), __float_as_uint(nm));
        }
      } else {
        const int n = 4 * min(ht, 59);
        int col;
        if (n < 160) col = n + (n < 64 ? 640 + cF : n < 128 ? 1216 + cF : 512 + 640 * role + cR - 16 * q);
        else col = 80 * j + n - 160 + (q ? (n < 224 ? 16 : -64) : 0);
        mbar_wait(bars + 8 * CG);
        uint4 v[8];
        ll_wait2(v, scr->cs + (col >> 1), epoch);
#pragma unroll
        for (int e = 0; e < 2; e++)
          rk1_store(sb + OFF_RK1 + n * 16 + 32 * e,
                    make_float2((__uint_as_float(v[e].x) + __uint_as_float(v[2 + e].x)) + (__uint_as_float(v[4 + e].x) + __uint_as_float(v[6 + e].x)),
                                (__uint_as_float(v[e].z) + __uint_as_float(v[2 + e].z)) + (__uint_as_float(v[4 + e].z) + __uint_as_float(v[6 + e].z))), 0);
        fence_async_smem();
      }
      __syncwarp();
      mbar_arrive_if0(lane, bars + 8 * SIDE, hw == 2 ? 2 : 3);
      if (hw != 1) TL(11 - hw / 2);
      if (elect_one()) {
#pragma unroll 1
        for (int n = FWO + 50 * hw; n < FWO + 50 * hw + 50; n += 10) {
#pragma unroll
          for (int e = 0; e < 10; e++) bar_init(n + e, n < AO ? 1 : 8);
        }
        mbar_arrive(bars + 8 * G2, hw == 2 ? 2 : 3);
      }
      __syncwarp();
      {
        if (hw == 2) {
          flag_wait(scr->flag + (96 + j) * 32, 0xffffu, epoch);
          fence_async_global();
          mbar_wait_wd(bars + 8 * RKV);
          if (elect_one()) {
            asm volatile("cp.reduce.async.bulk.global.shared::cta.bulk_group.add.f32 [%0], [%1], 6720;" ::"l"(scr->kv + j * 1696), "r"(sb + OFF_KVP) : "memory");
            asm volatile("cp.async.bulk.commit_group;" ::: "memory");
            asm volatile("cp.async.bulk.wait_group 0;" ::: "memory");
            flag_release(scr->flag + (104 + j) * 32, 1u << i);
          }
          TL(5);
        } else {
          mbar_wait_wd(bars + 8 * ZK);
#pragma unroll 1
          for (int m = 0; m < 15; m += 3) {
#pragma unroll
            for (int e = 0; e < 3; e++) sts128(sb + OFF_KVB + ((m + e) * 64 + ht) * 16, 0, 0, 0, 0);
          }
        }
        const int d0 = ht < 80 ? (ht * 205) >> 10 : ht - 80, pt = ht - 5 * d0;
        uint32_t da[5];
#pragma unroll
        for (int m = 0; m < 5; m++) {
          const int d = d0 + 16 * m, head = (d * 205) >> 12, n = 20 * head + 4 * pt;
          da[m] = sb + OFF_KVB + d * 16 + (ht < 80 ? (n >> 3) * 1280 + (n & 7) * 2 : (10 + (head >> 1)) * 1280 + (head & 1));
        }
        const float* ksrc = scr->kv + j * 1696 + (ht < 80 ? 4 * ht : 1600 + (d0 & 12));
        const int kstep = ht < 80 ? 320 : 16;
        reg_fence(da);
        named_bar<2, 96>();
        flag_wait(scr->flag + (104 + j) * 32, 0xffffu, epoch);
        if (hw == 0) TL(6);
        uint4 v[5];
#pragma unroll
        for (int m = 0; m < 5; m++) v[m] = ll_load(ksrc + m * kstep);
#pragma unroll
        for (int m = 0; m < 5; m++) {
          const uint32_t lo = pack2(__uint_as_float(v[m].x), __uint_as_float(v[m].y)), hi = pack2(__uint_as_float(v[m].z), __uint_as_float(v[m].w));
          const uint32_t zz = __byte_perm(lane & 2 ? hi : lo, 0, lane & 1 ? 0x4432 : 0x4410) << (16 * (da[m] & 1));
          if (ht < 80) sts64(da[m], lo, hi);
          else sts128(da[m] & ~1u, zz, zz, zz, zz);
        }
        fence_async_smem();
        __syncwarp();
        mbar_arrive_if0(lane, bars + 8 * KVB, hw == 2 ? 2 : 3);
        if (hw == 0) TL(7);
      }

      if (hw == 2) {
        if (cg < 24) {
          const float2 d = colsum(w1 + part * 160 * 1536 + 64 * cg, 1536, 0, 3);
          ll_store(scr->cs + 960 + cpair, d.x, d.y, epoch);
        }
        mbar_wait_wd(bars + 8 * (DW + 15));
#pragma unroll 1
        for (int n = lane; n < 96; n += 32)
          rk1_store(sb + OFF_RK1 + n * 32, ll_sum4(scr->cs + 960 + 96 * j + n, epoch), *reinterpret_cast<const uint32_t*>(b1 + 192 * j + 2 * n));
        fence_async_smem();
        __syncwarp();
        mbar_arrive_if0(lane, bars + 8 * SIDE2, 8);
        TL(18);
        const uint32_t eb = bars + 8 * (AF + 12 * ((lane >> 1) & 1) + 1 + (lane & 1));
        uint32_t pm = 15;
        do {
          mbar_wait_wd(__shfl_sync(0xffffffffu, eb, __ffs(pm) - 1));
          const uint32_t ok = mbar_test(eb) & (pm >> lane);
          if (ok) flag_release(scr->flag + (64 + 2 * i + (lane >> 1)) * 32, 0x100u << (8 * (lane & 1) + j));
          pm &= ~__ballot_sync(0xffffffffu, ok);
        } while (pm);
        mbar_wait_wd(bars + 8 * END);
        if (blockIdx.x == 0 && lane == 0) scr->epoch = epoch;
      } else {
        const int s = hw;
#pragma unroll 1
        for (int ph = 0; ph < 3; ph++) {
          const uint32_t ab = bars + 8 * (ph < 2 ? AO + 16 * ph + 8 * s : AF + 12 * s);
          const uint32_t bytes = ph < 2 ? 10240 : 8192;
          uint8_t* gb = scr->act + (ph * 32 + 2 * i + s) * 8 * 24576;
          uint32_t* fl = scr->flag + (ph * 32 + 2 * i + s) * 32;
          const int r = min(lane, 8);
          int cc = r + (r >= j), bit = cc, slot, wb, off = 0;
          if (ph == 0) {
            slot = r;
            wb = s ? DW + r + 1 : AO + 8;
          } else if (ph == 1) {
            slot = s ? 4 + ((0x0924u >> (2 * r)) & 3) : r & 3;
            wb = s ? (r < 3 ? DW + 15 : DF + 6 + r) : (r < 4 ? DW + 9 + r : DF + r - 3);
          } else {
            const int uu = (r * 11) >> 5, n = r - 3 * uu;
            cc = 2 * (n + (n >= p)) + q;
            bit = cc + 8 * uu;
            off = uu * 8192;
            slot = r & 3;
            wb = r < 4 ? DF + (r ? 8 * s : 0) + 7 : DG + 12 * s + r - 1;
          }
          const uint32_t fb = ab + 8 * r + (ph < 2 ? 8 : 24), wbar = bars + 8 * wb;
          const uint32_t dst = sb + (ph == 2 ? s * OFF_R1 : 0) + slot * bytes;
          const uint8_t* src = gb + cc * 24576 + off;
          uint32_t pm = ph < 2 ? 0x7fu : 0x1ffu, seen = 0;
          if (pm >> lane & 1) {
            mbar_expect(fb, bytes);
            mbar_arrive(fb, 7);
          }
          __syncwarp();
          mbar_wait(ab);
          if (elect_one()) flag_release(fl, 1u << j);
          __syncwarp();
          TL(44 + 2 * ph + s);
          do {
            const int next = __ffs(pm) - 1;
            if (!(seen >> next & 1)) {
              do seen = __ballot_sync(0xffffffffu, flag_read(fl, epoch) >> bit & 1);
              while (!(seen >> next & 1));
              asm volatile("fence.acquire.gpu;" ::: "memory");
              fence_async_global();
            }
            if (next == 0) TL(52 + 2 * ph + s);
            mbar_wait(__shfl_sync(0xffffffffu, wbar, next));
            const uint32_t ok = mbar_test(wbar) & ((pm & seen) >> lane);
            if (ok) bulk_load(dst, src, bytes, fb);
            pm &= ~__ballot_sync(0xffffffffu, ok);
          } while (pm);
        }
      }
    }
  } else {
    named_bar<0, 288>();
    asm volatile("barrier.cluster.arrive.relaxed.aligned;" ::: "memory");
    TC(tc4);
    uint32_t epoch;
    asm volatile("ld.relaxed.gpu.global.u32 %0, [%1];" : "=r"(epoch) : "l"(&scr->epoch) : "memory");
    epoch += 1;
    const int s = warp >> 2, w = warp & 3, tid = threadIdx.x & 127, c = lane & 3, g = lane >> 2;
    uint32_t sb_peer;
    asm volatile("mapa.shared::cluster.u32 %0, %1, %2;" : "=r"(sb_peer) : "r"(sb), "r"(q ^ 1));
    const int row0 = 128 * i + 64 * s + 16 * w;
    const uint32_t bs8 = bars + 64 * s, bs12 = bars + 96 * s;
    uint32_t pq[20], hp[20];
    {
      float acc[80];
      const Desc dx = mkdesc(s * 512, 0, 16, 1024, 1);
      const int srow = 16 * j + 2 * warp + (lane >> 4);
      float sm = 0.f, sq = 0.f;
      float4 u;
      auto load_res = [&]() {
        const uint32_t xa = sb + (64 * s + 16 * w + (lane & 15)) * 128;
#pragma unroll
        for (int ks = 0; ks < 5; ks++) {
          const int col = ks < 4 ? cF + 16 * ks : cR;
          ldsm4(xa + (col >> 6) * 16384 + (((((col & 63) >> 3) + (lane >> 4)) ^ (lane & 7)) << 4), hp + 4 * ks);
        }
      };
#pragma unroll
      for (int st = 0; st < 20; st++) {
        if ((st & 1) == 0 && st <= 4) mbar_wait(bars + 8 * (FX + (st >> 1)));
        mbar_wait(bars + 8 * (st < 16 ? RF + st % 5 : FE + st - 16), st < 16 ? (st / 5) & 1 : 0);
        const Desc da = dx + (st >> 1) * 1024 + (st & 1) * 4;
        const Desc db = mkdesc(0, st < 16 ? OFF_RING + (st % 5) * 12288 : (st - 16) * 12288, 4096, 1024, 1);
        wg_fence();
        wgmma_ss<160, 0, 1>(acc, da, db, st != 0);
        wgmma_ss<160, 0, 1>(acc, da + 2, db + 128, 1);
        wg_commit();
        TL0(64 + st);
        if (st == 0) { TL0(0); TS(38, tc4); TS(62, (uint32_t)tl_gt); }
        if (st == 1) asm volatile("setmaxnreg.inc.sync.aligned.u32 208;");
        if (st == 15) asm volatile("barrier.cluster.wait.aligned;" ::: "memory");
        if (st >= 3 && st <= 11 && (st & 1)) {
          const float uu[4] = {u.x, u.y, u.z, u.w};
#pragma unroll
          for (int e = 0; e < 4; e++) {
            const float a = bf_lo(__float_as_uint(uu[e])), b = bf_hi(__float_as_uint(uu[e]));
            sm += a + b;
            sq = fmaf(a, a, fmaf(b, b, sq));
          }
          asm volatile("" : "+f"(sm), "+f"(sq)::"memory");
        }
        if (st >= 2 && st <= 10 && (st & 1) == 0) {
          if (st > 4) mbar_wait(bars + 8 * (FX + st - 2));
          if (st > 2) mbar_wait(bars + 8 * (FX + st - 1));
          u = lds128(sb + (st - 2 + ((lane >> 3) & 1)) * 16384 + srow * 128 + (lane & 7) * 16);
        }
        if (st == 11 || st == 12) {
#pragma unroll
          for (int o = st == 11 ? 1 : 4; o < (st == 11 ? 4 : 16); o <<= 1) {
            sm += __shfl_xor_sync(0xffffffffu, sm, o);
            sq += __shfl_xor_sync(0xffffffffu, sq, o);
          }
        }
        if (st == 12) {
          if ((lane & 15) == 0) ll_store(scr->ln1 + 128 * i + srow, sm, sq, epoch);
          TL0(39);
        }
        if (st == 13) mbar_arrive_if0(lane, bars + 8 * CG, 1);
        if (st == 14) mbar_arrive_if0(lane, bars + 8 * ST1, 1);
        if (st == 7 && p < 2) load_res();
        if (st == 8) mbar_arrive_if0(lane, bars + 8 * XF, 1);
        if (st == 16 && p >= 2) load_res();
        if (st > 0) {
          wg_wait<1>();
          if (st <= 16) mbar_arrive_if0(lane, bars + 8 * (RE + (st - 1) % 5), 1);
        }
      }
      TL0(12);
      float accq[40];
      auto q_step = [&](int t) {
        if (t >= 7) mbar_wait(bars + 8 * (FX + 3 + t));
        mbar_wait(bars + 8 * (RF + (t + 1) % 5), ((t + 16) / 5) & 1);
        const Desc da = dx + (t < 7 ? t + 3 : t - 3) * 1024, db = mkdesc(0, OFF_RING + ((t + 1) % 5) * 12288, 4096, 512, 2);
        wg_fence();
#pragma unroll
        for (int ks = 0; ks < 4; ks++) wgmma_ss<80, 0, 1>(accq, da + 2 * ks, db + 64 * ks, 1);
        wg_commit();
        TL0(84 + t);
      };
      mbar_wait(bars + 8 * SIDE);
      float a1[2], a2[2];
      uint32_t rk[2];
#pragma unroll
      for (int r = 0; r < 2; r++) {
        const float2 st = lds64(sb + OFF_LN1 + (64 * s + 16 * w + g + 8 * r) * 8);
        a1[r] = st.x;
        a2[r] = st.x * LOG2E;
        rk[r] = rk1_frag(st.y, 0.f, c);
      }
      wg_fence();
      wgmma_rs<160, 0>(acc, rk[0], rk[1], 0, 0, mkdesc(0, OFF_RK1, 0, 128, 0), 1);
      wg_commit();
      wgmma_rs<80, 0>(accq, rk[0], rk[1], 0, 0, mkdesc(0, OFF_RK1 + 2560, 0, 128, 0), 0);
      q_step(0);
      const int hi = lane >> 4;
      const uint32_t rowoff = sb + (64 * s + 16 * w + (lane & 15)) * 16;
      const uint32_t remoff = sb_peer + (64 * s + 16 * w) * 16 + lane * 4;
      auto put_remote = [&](const uint32_t* r, uint32_t a) {
#pragma unroll
        for (int e = 0; e < 4; e++)
          asm volatile("st.async.shared::cluster.mbarrier::complete_tx::bytes.b32 [%0], %1, [%2];"
                       ::"r"(a + (e >> 1) * 2048 + (e & 1) * 128), "r"(r[e]), "r"(sb_peer + OFF_BAR + 8 * RXK) : "memory");
      };
      const int mF = 2 * (p & 1) - q, g0 = 2 * mF + hi;
      const uint32_t ka = rowoff + g0 * 2048;
      wg_wait<1>();
      reg_fence(acc);
      mbar_arrive_if0(lane, bars + 8 * KD, 1);
      mbar_arrive_remote_if0(lane, sb_peer + OFF_BAR + 8 * PX);
      TL0(1);
      uint32_t r[4], r2[4];
      if (role == 0) {
        ln_pair<true>(acc + 64, a1, a2, r);
        ln_pair<true>(acc + 72, a1, a2, r2);
        mbar_wait_cluster(bars + 8 * PX);
        put_remote(r, remoff + (q ? 0 : 6 * 2048));
        put_remote(r2, remoff + (q ? 2 * 2048 : 8 * 2048));
      } else {
        ln_pair<false>(acc + 64, a1, a2, r);
        ln_pair<false>(acc + 72, a1, a2, r2);
        const uint32_t a = rowoff + (hi + (q ? 17 : 10)) * 2048;
        mbar_wait(bars + 8 * KD);
        stsm4(a, r[0], r[1], r[2], r[3]);
        stsm4(a + 4096, r2[0], r2[1], r2[2], r2[3]);
      }
      q_step(1);
#pragma unroll
      for (int n = 0; n < 4; n++) {
        const int P = n == 0 ? 0 : n == 1 ? 3 : n - 1;
        ln_pair<true>(acc + 8 * P, a1, a2, r);
        ln_pair<false>(acc + 32 + 8 * P, a1, a2, r2);
        if (n == 0) mbar_wait(bars + 8 * KD);
        if (n < 2 && mF == (n ? 2 : -1)) {
          mbar_wait_cluster(bars + 8 * PX);
          put_remote(r, remoff + (n ? 0 : 8 * 2048));
          put_remote(r2, remoff + (n ? 10 * 2048 : 19 * 2048));
        } else {
          stsm4(ka + P * 4096, r[0], r[1], r[2], r[3]);
          stsm4(ka + P * 4096 + (g0 + 2 * P > 4 ? 11 * 2048 : 10 * 2048), r2[0], r2[1], r2[2], r2[3]);
        }
        if (n == 0) {
          wg_wait<1>();
          mbar_arrive_if0(lane, bars + 8 * (RE + 1), 1);
          mbar_arrive_if0(lane, bars + 8 * ZK, 1);
        }
        if (n == 1) q_step(2);
        if (n == 2) {
          wg_wait<1>();
          mbar_arrive_if0(lane, bars + 8 * (RE + 2), 1);
        }
      }
      sts128(rowoff + 15 * 2048, ONES, ONES, ONES, ONES);
      TL0(2);
      mbar_wait_cluster(bars + 8 * RXK);
      fence_async_smem();
      named_bar<1, 256>();
      TL0(3);
      float kv[24];
      {
        const Desc da = mkdesc(s * 640, 0, 128, 2048, 0), db = da + 1280;
        wg_fence();
#pragma unroll
        for (int kk = 0; kk < 8; kk++) wgmma_ss<48, 1, 1>(kv, da + 16 * kk, db + 16 * kk, kk != 0);
        wg_commit();
      }
      wg_wait<1>();
      mbar_arrive_if0(lane, bars + 8 * (RE + 3), 1);
      q_step(3);
      {
        wg_wait<1>();
        reg_fence(kv);
        TL0(4);
#pragma unroll
        for (int hh = 0; hh < 2; hh++) {
          const int r = 16 * w + g + 8 * hh, eb = c - 4 * s - (r < 20 ? 0 : r < 40 ? 10 : 99);
          const uint32_t a = sb + OFF_KVP + (40 * s + r) * 80 + 8 * eb;
#pragma unroll
          for (int tt = 0; tt < 6; tt++)
            asm volatile("{.reg .pred p; setp.lt.u32 p, %3, 10; @p st.shared.v2.f32 [%0], {%1, %2};}"
                         ::"r"(a + 32 * tt), "f"(kv[4 * tt + 2 * hh]), "f"(kv[4 * tt + 2 * hh + 1]), "r"(eb + 4 * tt) : "memory");
          asm volatile("{.reg .pred p; setp.lt.u32 p, %2, 40; @p st.shared.f32 [%0], %1;}"
                       ::"r"(sb + OFF_KVP + 6400 + (40 * s + r) * 4), "f"(s ? kv[2 * hh] : kv[20 + 2 * hh]), "r"(r) : "memory");
        }
        fence_async_smem();
        __syncwarp();
      }
      mbar_arrive_if0(lane, bars + 8 * RKV, 1);
      TL0(9);
#pragma unroll
      for (int t = 4; t < 10; t++) {
        q_step(t);
        wg_wait<1>();
        mbar_arrive_if0(lane, bars + 8 * (RE + t % 5), 1);
      }
      wg_wait<0>();
      reg_fence(accq);
      mbar_arrive_if0(lane, bars + 8 * RE, 1);
      TL0(13);
#pragma unroll
      for (int P = 0; P < 5; P++) ln_pair<true>(accq + 8 * P, a1, a2, pq + 4 * P);
      reg_fence(pq);
      TL0(14);
    }
    const uint32_t rs = sb + s * OFF_R1;
    const uint8_t* gout = scr->act + ((2 * i + s) * 8 + j) * 24576 + 256 * w + 4 * lane;
    const Desc drs = mkdesc(s * (OFF_R1 / 16), 0, 1024, 128, 0);
    float accg[80];
    {
      {
        float o[48];
        wg_fence();
        mbar_wait(bars + 8 * (s ? OM : KVB));
        TL0(15);
#pragma unroll
        for (int ks = 0; ks < 5; ks++)
          wgmma_rs<96, 1>(o, pq[4 * ks], pq[4 * ks + 1], pq[4 * ks + 2], pq[4 * ks + 3], mkdesc(ks < 4 ? 16 * q : -64 * q, OFF_KVB + 256 * ks, 128, 1280, 0), ks != 0);
        wg_commit();
        mbar_arrive_if0(lane | s, bars + 8 * OM, 2);
        wg_wait<0>();
        reg_fence(o);
        float inv[2][4];
#pragma unroll
        for (int hh = 0; hh < 2; hh++)
#pragma unroll
          for (int h = 0; h < 4; h++) inv[hh][h] = rcp(o[40 + 4 * (h >> 1) + 2 * hh + (h & 1)] + 1e-6f);
        if (s) mbar_wait(bars + 8 * AO);
#pragma unroll
        for (int t = 0; t < 10; t++) {
#pragma unroll
          for (int hh = 0; hh < 2; hh++) {
            const float f = t == 2 ? (c < 2 ? inv[hh][0] : inv[hh][1]) : t == 7 ? (c < 2 ? inv[hh][2] : inv[hh][3]) : inv[hh][(8 * t) / 20];
            pq[2 * t + hh] = pack2(o[4 * t + 2 * hh] * f, o[4 * t + 2 * hh + 1] * f);
            stg32(gout + t * 1024 + hh * 128, pq[2 * t + hh]);
          }
        }
        __syncwarp();
        mbar_arrive_if0(lane, bs8 + 8 * AO, 2);
        TLW(16 + s);
      }
      float acc[40];
#pragma unroll
      for (int r = 0; r < 20; r++) { acc[2 * r] = bf_lo(hp[r]); acc[2 * r + 1] = bf_hi(hp[r]); }
      reg_fence(acc);
#pragma unroll
      for (int t = 0; t < 8; t++) {
        mbar_wait(bars + 8 * (FWO + t));
        if (t) mbar_wait(bs8 + 8 * (AO + t));
        TLW(160 + 8 * s + t);
        if (t == 1) TLW(20 + s);
        const Desc da = mkdesc(0, (t - 1) * PAGE, 1024, 128, 0);
        const Desc db = mkdesc(0, 10 * PAGE + (t < 2 ? t ^ 1 : t) * 15360, 5120, 512, 2);
        wg_fence();
#pragma unroll
        for (int ks = 0; ks < 5; ks++) {
          if (t == 0) wgmma_rs<80, 1>(acc, pq[4 * ks], pq[4 * ks + 1], pq[4 * ks + 2], pq[4 * ks + 3], db + 64 * ks, 1);
          else wgmma_ss<80, 0, 1>(acc, da + 128 * ks, db + 64 * ks, 1);
        }
        wg_commit();
        if (t > 1) {
          wg_wait<1>();
          mbar_arrive_if0(lane, bs8 + 8 * (DW + t - 1), 2);
        }
      }
      wg_wait<0>();
      reg_fence(acc);
      mbar_arrive_if0(lane, bs8 + 8 * (DW + 7), 2);
      TLW(22 + s);
#pragma unroll
      for (int r = 0; r < 20; r++) {
        hp[r] = pack2(acc[2 * r], acc[2 * r + 1]);
        stg32(gout + 32 * 8 * 24576 + (r >> 1) * 1024 + (r & 1) * 128, hp[r]);
      }
      __syncwarp();
      mbar_arrive_if0(lane, bs8 + 8 * AH, 2);
      TLW(24 + s);
    }
    float accf[96];
    uint4 hs[4];
    const uint4* hsp = scr->hstat + ((2 * i + s) * 8 + 2 * c) * 64 + 16 * w + g;
    uint32_t rk[2];
    float3 gk[2];
#pragma unroll
    for (int t = 0; t < 8; t++) {
      mbar_wait(bars + 8 * (FW1 + t));
      if (t) mbar_wait(bs8 + 8 * (AH + t));
      TLW(176 + 8 * s + t);
      if (t == 1) TLW(26 + s);
      const Desc da = mkdesc(s * (4 + (t + 2) % 3 - ((t + 3) & 3)) * (PAGE / 16), ((t + 3) & 3) * PAGE, 1024, 128, 0);
      const Desc db = mkdesc(0, (7 + 3 * (t % 5)) * PAGE, 8192, 1024, 1);
      wg_fence();
#pragma unroll
      for (int ks = 0; ks < 5; ks++) {
        const Desc dk = ks < 4 ? db + 128 * ks : mkdesc(0, (7 + 3 * (t % 5)) * PAGE + 24576, 2048, 1024, 1);
        if (t == 0) wgmma_rs<192, 1>(accf, hp[4 * ks], hp[4 * ks + 1], hp[4 * ks + 2], hp[4 * ks + 3], dk, ks != 0);
        else wgmma_ss<192, 0, 1>(accf, da + 128 * ks, dk, 1);
      }
      if (t == 7) wgmma_rs<192, 0>(accf, rk[0], rk[1], 0, 0, mkdesc(0, OFF_RK1, 0, 128, 0), 1);
      wg_commit();
      if (t == 5) {
        while (__any_sync(0xffffffffu, ((hs[0].y ^ epoch) | (hs[0].w ^ epoch) | (hs[1].y ^ epoch) | (hs[1].w ^ epoch) | (hs[2].y ^ epoch) |
                                        (hs[2].w ^ epoch) | (hs[3].y ^ epoch) | (hs[3].w ^ epoch)) != 0)) {
#pragma unroll
          for (int m = 0; m < 4; m++) hs[m] = ll_load(hsp + (m >> 1) * 64 + 8 * (m & 1));
        }
#pragma unroll
        for (int hh = 0; hh < 2; hh++) {
          float sm = __uint_as_float(hs[hh].x) + __uint_as_float(hs[2 + hh].x), sq = __uint_as_float(hs[hh].z) + __uint_as_float(hs[2 + hh].z);
#pragma unroll
          for (int o = 1; o < 4; o <<= 1) {
            sm += __shfl_xor_sync(0xffffffffu, sm, o);
            sq += __shfl_xor_sync(0xffffffffu, sq, o);
          }
          gk[hh].x = sm;
          gk[hh].y = sq;
        }
      }
      if (t == 6) {
        mbar_wait(bars + 8 * SIDE2);
#pragma unroll
        for (int hh = 0; hh < 2; hh++) {
          const float mean = gk[hh].x * (1.f / 640.f), var = fmaxf(fmaf(-mean, mean, gk[hh].y * (1.f / 640.f)), 0.f) + 1e-5f;
          const float a = rsqrtf(var);
          rk[hh] = rk1_frag(-mean, var * a, c);
          gk[hh] = make_float3(0.7978845608028654f * a, 0.7978845608028654f * 0.044715f * a * a * a, 0.5f * a);
        }
      }
      if (t == 0) {
        wg_wait<0>();
        mbar_arrive_if0(lane, bs8 + 8 * DF, 2);
        float sm[2] = {0.f, 0.f}, sq[2] = {0.f, 0.f};
#pragma unroll
        for (int m = 0; m < 10; m++) {
          const float2 b = lds64(sb + OFF_B2 + (8 * m + 2 * c) * 4);
#pragma unroll
          for (int hh = 0; hh < 2; hh++) {
            const float h0 = bf_lo(hp[2 * m + hh]), h1 = bf_hi(hp[2 * m + hh]);
            sm[hh] += h0 + h1;
            sq[hh] = fmaf(h0, h0, fmaf(h1, h1, sq[hh]));
            const float v0 = b.x + h0, v1 = b.y + h1;
            const int e = 4 * m + 2 * hh;
            if (m < 8) { accg[e] = v0; accg[e + 1] = v1; accg[32 + e] = 0.f; accg[33 + e] = 0.f; }
            else { accg[e + 32] = q ? 0.f : v0; accg[e + 33] = q ? 0.f : v1; accg[e + 40] = q ? v0 : 0.f; accg[e + 41] = q ? v1 : 0.f; }
          }
        }
        reg_fence(accg);
#pragma unroll
        for (int o = 1; o < 4; o <<= 1) {
#pragma unroll
          for (int hh = 0; hh < 2; hh++) {
            sm[hh] += __shfl_xor_sync(0xffffffffu, sm[hh], o);
            sq[hh] += __shfl_xor_sync(0xffffffffu, sq[hh], o);
          }
        }
        if (c < 2) ll_store(scr->hstat + ((2 * i + s) * 8 + j) * 64 + 16 * w + g + 8 * c, c ? sm[1] : sm[0], c ? sq[1] : sq[0], epoch);
      } else if (t > 1) {
        wg_wait<1>();
        mbar_arrive_if0(lane, bs8 + 8 * (DF + t - 1), 2);
      }
      if (t == 3) {
#pragma unroll
        for (int m = 0; m < 4; m++) hs[m] = ll_load(hsp + (m >> 1) * 64 + 8 * (m & 1));
      }
    }
    wg_wait<0>();
    reg_fence(accf);
    mbar_arrive_if0(lane, bs8 + 8 * (DF + 7), 2);
    TLW(28 + s);
    uint32_t fp[48];
#pragma unroll
    for (int t = 0; t < 12; t++) {
      if (t < 3) {
#pragma unroll
        for (int e = 16 * t; e < 16 * t + 16; e++) {
          fp[e] = pack2(gelu(accf[2 * e], gk[e & 1]), gelu(accf[2 * e + 1], gk[e & 1]));
          stg32(gout + 64 * 8 * 24576 + (e >> 1) * 1024 + (e & 1) * 128, fp[e]);
        }
        __syncwarp();
        mbar_arrive_if0(lane, bs12 + 8 * (AF + t), 2);
        if (t == 2) TLW(30 + s);
      }
      mbar_wait(bars + 8 * (FW2 + t));
      if (t >= 3) mbar_wait(bs12 + 8 * (AF + t));
      TLW(192 + 12 * s + t);
      if (t == 3) TLW(32 + s);
      const Desc da = drs + ((t + 1) & 3) * 512, db = mkdesc(0, OFF_W2 + ((0x321045 >> (4 * (t % 6))) & 7) * 24576, 8192, 1024, 1);
      wg_fence();
#pragma unroll
      for (int ks = 0; ks < 4; ks++) {
        if (t < 3) wgmma_rs<160, 1>(accg, fp[16 * t + 4 * ks], fp[16 * t + 4 * ks + 1], fp[16 * t + 4 * ks + 2], fp[16 * t + 4 * ks + 3], db + 128 * ks, 1);
        else wgmma_ss<160, 0, 1>(accg, da + 128 * ks, db + 128 * ks, 1);
      }
      wg_commit();
      if (t != 0 && t != 3) {
        wg_wait<1>();
        mbar_arrive_if0(lane, bs12 + 8 * (DG + t - 1), 2);
        if (t == 7) mbar_arrive_remote_if0(lane, sb_peer + OFF_BAR + 8 * PF);
      }
      if (t == 2) {
        wg_wait<0>();
        mbar_arrive_if0(lane, bs12 + 8 * (DG + 2), 2);
      }
    }
    mbar_wait_cluster(bars + 8 * PF);
    wg_wait<0>();
    reg_fence(accg);
    mbar_arrive_if0(lane, bs12 + 8 * (DG + 11), 2);
    TLW(34 + s);
    {
      const uint32_t buf = OFF_W2 + 5 * 24576 + s * PAGE + tid * 16;
#pragma unroll
      for (int e = 0; e < 8; e++) {
        const float a = accg[64 + e], b = accg[72 + e];
        accg[64 + e] = q ? a : b;
        accg[72 + e] = q ? b : a;
      }
#pragma unroll
      for (int m = 0; m < 5; m++) {
        const float* a = accg + 32 + 8 * m;
        asm volatile("st.async.shared::cluster.mbarrier::complete_tx::bytes.v4.b32 [%0], {%1,%2,%3,%4}, [%5];"
                     ::"r"(sb_peer + buf + m * 2048), "r"(pack2(a[0], a[1])), "r"(pack2(a[2], a[3])), "r"(pack2(a[4], a[5])),
                     "r"(pack2(a[6], a[7])), "r"(sb_peer + OFF_BAR + 8 * (RX + s)) : "memory");
      }
      TLW(58 + s);
      mbar_wait(bs12 + 8 * (DG + 11));
      mbar_wait_cluster(bars + 8 * (RX + s));
      TLW(60 + s);
      float4 rx[5];
#pragma unroll
      for (int m = 0; m < 5; m++) rx[m] = lds128(sb + buf + m * 2048);
      const uint32_t stg = rs + w * 2816;
      const uint32_t sa = stg + (lane & 15) * 176 + (lane >> 4) * 16;
#pragma unroll
      for (int ks = 0; ks < 5; ks++) {
        const uint32_t u[4] = {__float_as_uint(rx[ks].x), __float_as_uint(rx[ks].y), __float_as_uint(rx[ks].z), __float_as_uint(rx[ks].w)};
        const float* a = accg + (ks < 4 ? 8 * ks : 72);
        stsm4(sa + ks * 32, pack2(a[0] + bf_lo(u[0]), a[1] + bf_hi(u[0])), pack2(a[2] + bf_lo(u[1]), a[3] + bf_hi(u[1])),
              pack2(a[4] + bf_lo(u[2]), a[5] + bf_hi(u[2])), pack2(a[6] + bf_lo(u[3]), a[7] + bf_hi(u[3])));
      }
      __syncwarp();
#pragma unroll
      for (int m = 0; m < 4; m++) rx[m] = lds128(stg + (4 * m + (lane >> 3)) * 176 + (lane & 7) * 16);
      rx[4] = lds128(stg + (lane >> 1) * 176 + 128 + (lane & 1) * 16);
      __nv_bfloat16* outp = out + (row0 + (lane >> 3)) * 640 + cF + (lane & 7) * 8;
#pragma unroll
      for (int m = 0; m < 4; m++) *reinterpret_cast<float4*>(outp + m * 4 * 640) = rx[m];
      *reinterpret_cast<float4*>(out + (row0 + (lane >> 1)) * 640 + cR + (lane & 1) * 8) = rx[4];
    }
    mbar_arrive_if0(lane, bars + 8 * END, 1);
    TLW(36 + s);
  }
}

typedef CUresult (*EncodeFn)(CUtensorMap*, CUtensorMapDataType, cuuint32_t, void*, const cuuint64_t*, const cuuint64_t*,
                             const cuuint32_t*, const cuuint32_t*, CUtensorMapInterleave, CUtensorMapSwizzle,
                             CUtensorMapL2promotion, CUtensorMapFloatOOBfill);

void make_map(EncodeFn enc, CUtensorMap* tm, const void* base, int rows, int cols, int box_rows, int box_cols, int group, int natom,
              CUtensorMapSwizzle sw) {
  const cuuint64_t dims[3] = {(cuuint64_t)(natom ? group : cols), (cuuint64_t)rows, (cuuint64_t)(cols / group)};
  const cuuint64_t strides[2] = {(cuuint64_t)cols * 2, (cuuint64_t)group * 2};
  const cuuint32_t box[3] = {(cuuint32_t)box_cols, (cuuint32_t)box_rows, (cuuint32_t)natom}, es[3] = {1, 1, 1};
  enc(tm, CU_TENSOR_MAP_DATA_TYPE_BFLOAT16, natom ? 3 : 2, const_cast<void*>(base), dims, strides, box, es,
      CU_TENSOR_MAP_INTERLEAVE_NONE, sw, CU_TENSOR_MAP_L2_PROMOTION_L2_128B, CU_TENSOR_MAP_FLOAT_OOB_FILL_NONE);
}

}

extern "C" void kernel_launch(void* const* d_in, const int* in_sizes, int n_in, void* d_out, int out_size) {
  const __nv_bfloat16* x = (const __nv_bfloat16*)d_in[0];
  const __nv_bfloat16* wqkv = (const __nv_bfloat16*)d_in[1];
  const __nv_bfloat16* wo = (const __nv_bfloat16*)d_in[2];
  const __nv_bfloat16* w1 = (const __nv_bfloat16*)d_in[4];
  const __nv_bfloat16* b1 = (const __nv_bfloat16*)d_in[5];
  const __nv_bfloat16* w2 = (const __nv_bfloat16*)d_in[6];
  const __nv_bfloat16* b2 = (const __nv_bfloat16*)d_in[7];

  void* fn = nullptr;
  cudaDriverEntryPointQueryResult qr;
  cudaGetDriverEntryPoint("cuTensorMapEncodeTiled", &fn, cudaEnableDefault, &qr);
  EncodeFn enc = (EncodeFn)fn;
  const CUtensorMapSwizzle S128 = CU_TENSOR_MAP_SWIZZLE_128B, S64 = CU_TENSOR_MAP_SWIZZLE_64B;
  Maps maps;
  make_map(enc, &maps.m[M_X], x, 2048, 640, 128, 64, 64, 0, S128);
  make_map(enc, &maps.m[M_KVF], wqkv, 640, 1920, 32, 64, 640, 2, S128);
  make_map(enc, &maps.m[M_KVH], wqkv, 640, 1920, 32, 32, 64, 0, S128);
  make_map(enc, &maps.m[M_Q2], wqkv, 640, 1920, 64, 32, 32, 2, S64);
  make_map(enc, &maps.m[M_QR], wqkv, 640, 1920, 64, 16, 64, 0, S64);
  make_map(enc, &maps.m[M_WO2], wo, 640, 640, 80, 32, 32, 2, S64);
  make_map(enc, &maps.m[M_WOR], wo, 640, 640, 80, 16, 64, 0, S64);
  make_map(enc, &maps.m[M_W1], w1, 640, 1536, 64, 64, 64, 3, S128);
  make_map(enc, &maps.m[M_W1R], w1, 640, 1536, 16, 64, 64, 3, S128);
  make_map(enc, &maps.m[M_W2F], w2, 1536, 640, 64, 64, 64, 0, S128);
  make_map(enc, &maps.m[M_W2H], w2, 1536, 640, 64, 32, 64, 0, S128);
  cudaFuncSetAttribute(fused_block_kernel, cudaFuncAttributeMaxDynamicSharedMemorySize, SMEM_BYTES);
  void* scr = nullptr;
  cudaGetSymbolAddress(&scr, g_scratch);
  fused_block_kernel<<<128, 384, SMEM_BYTES>>>((Scratch*)scr, wqkv, wo, w1, w2, b2, b1, (__nv_bfloat16*)d_out, maps);
}
```
